```python
import torch

def _softmax(x, axis=-1):
    return torch.softmax(x, dim=axis)
def _gelu(x):
    return torch.nn.functional.gelu(x, approximate="tanh")
def _silu(x):
    return torch.nn.functional.silu(x)
def _sigmoid(x):
    return torch.sigmoid(x)
def _layernorm(x, axis=-1, eps=1e-5):
    m = x.mean(dim=axis, keepdim=True)
    v = x.var(dim=axis, keepdim=True, unbiased=False)
    return (x - m) / torch.sqrt(v + eps)
def _scatter_add(tgt, idx, src, axis=0):
    return tgt.clone().index_add_(axis, idx, src)
def _segment_sum(src, seg, n):
    out = torch.zeros((n,) + src.shape[1:], dtype=src.dtype)
    return out.index_add_(0, seg, src)
def _pad(x, pw):
    flat = tuple(v for pair in reversed(pw) for v in pair)
    return torch.nn.functional.pad(x, flat)

kernel_name = 'parallel_sum__linear_attn_block__glu_gated_swiglu__prompt'

def setup_inputs():

    _w = (lambda a: (lambda t: t.to(torch.bfloat16) if t.is_floating_point() else t)(torch.as_tensor(a)))
    def _A_setup():
        B, S, D = 1, 2048, 512
        return {
            "x": _w((lambda *s: torch.randn(*s, dtype=torch.bfloat16) * 0.05)(B, S, D)),
            "wqkv": _w((lambda *s: torch.randn(*s, dtype=torch.bfloat16) * 0.05)(D, 3 * D)),
            "wo": _w((lambda *s: torch.randn(*s, dtype=torch.bfloat16) * 0.05)(D, D)),
        }
    _A_in = _A_setup()

    def _B_setup():
        B, S, D, F = 1, 2048, 512, 1792
        return {
            "x": _w((lambda *s: torch.randn(*s, dtype=torch.bfloat16) * 0.05)(B, S, D)),
            "w1": _w((lambda *s: torch.randn(*s, dtype=torch.bfloat16) * 0.2)(D, F) * (2.0 / D) ** 0.5),
            "w3": _w((lambda *s: torch.randn(*s, dtype=torch.bfloat16) * 0.2)(D, F) * (2.0 / D) ** 0.5),
            "w2": _w((lambda *s: torch.randn(*s, dtype=torch.bfloat16) * 0.2)(F, D) * (2.0 / F) ** 0.5),
        }
    _B_in = _B_setup()

    return {
        "A_x": _A_in["x"],
        "A_wqkv": _A_in["wqkv"],
        "A_wo": _A_in["wo"],
        "B_x": _B_in["x"],
        "B_w1": _B_in["w1"],
        "B_w3": _B_in["w3"],
        "B_w2": _B_in["w2"],
    }

def reference(A_x, A_wqkv, A_wo, B_x, B_w1, B_w3, B_w2):
    def _A_ref(x, wqkv, wo):
        B, S, D = x.shape
        H = 32; Dh = D // H
        qkv = (lambda x, *d: x.permute(*d))((x @ wqkv).reshape(B, S, 3, H, Dh), 2, 0, 3, 1, 4)
        q, k, v = qkv[0], qkv[1], qkv[2]
        phi = lambda t: torch.where(t > 0, t + 1, torch.exp(t)) + 1e-6
        pq, pk = phi(q), phi(k)
        kv = torch.einsum("bhsd,bhse->bhde", pk, v)
        z = torch.einsum("bhsd->bhd", pk)
        num = torch.einsum("bhqd,bhde->bhqe", pq, kv)
        den = torch.einsum("bhqd,bhd->bhq", pq, z)[..., None] + 1e-6
        o = num / den
        return (lambda x, *d: x.permute(*d))(o, 0, 2, 1, 3).reshape(B, S, D) @ wo

    def _B_ref(x, w1, w3, w2):
        gate = torch.einsum("bsd,df->bsf", x, w1)
        up = torch.einsum("bsd,df->bsf", x, w3)
        h = _silu(gate) * up
        out = torch.einsum("bsf,fd->bsd", h, w2)
        return out

    x = A_x
    xn = _layernorm(x, axis=-1)
    return x + _A_ref(xn, A_wqkv, A_wo) + _B_ref(xn, B_w1, B_w3, B_w2)
```

```cpp
#include <cuda_runtime.h>
#include <cuda_bf16.h>
#include <cuda.h>
#include <stdint.h>

namespace {

constexpr int kS = 2048, kD = 512, kF = 1792;
constexpr int kLag = 3;
constexpr uint32_t kSpinLimit = 1u << 22;

__device__ uint4    g_xbuf[16][4][9][2][4][128];
__device__ float4   g_pbuf[16][2][4][3][2][8][128];
__device__ float    g_kv[2][32][16][16];
__device__ float    g_z[2][32][16];
__device__ uint32_t g_xflag[16][4][9][2];
__device__ uint32_t g_pflag[16][2][4][3][2];
__device__ uint32_t g_kvcnt[4][32];
__device__ uint32_t g_epoch;
__device__ uint32_t g_done;

__device__ __forceinline__ uint32_t smem_u32(const void* p) { return (uint32_t)__cvta_generic_to_shared(p); }
__device__ __forceinline__ void mbar_init(uint32_t bar, uint32_t cnt) {
  asm volatile("mbarrier.init.shared::cta.b64 [%0], %1;" ::"r"(bar), "r"(cnt) : "memory");
}
__device__ __forceinline__ void mbar_expect_tx(uint32_t bar, uint32_t bytes) {
  asm volatile("mbarrier.arrive.expect_tx.shared::cta.b64 _, [%0], %1;" ::"r"(bar), "r"(bytes) : "memory");
}
__device__ __forceinline__ void mbar_arrive(uint32_t bar) {
  asm volatile("mbarrier.arrive.shared::cta.b64 _, [%0];" ::"r"(bar) : "memory");
}
__device__ __forceinline__ void mbar_wait(uint32_t bar, uint32_t parity) {
  asm volatile(
      "{\n.reg .pred p;\n"
      "LAB_WAIT:\n"
      "mbarrier.try_wait.parity.shared::cta.b64 p, [%0], %1;\n"
      "@p bra DONE;\n"
      "bra LAB_WAIT;\n"
      "DONE:\n}" ::"r"(bar), "r"(parity) : "memory");
}
__device__ __forceinline__ void tma_load_2d(uint32_t dst, const CUtensorMap* tm, uint32_t bar, int c0, int c1) {
  asm volatile(
      "cp.async.bulk.tensor.2d.shared::cluster.global.mbarrier::complete_tx::bytes [%0], [%1, {%3, %4}], [%2];" ::"r"(dst),
      "l"(tm), "r"(bar), "r"(c0), "r"(c1)
      : "memory");
}
__device__ __forceinline__ void prefetch_tmap(const CUtensorMap* tm) {
  asm volatile("prefetch.tensormap [%0];" ::"l"(tm) : "memory");
}
__device__ __forceinline__ void wgmma_fence() { asm volatile("wgmma.fence.sync.aligned;" ::: "memory"); }
__device__ __forceinline__ void wgmma_commit() { asm volatile("wgmma.commit_group.sync.aligned;" ::: "memory"); }
template <int N>
__device__ __forceinline__ void wgmma_wait() { asm volatile("wgmma.wait_group.sync.aligned %0;" ::"n"(N) : "memory"); }
__device__ __forceinline__ void bar_sync(int id, int n) { asm volatile("bar.sync %0, %1;" ::"r"(id), "r"(n) : "memory"); }
__device__ __forceinline__ void bar_arrive(int id, int n) { asm volatile("bar.arrive %0, %1;" ::"r"(id), "r"(n) : "memory"); }
__device__ __forceinline__ void fence_proxy_async() { asm volatile("fence.proxy.async.shared::cta;" ::: "memory"); }

__device__ __forceinline__ uint32_t ld_acquire(const uint32_t* p) {
  uint32_t v;
  asm volatile("ld.acquire.gpu.global.u32 %0, [%1];" : "=r"(v) : "l"(p) : "memory");
  return v;
}
__device__ __forceinline__ void st_relaxed(uint32_t* p, uint32_t v) {
  asm volatile("st.relaxed.gpu.global.u32 [%0], %1;" ::"l"(p), "r"(v) : "memory");
}
__device__ __forceinline__ void wait_flag_eq(const uint32_t* p, uint32_t val) {
  uint32_t it = 0;
  while (ld_acquire(p) != val) {
    if (++it > kSpinLimit) break;
  }
}
__device__ __forceinline__ void wait_count_ge(const uint32_t* p, uint32_t val) {
  uint32_t it = 0;
  while ((int32_t)(ld_acquire(p) - val) < 0) {
    __nanosleep(64);
    if (++it > kSpinLimit) break;
  }
}
__device__ __forceinline__ uint4 ldg_cg_u4(const void* p) {
  uint4 v;
  asm volatile("ld.global.cg.v4.u32 {%0,%1,%2,%3}, [%4];" : "=r"(v.x), "=r"(v.y), "=r"(v.z), "=r"(v.w) : "l"(p) : "memory");
  return v;
}
__device__ __forceinline__ float4 ldg_cg_f4(const void* p) {
  float4 v;
  asm volatile("ld.global.cg.v4.f32 {%0,%1,%2,%3}, [%4];" : "=f"(v.x), "=f"(v.y), "=f"(v.z), "=f"(v.w) : "l"(p) : "memory");
  return v;
}
__device__ __forceinline__ void stg_u4(void* p, uint32_t a, uint32_t b, uint32_t c, uint32_t d) {
  asm volatile("st.global.v4.u32 [%0], {%1,%2,%3,%4};" ::"l"(p), "r"(a), "r"(b), "r"(c), "r"(d) : "memory");
}
__device__ __forceinline__ void stg_f4(void* p, float a, float b, float c, float d) {
  asm volatile("st.global.v4.f32 [%0], {%1,%2,%3,%4};" ::"l"(p), "f"(a), "f"(b), "f"(c), "f"(d) : "memory");
}
__device__ __forceinline__ void sts_u4(uint32_t addr, uint32_t a, uint32_t b, uint32_t c, uint32_t d) {
  asm volatile("st.shared.v4.u32 [%0], {%1,%2,%3,%4};" ::"r"(addr), "r"(a), "r"(b), "r"(c), "r"(d) : "memory");
}
__device__ __forceinline__ void lds_u4(uint32_t addr, uint32_t& a, uint32_t& b, uint32_t& c, uint32_t& d) {
  asm volatile("ld.shared.v4.u32 {%0,%1,%2,%3}, [%4];" : "=r"(a), "=r"(b), "=r"(c), "=r"(d) : "r"(addr) : "memory");
}
__device__ __forceinline__ uint32_t lds_u32(uint32_t addr) {
  uint32_t v;
  asm volatile("ld.shared.u32 %0, [%1];" : "=r"(v) : "r"(addr) : "memory");
  return v;
}
__device__ __forceinline__ void ldmatrix_x4(uint32_t addr, uint32_t& a, uint32_t& b, uint32_t& c, uint32_t& d) {
  asm volatile("ldmatrix.sync.aligned.m8n8.x4.shared.b16 {%0,%1,%2,%3}, [%4];" : "=r"(a), "=r"(b), "=r"(c), "=r"(d) : "r"(addr) : "memory");
}
__device__ __forceinline__ void ldmatrix_x4_trans(uint32_t addr, uint32_t& a, uint32_t& b, uint32_t& c, uint32_t& d) {
  asm volatile("ldmatrix.sync.aligned.m8n8.x4.trans.shared.b16 {%0,%1,%2,%3}, [%4];" : "=r"(a), "=r"(b), "=r"(c), "=r"(d) : "r"(addr) : "memory");
}
__device__ __forceinline__ void stmatrix_x4(uint32_t addr, uint32_t a, uint32_t b, uint32_t c, uint32_t d) {
  asm volatile("stmatrix.sync.aligned.m8n8.x4.shared.b16 [%0], {%1,%2,%3,%4};" ::"r"(addr), "r"(a), "r"(b), "r"(c), "r"(d) : "memory");
}
__device__ __forceinline__ void mma_16816(float (&c)[4], uint32_t a0, uint32_t a1, uint32_t a2, uint32_t a3, uint32_t b0, uint32_t b1) {
  asm volatile(
      "mma.sync.aligned.m16n8k16.row.col.f32.bf16.bf16.f32 {%0,%1,%2,%3}, {%4,%5,%6,%7}, {%8,%9}, {%0,%1,%2,%3};"
      : "+f"(c[0]), "+f"(c[1]), "+f"(c[2]), "+f"(c[3])
      : "r"(a0), "r"(a1), "r"(a2), "r"(a3), "r"(b0), "r"(b1));
}
__device__ __forceinline__ uint32_t pack_bf16(float lo, float hi) {
  uint32_t r;
  asm("cvt.rn.bf16x2.f32 %0, %1, %2;" : "=r"(r) : "f"(hi), "f"(lo));
  return r;
}
__device__ __forceinline__ uint32_t hsub2_bf16(uint32_t a, uint32_t b) {
  uint32_t r;
  asm("sub.rn.bf16x2 %0, %1, %2;" : "=r"(r) : "r"(a), "r"(b));
  return r;
}
__device__ __forceinline__ float ex2f(float x) {
  float r;
  asm("ex2.approx.ftz.f32 %0, %1;" : "=f"(r) : "f"(x));
  return r;
}
__device__ __forceinline__ float rcpf(float x) {
  float r;
  asm("rcp.approx.ftz.f32 %0, %1;" : "=f"(r) : "f"(x));
  return r;
}
__device__ __forceinline__ void red_add_v2(float* p, float a, float b) {
  asm volatile("red.relaxed.gpu.global.add.v2.f32 [%0], {%1,%2};" ::"l"(p), "f"(a), "f"(b) : "memory");
}
__device__ __forceinline__ void red_add(float* p, float a) {
  asm volatile("red.relaxed.gpu.global.add.f32 [%0], %1;" ::"l"(p), "f"(a) : "memory");
}
__device__ __forceinline__ float phi_f(float t) {
  float e = ex2f(t * 1.4426950408889634f);
  return (t > 0.f ? t + 1.f : e) + 1e-6f;
}

#define R8(a, o) "+f"(a[o + 0]), "+f"(a[o + 1]), "+f"(a[o + 2]), "+f"(a[o + 3]), "+f"(a[o + 4]), "+f"(a[o + 5]), "+f"(a[o + 6]), "+f"(a[o + 7])

__device__ __forceinline__ void wgmma_n128_rs(float (&d)[64], uint32_t a0, uint32_t a1, uint32_t a2, uint32_t a3, uint64_t descB, int scaleD) {
  asm volatile(
      "{\n.reg .pred p;\nsetp.ne.b32 p, %69, 0;\n"
      "wgmma.mma_async.sync.aligned.m64n128k16.f32.bf16.bf16 "
      "{%0,%1,%2,%3,%4,%5,%6,%7,%8,%9,%10,%11,%12,%13,%14,%15,%16,%17,%18,%19,%20,%21,%22,%23,%24,%25,%26,%27,%28,%29,%30,%31,"
      "%32,%33,%34,%35,%36,%37,%38,%39,%40,%41,%42,%43,%44,%45,%46,%47,%48,%49,%50,%51,%52,%53,%54,%55,%56,%57,%58,%59,%60,%61,%62,%63},"
      "{%64,%65,%66,%67}, %68, p, 1, 1, 1;\n}"
      : R8(d, 0), R8(d, 8), R8(d, 16), R8(d, 24), R8(d, 32), R8(d, 40), R8(d, 48), R8(d, 56)
      : "r"(a0), "r"(a1), "r"(a2), "r"(a3), "l"(descB), "r"(scaleD));
}
__device__ __forceinline__ void wgmma_n64_rs(float (&d)[32], uint32_t a0, uint32_t a1, uint32_t a2, uint32_t a3, uint64_t descB, int scaleD) {
  asm volatile(
      "{\n.reg .pred p;\nsetp.ne.b32 p, %37, 0;\n"
      "wgmma.mma_async.sync.aligned.m64n64k16.f32.bf16.bf16 "
      "{%0,%1,%2,%3,%4,%5,%6,%7,%8,%9,%10,%11,%12,%13,%14,%15,%16,%17,%18,%19,%20,%21,%22,%23,%24,%25,%26,%27,%28,%29,%30,%31},"
      "{%32,%33,%34,%35}, %36, p, 1, 1, 1;\n}"
      : R8(d, 0), R8(d, 8), R8(d, 16), R8(d, 24)
      : "r"(a0), "r"(a1), "r"(a2), "r"(a3), "l"(descB), "r"(scaleD));
}
__device__ __forceinline__ void wgmma_n72_ss_tt(float (&d)[36], uint64_t descA, uint64_t descB, int scaleD) {
  asm volatile(
      "{\n.reg .pred p;\nsetp.ne.b32 p, %38, 0;\n"
      "wgmma.mma_async.sync.aligned.m64n72k16.f32.bf16.bf16 "
      "{%0,%1,%2,%3,%4,%5,%6,%7,%8,%9,%10,%11,%12,%13,%14,%15,%16,%17,%18,%19,%20,%21,%22,%23,%24,%25,%26,%27,%28,%29,%30,%31,"
      "%32,%33,%34,%35}, %36, %37, p, 1, 1, 1, 1;\n}"
      : R8(d, 0), R8(d, 8), R8(d, 16), R8(d, 24), "+f"(d[32]), "+f"(d[33]), "+f"(d[34]), "+f"(d[35])
      : "l"(descA), "l"(descB), "r"(scaleD));
}

__device__ __forceinline__ uint64_t make_desc(uint32_t addr, uint32_t lbo) {
  return (uint64_t)((addr & 0x3FFFF) >> 4) | ((uint64_t)((lbo >> 4) & 0x3FFF) << 16) | ((uint64_t)(1024 >> 4) << 32) | (1ull << 62);
}

__device__ __forceinline__ uint32_t stage_off(int st) {
  return st < 6 ? 131072u + (uint32_t)st * 16384u : (uint32_t)(st - 6) * 65536u + 49152u;
}

constexpr int B_FULL = 0, B_EMPTY = 8, B_XFULL = 16, B_XDONE = 32, B_KVREADY = 33, B_EV = 34, B_COUNT = 34 + 16;

__global__ void __launch_bounds__(384, 1)
fused_kernel(const __grid_constant__ CUtensorMap tm_x, const __grid_constant__ CUtensorMap tm_wqkv,
             const __grid_constant__ CUtensorMap tm_w1, const __grid_constant__ CUtensorMap tm_w3,
             const __grid_constant__ CUtensorMap tm_w2, const __grid_constant__ CUtensorMap tm_wo,
             const __nv_bfloat16* __restrict__ x, __nv_bfloat16* __restrict__ out) {
  extern __shared__ uint8_t smem_raw[];
  __shared__ __align__(8) uint64_t s_bars[B_COUNT];
  __shared__ uint32_t s_epoch;
  const uint32_t sbase = (smem_u32(smem_raw) + 1023u) & ~1023u;
  const uint32_t bars = smem_u32(s_bars);
  const int tid = threadIdx.x, warp = tid >> 5, lane = tid & 31;
  const int m = blockIdx.x >> 3, r = blockIdx.x & 7, p = r >> 1, odd = r & 1;
#define BAR(i) (bars + 8u * (uint32_t)(i))

  if (tid == 256) {
    for (int i = 0; i < 8; i++) { mbar_init(BAR(B_FULL + i), 1); mbar_init(BAR(B_EMPTY + i), 2); }
    for (int i = 0; i < 16; i++) { mbar_init(BAR(B_XFULL + i), 1); mbar_init(BAR(B_EV + i), 4); }
    mbar_init(BAR(B_XDONE), 2);
    mbar_init(BAR(B_KVREADY), 1);
    asm volatile("fence.mbarrier_init.release.cluster;" ::: "memory");
    fence_proxy_async();
    for (int b = 0; b < 8; b++) {
      mbar_expect_tx(BAR(B_XFULL + b), 8192);
      tma_load_2d(sbase + b * 8192, &tm_x, BAR(B_XFULL + b), b * 64, m * 128);
    }
  } else if (tid == 288) {
    prefetch_tmap(&tm_wqkv); prefetch_tmap(&tm_w1); prefetch_tmap(&tm_w3); prefetch_tmap(&tm_w2); prefetch_tmap(&tm_wo);
  } else if (tid == 0) {
    s_epoch = *(volatile uint32_t*)&g_epoch;
  }
  __syncthreads();
  const uint32_t epoch = s_epoch;
  const uint32_t tag = epoch + 1u;
  const int par = epoch & 1;

  if (warp >= 8) {
    asm volatile("setmaxnreg.dec.sync.aligned.u32 40;");
    if (warp == 8) {
      if (lane == 0) {
        for (int t = 0; t < 5; t++) {
          const CUtensorMap *ta, *tb;
          int ca, cb;
          if (!odd) {
            if (t < 4) { ta = &tm_w1; tb = &tm_w3; ca = cb = (7 * p + t) * 64; }
            else { ta = tb = &tm_wqkv; ca = 128 * p; cb = 128 * p + 64; }
          } else {
            if (t < 2) { ta = tb = &tm_wqkv; ca = 512 + (2 * p + t) * 64; cb = 1024 + (2 * p + t) * 64; }
            else { ta = &tm_w1; tb = &tm_w3; ca = cb = (7 * p + 4 + (t - 2)) * 64; }
          }
          for (int k = 0; k < 8; k++) {
            if (t == 0 && k == 2) {
              for (int b = 0; b < 8; b++) {
                mbar_expect_tx(BAR(B_XFULL + 8 + b), 8192);
                tma_load_2d(sbase + 65536 + b * 8192, &tm_x, BAR(B_XFULL + 8 + b), b * 64, m * 128 + 64);
              }
            }
            mbar_wait(BAR(B_EMPTY + k), k < 6 ? ((t & 1) ^ 1) : (t & 1));
            mbar_expect_tx(BAR(B_FULL + k), 16384);
            uint32_t dst = sbase + stage_off(k);
            tma_load_2d(dst, ta, BAR(B_FULL + k), ca, k * 64);
            tma_load_2d(dst + 8192, tb, BAR(B_FULL + k), cb, k * 64);
          }
        }
        for (int i = 0; i < 36; i++) {
          const int j = i >> 1, st = j & 7, n = 5 + (j >> 3);
          const int bi = i / 9, kb = i - bi * 9;
          if ((i & 1) == 0) {
            mbar_wait(BAR(B_EMPTY + st), st < 6 ? ((n & 1) ^ 1) : (n & 1));
            mbar_expect_tx(BAR(B_FULL + st), 16384);
          }
          const int col = odd * 256 + ((p + 1 + bi) & 3) * 64;
          const CUtensorMap* tmk;
          int row;
          if (!odd) {
            if (kb < 4) { tmk = &tm_w2; row = (7 * p + kb) * 64; }
            else if (kb < 6) { tmk = &tm_wo; row = (2 * p + kb - 4) * 64; }
            else { tmk = &tm_w2; row = (7 * p + 4 + kb - 6) * 64; }
          } else {
            if (kb < 3) { tmk = &tm_w2; row = (7 * p + 4 + kb) * 64; }
            else if (kb < 7) { tmk = &tm_w2; row = (7 * p + kb - 3) * 64; }
            else { tmk = &tm_wo; row = (2 * p + kb - 7) * 64; }
          }
          tma_load_2d(sbase + stage_off(st) + (i & 1) * 8192, tmk, BAR(B_FULL + st), col, row);
        }
      }
    } else if (warp <= 10) {
      if (lane == 0) {
        const int w = warp - 9;
        for (int e = 0; e < 8; e++) {
          mbar_wait(BAR(B_EV + w * 8 + e), 0);
          __threadfence();
          if (e >= 5) {
            const int bi = e - 5;
            st_relaxed(&g_pflag[m][odd][(p + 1 + bi) & 3][bi][w], tag);
          } else if (!odd) {
            st_relaxed(&g_xflag[m][p][e][w], tag);
            if (e == 4) st_relaxed(&g_xflag[m][p][5][w], tag);
          } else {
            if (e < 2) atomicAdd(&g_kvcnt[p][0], 1u);
            else st_relaxed(&g_xflag[m][p][6 + e - 2][w], tag);
          }
        }
      }
    } else {
      if (!odd) {
        {
          const int ce = m * 4 + p;
          float* kvn = &g_kv[par ^ 1][0][0][0];
          for (int i = lane; i < 128; i += 32) kvn[ce * 128 + i] = 0.f;
          if (lane < 8) (&g_z[par ^ 1][0][0])[ce * 8 + lane] = 0.f;
        }
        mbar_wait(BAR(B_XDONE), 0);
        wait_count_ge(&g_kvcnt[p][0], 64u * tag);
        const float* kvp = &g_kv[par][8 * p][0][0];
        const uint32_t dst0 = sbase + 5 * 8192, dst1 = dst0 + 65536;
#pragma unroll 4
        for (int i = 0; i < 16; i++) {
          float4 v = ldg_cg_f4(kvp + (i * 32 + lane) * 4);
          uint32_t lo = pack_bf16(v.x, v.y), hi = pack_bf16(v.z, v.w);
          uint32_t off = (uint32_t)(i * 32 + lane) * 8u;
          asm volatile("st.shared.v2.u32 [%0], {%1,%2};" ::"r"(dst0 + off), "r"(lo), "r"(hi) : "memory");
          asm volatile("st.shared.v2.u32 [%0], {%1,%2};" ::"r"(dst1 + off), "r"(lo), "r"(hi) : "memory");
        }
        {
          float4 v = ldg_cg_f4(&g_z[par][8 * p][0] + lane * 4);
          uint32_t lo = pack_bf16(v.x, v.y), hi = pack_bf16(v.z, v.w);
          uint32_t off = 4096u + (uint32_t)lane * 8u;
          asm volatile("st.shared.v2.u32 [%0], {%1,%2};" ::"r"(dst0 + off), "r"(lo), "r"(hi) : "memory");
          asm volatile("st.shared.v2.u32 [%0], {%1,%2};" ::"r"(dst1 + off), "r"(lo), "r"(hi) : "memory");
        }
        __syncwarp();
        if (lane == 0) mbar_arrive(BAR(B_KVREADY));
      }
    }
  } else {
    asm volatile("setmaxnreg.inc.sync.aligned.u32 232;");
    const int w = warp >> 2, wq = warp & 3, t128 = tid & 127;
    const int g = lane >> 2, tq = lane & 3;
    const uint32_t area = sbase + (uint32_t)w * 65536u;
    const bool elect = (t128 == 0);
    uint32_t A[144];
    float dmean0, dmean1;

    {
      const int row = wq * 16 + (lane & 7) + ((lane >> 3) & 1) * 8;
      const uint32_t rbase = area + row * 128;
      float s0[4] = {0.f, 0.f, 0.f, 0.f}, s1[4] = {0.f, 0.f, 0.f, 0.f};
      const uint32_t ones = 0x3F803F80u;
#pragma unroll
      for (int b = 0; b < 8; b++) {
        mbar_wait(BAR(B_XFULL + w * 8 + b), 0);
#pragma unroll
        for (int kk = 0; kk < 4; kk++) {
          const int i = (b * 4 + kk) * 4;
          ldmatrix_x4(rbase + b * 8192 + (((kk * 2 + (lane >> 4)) ^ (row & 7)) << 4), A[i], A[i + 1], A[i + 2], A[i + 3]);
        }
#pragma unroll
        for (int kk = 0; kk < 4; kk++) {
          const int i = (b * 4 + kk) * 4;
          if (kk & 1) mma_16816(s1, A[i], A[i + 1], A[i + 2], A[i + 3], ones, ones);
          else mma_16816(s0, A[i], A[i + 1], A[i + 2], A[i + 3], ones, ones);
        }
      }
      const float mean0 = (s0[0] + s1[0]) * (1.f / 512.f), mean1 = (s0[2] + s1[2]) * (1.f / 512.f);
      const uint32_t m0 = pack_bf16(mean0, mean0), m1 = pack_bf16(mean1, mean1);
      dmean0 = mean0 - __uint_as_float(m0 << 16);
      dmean1 = mean1 - __uint_as_float(m1 << 16);
#pragma unroll
      for (int i = 0; i < 128; i += 2) {
        A[i] = hsub2_bf16(A[i], m0);
        A[i + 1] = hsub2_bf16(A[i + 1], m1);
      }
      bar_sync(1 + w, 128);
      if (elect) { mbar_arrive(BAR(B_EMPTY + 6)); mbar_arrive(BAR(B_EMPTY + 7)); mbar_arrive(BAR(B_XDONE)); }
    }

    float rs0 = 0.f, rs1 = 0.f;

#pragma unroll 1
    for (int t = 0; t < 5; t++) {
      float acc[64];
      if (w == 1) bar_sync(3 + (t & 1), 256);
      const uint32_t ph = t & 1;
#pragma unroll
      for (int k = 0; k < 8; k++) {
        mbar_wait(BAR(B_FULL + k), ph);
        const uint64_t desc = make_desc(sbase + stage_off(k), 8192);
        wgmma_fence();
#pragma unroll
        for (int kk = 0; kk < 4; kk++) {
          const int i = (k * 4 + kk) * 4;
          wgmma_n128_rs(acc, A[i], A[i + 1], A[i + 2], A[i + 3], desc + (uint64_t)(kk * 128), (k | kk) != 0);
        }
        wgmma_commit();
        if (k == kLag && w == 0) bar_arrive(3 + (t & 1), 256);
        if (k > 0) {
          wgmma_wait<1>();
          if (elect) mbar_arrive(BAR(B_EMPTY + k - 1));
        }
      }
      wgmma_wait<0>();
      if (elect) mbar_arrive(BAR(B_EMPTY + 7));

      if (t == 0) {
        float q0[4] = {0.f, 0.f, 0.f, 0.f}, q1[4] = {0.f, 0.f, 0.f, 0.f};
#pragma unroll
        for (int i = 0; i < 128; i += 4) {
          mma_16816(q0, A[i], A[i + 1], A[i + 2], A[i + 3], A[i], A[i + 2]);
          mma_16816(q1, A[i], A[i + 1], A[i + 2], A[i + 3], A[i + 1], A[i + 3]);
        }
        float v0 = (g & 1) ? q0[1] : q0[0];
        float v1 = (g & 1) ? q1[3] : q1[2];
        const int src = 4 * g + (g >> 1);
        v0 = __shfl_sync(0xffffffffu, v0, src);
        v1 = __shfl_sync(0xffffffffu, v1, src);
        v0 = fmaxf(v0 * (1.f / 512.f) - dmean0 * dmean0, 0.f);
        v1 = fmaxf(v1 * (1.f / 512.f) - dmean1 * dmean1, 0.f);
        rs0 = rsqrtf(v0 + 1e-5f);
        rs1 = rsqrtf(v1 + 1e-5f);
      }

      const bool is_kv = odd && t < 2;
      const bool is_q = !odd && t == 4;
      if (is_kv) {
        const uint32_t pkb = area + 3 * 8192, vb = area + 4 * 8192, oneb = area + 5 * 8192;
        if (t == 0) sts_u4(oneb + t128 * 16, 0x3F803F80u, 0x3F803F80u, 0x3F803F80u, 0x3F803F80u);
        const int srow = wq * 16 + (lane & 7) + ((lane >> 3) & 1) * 8;
#pragma unroll
        for (int jj = 0; jj < 4; jj++) {
          const int a = jj * 8;
          uint32_t r0 = pack_bf16(phi_f(acc[a] * rs0), phi_f(acc[a + 1] * rs0));
          uint32_t r1 = pack_bf16(phi_f(acc[a + 2] * rs1), phi_f(acc[a + 3] * rs1));
          uint32_t r2 = pack_bf16(phi_f(acc[a + 4] * rs0), phi_f(acc[a + 5] * rs0));
          uint32_t r3 = pack_bf16(phi_f(acc[a + 6] * rs1), phi_f(acc[a + 7] * rs1));
          const uint32_t off = srow * 128 + (((jj * 2 + (lane >> 4)) ^ (srow & 7)) << 4);
          stmatrix_x4(pkb + off, r0, r1, r2, r3);
          const int b = 32 + a;
          r0 = pack_bf16(acc[b] * rs0, acc[b + 1] * rs0);
          r1 = pack_bf16(acc[b + 2] * rs1, acc[b + 3] * rs1);
          r2 = pack_bf16(acc[b + 4] * rs0, acc[b + 5] * rs0);
          r3 = pack_bf16(acc[b + 6] * rs1, acc[b + 7] * rs1);
          stmatrix_x4(vb + off, r0, r1, r2, r3);
        }
        fence_proxy_async();
        bar_sync(1 + w, 128);
        float kv[36];
        wgmma_fence();
#pragma unroll
        for (int kk = 0; kk < 4; kk++) {
          wgmma_n72_ss_tt(kv, make_desc(pkb + kk * 2048, 0), make_desc(vb + kk * 2048, 8192 - kk * 2048), kk != 0);
        }
        wgmma_commit();
        wgmma_wait<0>();
        float c[8];
#pragma unroll
        for (int i = 0; i < 8; i++)
          c[i] = wq == 0 ? kv[i] : (wq == 1 ? kv[8 + i] : (wq == 2 ? kv[16 + i] : kv[24 + i]));
        const int head = (2 * p + t) * 4 + wq;
        float* kvp = &g_kv[par][head][0][0];
        red_add_v2(kvp + g * 16 + 2 * tq, c[0], c[1]);
        red_add_v2(kvp + (g + 8) * 16 + 2 * tq, c[2], c[3]);
        red_add_v2(kvp + g * 16 + 8 + 2 * tq, c[4], c[5]);
        red_add_v2(kvp + (g + 8) * 16 + 8 + 2 * tq, c[6], c[7]);
        if (tq == 0) {
          red_add(&g_z[par][head][g], kv[32]);
          red_add(&g_z[par][head][g + 8], kv[34]);
        }
        bar_sync(1 + w, 128);
      } else if (is_q) {
        mbar_wait(BAR(B_KVREADY), 0);
        const uint32_t kvb = area + 5 * 8192;
        uint32_t Bf[8][6];
#pragma unroll
        for (int hh = 0; hh < 8; hh++) {
          const uint32_t addr = kvb + hh * 512 + ((lane & 7) + ((lane >> 3) & 1) * 8) * 32 + (lane >> 4) * 16;
          ldmatrix_x4_trans(addr, Bf[hh][0], Bf[hh][1], Bf[hh][2], Bf[hh][3]);
          Bf[hh][4] = lds_u32(kvb + 4096 + hh * 32 + tq * 4);
          Bf[hh][5] = lds_u32(kvb + 4096 + hh * 32 + 16 + tq * 4);
        }
        bar_sync(1 + w, 128);
#pragma unroll
        for (int hh = 0; hh < 8; hh++) {
          const int a = hh * 8;
          const uint32_t a0 = pack_bf16(phi_f(acc[a] * rs0), phi_f(acc[a + 1] * rs0));
          const uint32_t a1 = pack_bf16(phi_f(acc[a + 2] * rs1), phi_f(acc[a + 3] * rs1));
          const uint32_t a2 = pack_bf16(phi_f(acc[a + 4] * rs0), phi_f(acc[a + 5] * rs0));
          const uint32_t a3 = pack_bf16(phi_f(acc[a + 6] * rs1), phi_f(acc[a + 7] * rs1));
          float n0[4] = {0.f, 0.f, 0.f, 0.f}, n1[4] = {0.f, 0.f, 0.f, 0.f}, dn[4] = {0.f, 0.f, 0.f, 0.f};
          mma_16816(n0, a0, a1, a2, a3, Bf[hh][0], Bf[hh][1]);
          mma_16816(n1, a0, a1, a2, a3, Bf[hh][2], Bf[hh][3]);
          mma_16816(dn, a0, a1, a2, a3, Bf[hh][4], Bf[hh][5]);
          const float i0 = __frcp_rn(dn[0] + 1e-6f), i1 = __frcp_rn(dn[2] + 1e-6f);
          const uint32_t o0 = pack_bf16(n0[0] * i0, n0[1] * i0), o1 = pack_bf16(n0[2] * i1, n0[3] * i1);
          const uint32_t o2 = pack_bf16(n1[0] * i0, n1[1] * i0), o3 = pack_bf16(n1[2] * i1, n1[3] * i1);
          const int slot = 4 + (hh >> 2), jj = hh & 3;
          sts_u4(area + slot * 8192 + jj * 2048 + t128 * 16, o0, o1, o2, o3);
          stg_u4(&g_xbuf[m][p][slot][w][jj][t128], o0, o1, o2, o3);
        }
      } else {
        const int slot = odd ? t - 2 : t;
        const int xslot = odd ? 4 + t : t;
        const float c0 = rs0 * -1.4426950408889634f, c1 = rs1 * -1.4426950408889634f;
        const float q0 = rs0 * rs0, q1 = rs1 * rs1;
#pragma unroll
        for (int jj = 0; jj < 4; jj++) {
          float hv[8];
#pragma unroll
          for (int i = 0; i < 8; i++) {
            const float gr = acc[jj * 8 + i], ur = acc[32 + jj * 8 + i];
            const bool hi = (i >> 1) & 1;
            const float e = ex2f(gr * (hi ? c1 : c0));
            hv[i] = gr * ur * (hi ? q1 : q0) * rcpf(1.f + e);
          }
          const uint32_t h0 = pack_bf16(hv[0], hv[1]), h1 = pack_bf16(hv[2], hv[3]);
          const uint32_t h2 = pack_bf16(hv[4], hv[5]), h3 = pack_bf16(hv[6], hv[7]);
          sts_u4(area + slot * 8192 + jj * 2048 + t128 * 16, h0, h1, h2, h3);
          stg_u4(&g_xbuf[m][p][xslot][w][jj][t128], h0, h1, h2, h3);
        }
      }
      __syncwarp();
      if (lane == 0) mbar_arrive(BAR(B_EV + w * 8 + t));
    }

    const int n_own = odd ? 3 : 6;
    const int peer0 = odd ? -3 : 0;
    auto load_a = [&](int kb) {
      if (kb < n_own) {
#pragma unroll
        for (int jj = 0; jj < 4; jj++) {
          const int i = (kb * 4 + jj) * 4;
          lds_u4(area + kb * 8192 + jj * 2048 + t128 * 16, A[i], A[i + 1], A[i + 2], A[i + 3]);
        }
      } else {
        wait_flag_eq(&g_xflag[m][p][kb + peer0][w], tag);
#pragma unroll
        for (int jj = 0; jj < 4; jj++) {
          const int i = (kb * 4 + jj) * 4;
          uint4 v = ldg_cg_u4(&g_xbuf[m][p][kb + peer0][w][jj][t128]);
          A[i] = v.x; A[i + 1] = v.y; A[i + 2] = v.z; A[i + 3] = v.w;
        }
      }
    };
#pragma unroll
    for (int kb = 0; kb < 7; kb++) load_a(kb);

    const int orow = m * 128 + w * 64 + wq * 16 + g;
    const int ocol = odd * 256 + p * 64 + 2 * tq;
    float ps[32];
#pragma unroll
    for (int bi = 0; bi < 4; bi++) {
      float acc[32];
#pragma unroll
      for (int kb = 0; kb < 9; kb++) {
        const int i = bi * 9 + kb, j = i >> 1, st = j & 7;
        if (bi == 0 && kb == 5) { load_a(7); load_a(8); }
        if ((i & 1) == 0) mbar_wait(BAR(B_FULL + st), (5 + (j >> 3)) & 1);
        const uint64_t desc = make_desc(sbase + stage_off(st) + (i & 1) * 8192, 0);
        wgmma_fence();
#pragma unroll
        for (int kk = 0; kk < 4; kk++) {
          const int a = (kb * 4 + kk) * 4;
          wgmma_n64_rs(acc, A[a], A[a + 1], A[a + 2], A[a + 3], desc + (uint64_t)(kk * 128), (kb | kk) != 0);
        }
        wgmma_commit();
        if (kb > 0) {
          wgmma_wait<1>();
          if ((i & 1) == 0 && elect) mbar_arrive(BAR(B_EMPTY + ((j - 1) & 7)));
        }
        if (bi == 3 && kb == 3) {
          wait_flag_eq(&g_pflag[m][odd][p][0][w], tag);
          wait_flag_eq(&g_pflag[m][odd][p][1][w], tag);
#pragma unroll
          for (int q = 0; q < 8; q++) {
            const float4 u = ldg_cg_f4(&g_pbuf[m][odd][p][0][w][q][t128]);
            const float4 v = ldg_cg_f4(&g_pbuf[m][odd][p][1][w][q][t128]);
            const uint32_t xa = __ldg((const uint32_t*)(x + (size_t)orow * kD + ocol + q * 8));
            const uint32_t xb = __ldg((const uint32_t*)(x + (size_t)(orow + 8) * kD + ocol + q * 8));
            ps[q * 4 + 0] = u.x + v.x + __uint_as_float(xa << 16);
            ps[q * 4 + 1] = u.y + v.y + __uint_as_float(xa & 0xffff0000u);
            ps[q * 4 + 2] = u.z + v.z + __uint_as_float(xb << 16);
            ps[q * 4 + 3] = u.w + v.w + __uint_as_float(xb & 0xffff0000u);
          }
        }
        if (bi == 3 && kb == 7) {
          wait_flag_eq(&g_pflag[m][odd][p][2][w], tag);
#pragma unroll
          for (int q = 0; q < 8; q++) {
            const float4 u = ldg_cg_f4(&g_pbuf[m][odd][p][2][w][q][t128]);
            ps[q * 4 + 0] += u.x; ps[q * 4 + 1] += u.y; ps[q * 4 + 2] += u.z; ps[q * 4 + 3] += u.w;
          }
        }
      }
      wgmma_wait<0>();
      {
        const int i = bi * 9 + 8, j = i >> 1;
        if ((i & 1) == 1 && elect) mbar_arrive(BAR(B_EMPTY + (j & 7)));
      }
      if (bi < 3) {
        float4* dst = &g_pbuf[m][odd][(p + 1 + bi) & 3][bi][w][0][t128];
#pragma unroll
        for (int q = 0; q < 8; q++) stg_f4(dst + q * 128, acc[q * 4], acc[q * 4 + 1], acc[q * 4 + 2], acc[q * 4 + 3]);
        __syncwarp();
        if (lane == 0) mbar_arrive(BAR(B_EV + w * 8 + 5 + bi));
      } else {
#pragma unroll
        for (int q = 0; q < 8; q++) {
          *(uint32_t*)(out + (size_t)orow * kD + ocol + q * 8) = pack_bf16(acc[q * 4] + ps[q * 4], acc[q * 4 + 1] + ps[q * 4 + 1]);
          *(uint32_t*)(out + (size_t)(orow + 8) * kD + ocol + q * 8) = pack_bf16(acc[q * 4 + 2] + ps[q * 4 + 2], acc[q * 4 + 3] + ps[q * 4 + 3]);
        }
      }
    }
    if (tid == 0) {
      const uint32_t old = atomicAdd(&g_done, 1u);
      if ((old & 127u) == 127u) *(volatile uint32_t*)&g_epoch = epoch + 1u;
    }
  }
#undef BAR
}

typedef CUresult (*EncodeFn)(CUtensorMap*, CUtensorMapDataType, cuuint32_t, void*, const cuuint64_t*, const cuuint64_t*,
                             const cuuint32_t*, const cuuint32_t*, CUtensorMapInterleave, CUtensorMapSwizzle,
                             CUtensorMapL2promotion, CUtensorMapFloatOOBfill);

void make_map(EncodeFn enc, CUtensorMap* tm, const void* ptr, int rows, int cols) {
  cuuint64_t gd[2] = {(cuuint64_t)cols, (cuuint64_t)rows};
  cuuint64_t gs[1] = {(cuuint64_t)cols * 2};
  cuuint32_t bd[2] = {64, 64};
  cuuint32_t es[2] = {1, 1};
  enc(tm, CU_TENSOR_MAP_DATA_TYPE_BFLOAT16, 2, const_cast<void*>(ptr), gd, gs, bd, es, CU_TENSOR_MAP_INTERLEAVE_NONE,
      CU_TENSOR_MAP_SWIZZLE_128B, CU_TENSOR_MAP_L2_PROMOTION_L2_256B, CU_TENSOR_MAP_FLOAT_OOB_FILL_NONE);
}

constexpr int kSmemBytes = 229376 + 1024;

}

extern "C" void kernel_launch(void* const* d_in, const int* in_sizes, int n_in, void* d_out, int out_size) {
  static EncodeFn enc = nullptr;
  if (!enc) {
    void* fn = nullptr;
    cudaDriverEntryPointQueryResult qr;
    cudaGetDriverEntryPoint("cuTensorMapEncodeTiled", &fn, cudaEnableDefault, &qr);
    enc = (EncodeFn)fn;
    cudaFuncSetAttribute(fused_kernel, cudaFuncAttributeMaxDynamicSharedMemorySize, kSmemBytes);
  }
  CUtensorMap tm_x, tm_wqkv, tm_w1, tm_w3, tm_w2, tm_wo;
  make_map(enc, &tm_x, d_in[0], kS, kD);
  make_map(enc, &tm_wqkv, d_in[1], kD, 3 * kD);
  make_map(enc, &tm_wo, d_in[2], kD, kD);
  make_map(enc, &tm_w1, d_in[4], kD, kF);
  make_map(enc, &tm_w3, d_in[5], kD, kF);
  make_map(enc, &tm_w2, d_in[6], kF, kD);
  fused_kernel<<<128, 384, kSmemBytes>>>(tm_x, tm_wqkv, tm_w1, tm_w3, tm_w2, tm_wo, (const __nv_bfloat16*)d_in[0],
                                         (__nv_bfloat16*)d_out);
}
```

```cpp
#include <cuda_runtime.h>
#include <cuda_bf16.h>
#include <cuda.h>
#include <stdint.h>

namespace {

constexpr int kS = 2048, kD = 512, kF = 1792;
constexpr uint32_t kSpinLimit = 1u << 22;

__device__ uint4    g_xbuf[16][4][9][2][4][128];
__device__ float4   g_pbuf[16][2][4][3][2][8][128];
__device__ float    g_kv[2][32][16][16];
__device__ float    g_z[2][32][16];
__device__ uint32_t g_xflag[16][4][9][2];
__device__ uint32_t g_pflag[16][2][4][3][2];
__device__ uint32_t g_kvcnt[4][32];
__device__ uint32_t g_epoch;
__device__ uint32_t g_done;
#define PROF(wg, i) do {} while (0)

__device__ __forceinline__ uint32_t smem_u32(const void* p) { return (uint32_t)__cvta_generic_to_shared(p); }
__device__ __forceinline__ void mbar_init(uint32_t bar, uint32_t cnt) {
  asm volatile("mbarrier.init.shared::cta.b64 [%0], %1;" ::"r"(bar), "r"(cnt) : "memory");
}
__device__ __forceinline__ void mbar_expect_tx(uint32_t bar, uint32_t bytes) {
  asm volatile("mbarrier.arrive.expect_tx.shared::cta.b64 _, [%0], %1;" ::"r"(bar), "r"(bytes) : "memory");
}
__device__ __forceinline__ void mbar_arrive(uint32_t bar) {
  asm volatile("mbarrier.arrive.shared::cta.b64 _, [%0];" ::"r"(bar) : "memory");
}
__device__ __forceinline__ void mbar_wait(uint32_t bar, uint32_t parity) {
  asm volatile(
      "{\n.reg .pred p;\n"
      "LAB_WAIT:\n"
      "mbarrier.try_wait.parity.shared::cta.b64 p, [%0], %1;\n"
      "@p bra DONE;\n"
      "bra LAB_WAIT;\n"
      "DONE:\n}" ::"r"(bar), "r"(parity) : "memory");
}
__device__ __forceinline__ void tma_load_2d(uint32_t dst, const CUtensorMap* tm, uint32_t bar, int c0, int c1) {
  asm volatile(
      "cp.async.bulk.tensor.2d.shared::cluster.global.mbarrier::complete_tx::bytes [%0], [%1, {%3, %4}], [%2];" ::"r"(dst),
      "l"(tm), "r"(bar), "r"(c0), "r"(c1)
      : "memory");
}
__device__ __forceinline__ void tma_load_2d_mc(uint32_t dst, const CUtensorMap* tm, uint32_t bar, int c0, int c1) {
  asm volatile(
      "cp.async.bulk.tensor.2d.shared::cluster.global.mbarrier::complete_tx::bytes.multicast::cluster [%0], [%1, {%3, %4}], [%2], %5;" ::"r"(dst),
      "l"(tm), "r"(bar), "r"(c0), "r"(c1), "h"((uint16_t)3)
      : "memory");
}
__device__ __forceinline__ void mbar_arrive_cluster(uint32_t bar, uint32_t cta) {
  asm volatile("{\n.reg .b32 ra;\nmapa.shared::cluster.u32 ra, %0, %1;\nmbarrier.arrive.shared::cluster.b64 _, [ra];\n}" ::"r"(bar), "r"(cta) : "memory");
}
__device__ __forceinline__ void prefetch_tmap(const CUtensorMap* tm) {
  asm volatile("prefetch.tensormap [%0];" ::"l"(tm) : "memory");
}
__device__ __forceinline__ void wgmma_fence() { asm volatile("wgmma.fence.sync.aligned;" ::: "memory"); }
__device__ __forceinline__ void wgmma_commit() { asm volatile("wgmma.commit_group.sync.aligned;" ::: "memory"); }
template <int N>
__device__ __forceinline__ void wgmma_wait() { asm volatile("wgmma.wait_group.sync.aligned %0;" ::"n"(N) : "memory"); }
__device__ __forceinline__ void bar_sync(int id, int n) { asm volatile("bar.sync %0, %1;" ::"r"(id), "r"(n) : "memory"); }
__device__ __forceinline__ void bar_arrive(int id, int n) { asm volatile("bar.arrive %0, %1;" ::"r"(id), "r"(n) : "memory"); }
__device__ __forceinline__ void fence_proxy_async() { asm volatile("fence.proxy.async.shared::cta;" ::: "memory"); }

__device__ __forceinline__ uint32_t ld_acquire(const uint32_t* p) {
  uint32_t v;
  asm volatile("ld.acquire.gpu.global.u32 %0, [%1];" : "=r"(v) : "l"(p) : "memory");
  return v;
}
__device__ __forceinline__ void st_relaxed(uint32_t* p, uint32_t v) {
  asm volatile("st.relaxed.gpu.global.u32 [%0], %1;" ::"l"(p), "r"(v) : "memory");
}
__device__ __forceinline__ void wait_flag_eq(const uint32_t* p, uint32_t val) {
  uint32_t it = 0;
  while (ld_acquire(p) != val) {
    if (++it > kSpinLimit) break;
  }
}
__device__ __forceinline__ void wait_count_ge(const uint32_t* p, uint32_t val) {
  uint32_t it = 0;
  while ((int32_t)(ld_acquire(p) - val) < 0) {
    __nanosleep(64);
    if (++it > kSpinLimit) break;
  }
}
__device__ __forceinline__ uint4 ldg_cg_u4(const void* p) {
  uint4 v;
  asm volatile("ld.global.cg.v4.u32 {%0,%1,%2,%3}, [%4];" : "=r"(v.x), "=r"(v.y), "=r"(v.z), "=r"(v.w) : "l"(p) : "memory");
  return v;
}
__device__ __forceinline__ float4 ldg_cg_f4(const void* p) {
  float4 v;
  asm volatile("ld.global.cg.v4.f32 {%0,%1,%2,%3}, [%4];" : "=f"(v.x), "=f"(v.y), "=f"(v.z), "=f"(v.w) : "l"(p) : "memory");
  return v;
}
__device__ __forceinline__ void stg_u4(void* p, uint32_t a, uint32_t b, uint32_t c, uint32_t d) {
  asm volatile("st.global.v4.u32 [%0], {%1,%2,%3,%4};" ::"l"(p), "r"(a), "r"(b), "r"(c), "r"(d) : "memory");
}
__device__ __forceinline__ void stg_f4(void* p, float a, float b, float c, float d) {
  asm volatile("st.global.v4.f32 [%0], {%1,%2,%3,%4};" ::"l"(p), "f"(a), "f"(b), "f"(c), "f"(d) : "memory");
}
__device__ __forceinline__ void sts_u4(uint32_t addr, uint32_t a, uint32_t b, uint32_t c, uint32_t d) {
  asm volatile("st.shared.v4.u32 [%0], {%1,%2,%3,%4};" ::"r"(addr), "r"(a), "r"(b), "r"(c), "r"(d) : "memory");
}
__device__ __forceinline__ void lds_u4(uint32_t addr, uint32_t& a, uint32_t& b, uint32_t& c, uint32_t& d) {
  asm volatile("ld.shared.v4.u32 {%0,%1,%2,%3}, [%4];" : "=r"(a), "=r"(b), "=r"(c), "=r"(d) : "r"(addr) : "memory");
}
__device__ __forceinline__ uint32_t lds_u32(uint32_t addr) {
  uint32_t v;
  asm volatile("ld.shared.u32 %0, [%1];" : "=r"(v) : "r"(addr) : "memory");
  return v;
}
__device__ __forceinline__ void ldmatrix_x4(uint32_t addr, uint32_t& a, uint32_t& b, uint32_t& c, uint32_t& d) {
  asm volatile("ldmatrix.sync.aligned.m8n8.x4.shared.b16 {%0,%1,%2,%3}, [%4];" : "=r"(a), "=r"(b), "=r"(c), "=r"(d) : "r"(addr) : "memory");
}
__device__ __forceinline__ void ldmatrix_x4_trans(uint32_t addr, uint32_t& a, uint32_t& b, uint32_t& c, uint32_t& d) {
  asm volatile("ldmatrix.sync.aligned.m8n8.x4.trans.shared.b16 {%0,%1,%2,%3}, [%4];" : "=r"(a), "=r"(b), "=r"(c), "=r"(d) : "r"(addr) : "memory");
}
__device__ __forceinline__ void stmatrix_x4(uint32_t addr, uint32_t a, uint32_t b, uint32_t c, uint32_t d) {
  asm volatile("stmatrix.sync.aligned.m8n8.x4.shared.b16 [%0], {%1,%2,%3,%4};" ::"r"(addr), "r"(a), "r"(b), "r"(c), "r"(d) : "memory");
}
__device__ __forceinline__ void mma_16816(float (&c)[4], uint32_t a0, uint32_t a1, uint32_t a2, uint32_t a3, uint32_t b0, uint32_t b1) {
  asm volatile(
      "mma.sync.aligned.m16n8k16.row.col.f32.bf16.bf16.f32 {%0,%1,%2,%3}, {%4,%5,%6,%7}, {%8,%9}, {%0,%1,%2,%3};"
      : "+f"(c[0]), "+f"(c[1]), "+f"(c[2]), "+f"(c[3])
      : "r"(a0), "r"(a1), "r"(a2), "r"(a3), "r"(b0), "r"(b1));
}
__device__ __forceinline__ uint32_t pack_bf16(float lo, float hi) {
  uint32_t r;
  asm("cvt.rn.bf16x2.f32 %0, %1, %2;" : "=r"(r) : "f"(hi), "f"(lo));
  return r;
}
__device__ __forceinline__ uint32_t hsub2_bf16(uint32_t a, uint32_t b) {
  uint32_t r;
  asm("sub.rn.bf16x2 %0, %1, %2;" : "=r"(r) : "r"(a), "r"(b));
  return r;
}
__device__ __forceinline__ float ex2f(float x) {
  float r;
  asm("ex2.approx.ftz.f32 %0, %1;" : "=f"(r) : "f"(x));
  return r;
}
__device__ __forceinline__ float rcpf(float x) {
  float r;
  asm("rcp.approx.ftz.f32 %0, %1;" : "=f"(r) : "f"(x));
  return r;
}
__device__ __forceinline__ void red_add_v2(float* p, float a, float b) {
  asm volatile("red.relaxed.gpu.global.add.v2.f32 [%0], {%1,%2};" ::"l"(p), "f"(a), "f"(b) : "memory");
}
__device__ __forceinline__ void red_add(float* p, float a) {
  asm volatile("red.relaxed.gpu.global.add.f32 [%0], %1;" ::"l"(p), "f"(a) : "memory");
}
__device__ __forceinline__ float phi_f(float t) {
  float e = ex2f(t * 1.4426950408889634f);
  return (t > 0.f ? t + 1.f : e) + 1e-6f;
}

#define R8(a, o) "+f"(a[o + 0]), "+f"(a[o + 1]), "+f"(a[o + 2]), "+f"(a[o + 3]), "+f"(a[o + 4]), "+f"(a[o + 5]), "+f"(a[o + 6]), "+f"(a[o + 7])

#define W8(a, o) "=f"(a[o + 0]), "=f"(a[o + 1]), "=f"(a[o + 2]), "=f"(a[o + 3]), "=f"(a[o + 4]), "=f"(a[o + 5]), "=f"(a[o + 6]), "=f"(a[o + 7])
#define D32 "{%0,%1,%2,%3,%4,%5,%6,%7,%8,%9,%10,%11,%12,%13,%14,%15,%16,%17,%18,%19,%20,%21,%22,%23,%24,%25,%26,%27,%28,%29,%30,%31}"
#define D36 "{%0,%1,%2,%3,%4,%5,%6,%7,%8,%9,%10,%11,%12,%13,%14,%15,%16,%17,%18,%19,%20,%21,%22,%23,%24,%25,%26,%27,%28,%29,%30,%31,%32,%33,%34,%35}"

constexpr uint32_t kHi128 = (1024u >> 4) | (1u << 30);
constexpr uint32_t kHi64 = (512u >> 4) | (2u << 30);
__host__ __device__ constexpr uint32_t desc_lo(uint32_t off, uint32_t lbo) { return (off >> 4) | ((lbo >> 4) << 16); }

template <bool ACC, uint32_t LO, uint32_t HI>
__device__ __forceinline__ void wgmma_n64_rs(float (&d)[32], uint32_t a0, uint32_t a1, uint32_t a2, uint32_t a3, uint32_t base) {
  if (ACC) {
    asm volatile(
        "{\n.reg .pred p;\n.reg .b32 lo;\n.reg .b64 dd;\nsetp.eq.b32 p, 0, 0;\nadd.u32 lo, %36, %37;\nmov.b64 dd, {lo, %38};\n"
        "wgmma.mma_async.sync.aligned.m64n64k16.f32.bf16.bf16 " D32 ", {%32,%33,%34,%35}, dd, p, 1, 1, 1;\n}"
        : R8(d, 0), R8(d, 8), R8(d, 16), R8(d, 24)
        : "r"(a0), "r"(a1), "r"(a2), "r"(a3), "r"(base), "n"(LO), "n"(HI));
  } else {
    asm volatile(
        "{\n.reg .pred p;\n.reg .b32 lo;\n.reg .b64 dd;\nsetp.ne.b32 p, 0, 0;\nadd.u32 lo, %36, %37;\nmov.b64 dd, {lo, %38};\n"
        "wgmma.mma_async.sync.aligned.m64n64k16.f32.bf16.bf16 " D32 ", {%32,%33,%34,%35}, dd, p, 1, 1, 1;\n}"
        : W8(d, 0), W8(d, 8), W8(d, 16), W8(d, 24)
        : "r"(a0), "r"(a1), "r"(a2), "r"(a3), "r"(base), "n"(LO), "n"(HI));
  }
}
template <bool ACC, uint32_t LOA, uint32_t LOB>
__device__ __forceinline__ void wgmma_n72_ss_tt(float (&d)[36], uint32_t base) {
  if (ACC) {
    asm volatile(
        "{\n.reg .pred p;\n.reg .b32 lo;\n.reg .b64 da, db;\nsetp.eq.b32 p, 0, 0;\n"
        "add.u32 lo, %36, %37;\nmov.b64 da, {lo, %39};\nadd.u32 lo, %36, %38;\nmov.b64 db, {lo, %39};\n"
        "wgmma.mma_async.sync.aligned.m64n72k16.f32.bf16.bf16 " D36 ", da, db, p, 1, 1, 1, 1;\n}"
        : R8(d, 0), R8(d, 8), R8(d, 16), R8(d, 24), "+f"(d[32]), "+f"(d[33]), "+f"(d[34]), "+f"(d[35])
        : "r"(base), "n"(LOA), "n"(LOB), "n"(kHi128));
  } else {
    asm volatile(
        "{\n.reg .pred p;\n.reg .b32 lo;\n.reg .b64 da, db;\nsetp.ne.b32 p, 0, 0;\n"
        "add.u32 lo, %36, %37;\nmov.b64 da, {lo, %39};\nadd.u32 lo, %36, %38;\nmov.b64 db, {lo, %39};\n"
        "wgmma.mma_async.sync.aligned.m64n72k16.f32.bf16.bf16 " D36 ", da, db, p, 1, 1, 1, 1;\n}"
        : W8(d, 0), W8(d, 8), W8(d, 16), W8(d, 24), "=f"(d[32]), "=f"(d[33]), "=f"(d[34]), "=f"(d[35])
        : "r"(base), "n"(LOA), "n"(LOB), "n"(kHi128));
  }
}

template <int V> struct IC { static constexpr int value = V; };
template <int N, int I = 0, typename F>
__device__ __forceinline__ void static_for(F&& f) {
  if constexpr (I < N) { f(IC<I>{}); static_for<N, I + 1>(f); }
}

__host__ __device__ constexpr uint32_t stage_off(int st) {
  return st < 6 ? 131072u + (uint32_t)st * 16384u : (uint32_t)(st - 6) * 65536u + 49152u;
}

constexpr int B_FULL = 0, B_EMPTY = 8, B_XFULL = 16, B_XDONE = 32, B_KVREADY = 33, B_EV = 34, B_XIN = 50, B_PIN = 62, B_COUNT = 68;
constexpr uint32_t kBarOff = 229376;
constexpr int kSmemBytes = 229376 + 1024;

enum { K_NONE = 0, K_GU = 1, K_KV = 2, K_Q = 3 };

__global__ void __cluster_dims__(2, 1, 1) __launch_bounds__(384, 1)
fused_kernel(const __grid_constant__ CUtensorMap tm_x, const __grid_constant__ CUtensorMap tm_wqkv,
             const __grid_constant__ CUtensorMap tm_w1, const __grid_constant__ CUtensorMap tm_w3,
             const __grid_constant__ CUtensorMap tm_w2, const __grid_constant__ CUtensorMap tm_wo,
             const __nv_bfloat16* __restrict__ x, __nv_bfloat16* __restrict__ out) {
  extern __shared__ __align__(1024) uint8_t smem_raw[];
  const uint32_t sbase = __shfl_sync(0xffffffffu, smem_u32(smem_raw), 0);
  const uint32_t bars = sbase + kBarOff;
  const int tid = threadIdx.x, lane = tid & 31;
  const int warp = __shfl_sync(0xffffffffu, tid >> 5, 0);
  const int cr = blockIdx.x & 1;
  const int r = (blockIdx.x >> 1) & 7, m = ((blockIdx.x >> 4) << 1) | cr, p = r >> 1, odd = r & 1;
#define BAR(i) (bars + 8u * (uint32_t)(i))
  volatile uint32_t* s_epoch = (volatile uint32_t*)(smem_raw + kBarOff + 8 * B_COUNT);

  if (tid == 256) {
    if (sbase & 1023u) __trap();
    for (int i = 0; i < 8; i++) { mbar_init(BAR(B_FULL + i), 1); mbar_init(BAR(B_EMPTY + i), 4); }
    for (int i = 0; i < 16; i++) { mbar_init(BAR(B_XFULL + i), 1); mbar_init(BAR(B_EV + i), 4); }
    for (int i = 0; i < 18; i++) mbar_init(BAR(B_XIN + i), 1);
    mbar_init(BAR(B_XDONE), 2);
    mbar_init(BAR(B_KVREADY), 1);
    asm volatile("fence.mbarrier_init.release.cluster;" ::: "memory");
    fence_proxy_async();
    for (int b = 0; b < 8; b++) {
      mbar_expect_tx(BAR(B_XFULL + b), 8192);
      tma_load_2d(sbase + b * 8192, &tm_x, BAR(B_XFULL + b), b * 64, m * 128);
    }
  } else if (tid == 288) {
    prefetch_tmap(&tm_wqkv); prefetch_tmap(&tm_w1); prefetch_tmap(&tm_w3); prefetch_tmap(&tm_w2); prefetch_tmap(&tm_wo);
  } else if (tid == 0) {
    *s_epoch = *(volatile uint32_t*)&g_epoch;
  }
  __syncthreads();
  asm volatile("barrier.cluster.arrive.release.aligned;\nbarrier.cluster.wait.acquire.aligned;" ::: "memory");
  const uint32_t epoch = *s_epoch;
  const uint32_t tag = epoch + 1u;
  const int par = epoch & 1;

  if (warp >= 8) {
    asm volatile("setmaxnreg.dec.sync.aligned.u32 24;");
    if (warp == 8) {
      if (lane == 0) {
        for (int j = 0; j < 10; j++) {
          const CUtensorMap* tm;
          int col;
          if (!odd) {
            if (j < 8) { tm = cr ? &tm_w3 : &tm_w1; col = 7 * p * 64 + j * 32; }
            else { tm = &tm_wqkv; col = 128 * p + (j - 8) * 64 + cr * 32; }
          } else {
            if (j < 4) { tm = &tm_wqkv; col = 512 + cr * 512 + 128 * p + j * 32; }
            else { tm = cr ? &tm_w3 : &tm_w1; col = (7 * p + 4) * 64 + (j - 4) * 32; }
          }
          const int t = j >> 1;
          for (int kq = 0; kq < 4; kq++) {
            const int k = (j & 1) * 4 + kq;
            if (j == 0 && kq == 2) {
              for (int b = 0; b < 8; b++) {
                mbar_expect_tx(BAR(B_XFULL + 8 + b), 8192);
                tma_load_2d(sbase + 65536 + b * 8192, &tm_x, BAR(B_XFULL + 8 + b), b * 64, m * 128 + 64);
              }
            }
            mbar_wait(BAR(B_EMPTY + k), k < 6 ? ((t & 1) ^ 1) : (t & 1));
            mbar_expect_tx(BAR(B_FULL + k), 16384);
            tma_load_2d_mc(sbase + stage_off(k) + cr * 8192, tm, BAR(B_FULL + k), col, kq * 128);
          }
        }
        for (int j = 0; j < 18; j++) {
          const int st = j & 7, n = 5 + (j >> 3);
          const int i = 2 * j + cr;
          const int bi = i / 9, kb = i - bi * 9;
          const int col = odd * 256 + ((p + 1 + bi) & 3) * 64;
          const CUtensorMap* tmk;
          int row;
          if (!odd) {
            if (kb < 4) { tmk = &tm_w2; row = (7 * p + kb) * 64; }
            else if (kb < 6) { tmk = &tm_wo; row = (2 * p + kb - 4) * 64; }
            else { tmk = &tm_w2; row = (7 * p + 4 + kb - 6) * 64; }
          } else {
            if (kb < 3) { tmk = &tm_w2; row = (7 * p + 4 + kb) * 64; }
            else if (kb < 7) { tmk = &tm_w2; row = (7 * p + kb - 3) * 64; }
            else { tmk = &tm_wo; row = (2 * p + kb - 7) * 64; }
          }
          mbar_wait(BAR(B_EMPTY + st), st < 6 ? ((n & 1) ^ 1) : (n & 1));
          mbar_expect_tx(BAR(B_FULL + st), 16384);
          tma_load_2d_mc(sbase + stage_off(st) + cr * 8192, tmk, BAR(B_FULL + st), col, row);
        }
      }
    } else if (warp <= 10) {
      if (lane == 0) {
        const int w = warp - 9;
        for (int e = 0; e < 8; e++) {
          mbar_wait(BAR(B_EV + w * 8 + e), 0);
          __threadfence();
          if (e >= 5) {
            const int bi = e - 5;
            st_relaxed(&g_pflag[m][odd][(p + 1 + bi) & 3][bi][w], tag);
          } else if (!odd) {
            st_relaxed(&g_xflag[m][p][e][w], tag);
          } else {
            if (e < 2) atomicAdd(&g_kvcnt[p][0], 1u);
            else st_relaxed(&g_xflag[m][p][6 + e - 2][w], tag);
          }
        }
      }
    } else {
      if (!odd) {
        {
          const int ce = m * 4 + p;
          float* kvn = &g_kv[par ^ 1][0][0][0];
          for (int i = lane; i < 128; i += 32) kvn[ce * 128 + i] = 0.f;
          if (lane < 8) (&g_z[par ^ 1][0][0])[ce * 8 + lane] = 0.f;
        }
        mbar_wait(BAR(B_XDONE), 0);
        wait_count_ge(&g_kvcnt[p][0], 64u * tag);
        const float* kvp = &g_kv[par][8 * p][0][0];
        const uint32_t dst0 = sbase + 5 * 8192, dst1 = dst0 + 65536;
#pragma unroll 4
        for (int i = 0; i < 16; i++) {
          float4 v = ldg_cg_f4(kvp + (i * 32 + lane) * 4);
          uint32_t lo = pack_bf16(v.x, v.y), hi = pack_bf16(v.z, v.w);
          uint32_t off = (uint32_t)(i * 32 + lane) * 8u;
          asm volatile("st.shared.v2.u32 [%0], {%1,%2};" ::"r"(dst0 + off), "r"(lo), "r"(hi) : "memory");
          asm volatile("st.shared.v2.u32 [%0], {%1,%2};" ::"r"(dst1 + off), "r"(lo), "r"(hi) : "memory");
        }
        {
          float4 v = ldg_cg_f4(&g_z[par][8 * p][0] + lane * 4);
          uint32_t lo = pack_bf16(v.x, v.y), hi = pack_bf16(v.z, v.w);
          uint32_t off = 4096u + (uint32_t)lane * 8u;
          asm volatile("st.shared.v2.u32 [%0], {%1,%2};" ::"r"(dst0 + off), "r"(lo), "r"(hi) : "memory");
          asm volatile("st.shared.v2.u32 [%0], {%1,%2};" ::"r"(dst1 + off), "r"(lo), "r"(hi) : "memory");
        }
        __syncwarp();
        if (lane == 0) mbar_arrive(BAR(B_KVREADY));
      }
      const uint32_t* flag = nullptr;
      if (lane < 12) {
        const int w = lane / 6, idx = lane - w * 6;
        if (odd ? idx < 5 : idx < 3) flag = &g_xflag[m][p][odd ? idx : 6 + idx][w];
      } else if (lane < 18) {
        const int w = (lane - 12) / 3, idx = lane - 12 - w * 3;
        flag = &g_pflag[m][odd][p][idx][w];
      }
      bool pending = flag != nullptr;
      uint32_t it = 0;
      while (__any_sync(0xffffffffu, pending)) {
        if (pending) {
          if (ld_acquire(flag) == tag || it > kSpinLimit) { mbar_arrive(BAR(B_XIN + lane)); pending = false; }
        }
        ++it;
        __nanosleep(32);
      }
    }
  } else {
    asm volatile("setmaxnreg.inc.sync.aligned.u32 240;");
    const int w = warp >> 2, wq = warp & 3, t128 = tid & 127;
    const int g = lane >> 2, tq = lane & 3;
    const uint32_t area = sbase + (uint32_t)w * 65536u;
    const bool elect = (t128 == 0);
    const uint32_t dbase = (sbase & 0x3FFFFu) >> 4;
    uint32_t A[144];
    float rs0, rs1;
    auto release = [&](int st) {
      if (elect) { mbar_arrive_cluster(BAR(B_EMPTY + st), 0); mbar_arrive_cluster(BAR(B_EMPTY + st), 1); }
    };

    {
      const int row = wq * 16 + (lane & 7) + ((lane >> 3) & 1) * 8;
      const uint32_t rbase = area + row * 128;
      float s0[4] = {0.f, 0.f, 0.f, 0.f}, q0[4] = {0.f, 0.f, 0.f, 0.f}, q1[4] = {0.f, 0.f, 0.f, 0.f};
      const uint32_t ones = 0x3F803F80u;
#pragma unroll
      for (int b = 0; b < 8; b++) {
        mbar_wait(BAR(B_XFULL + w * 8 + b), 0);
#pragma unroll
        for (int kk = 0; kk < 4; kk++) {
          const int i = (b * 4 + kk) * 4;
          ldmatrix_x4(rbase + b * 8192 + (((kk * 2 + (lane >> 4)) ^ (row & 7)) << 4), A[i], A[i + 1], A[i + 2], A[i + 3]);
        }
#pragma unroll
        for (int kk = 0; kk < 4; kk++) {
          const int i = (b * 4 + kk) * 4;
          mma_16816(s0, A[i], A[i + 1], A[i + 2], A[i + 3], ones, ones);
          mma_16816(q0, A[i], A[i + 1], A[i + 2], A[i + 3], A[i], A[i + 2]);
          mma_16816(q1, A[i], A[i + 1], A[i + 2], A[i + 3], A[i + 1], A[i + 3]);
        }
      }
      const float mean0 = s0[0] * (1.f / 512.f), mean1 = s0[2] * (1.f / 512.f);
      const uint32_t m0 = pack_bf16(mean0, mean0), m1 = pack_bf16(mean1, mean1);
#pragma unroll
      for (int i = 0; i < 128; i += 2) {
        A[i] = hsub2_bf16(A[i], m0);
        A[i + 1] = hsub2_bf16(A[i + 1], m1);
      }
      float v0 = (g & 1) ? q0[1] : q0[0];
      float v1 = (g & 1) ? q1[3] : q1[2];
      const int src = 4 * g + (g >> 1);
      v0 = __shfl_sync(0xffffffffu, v0, src);
      v1 = __shfl_sync(0xffffffffu, v1, src);
      v0 = fmaxf(v0 * (1.f / 512.f) - mean0 * mean0, 0.f);
      v1 = fmaxf(v1 * (1.f / 512.f) - mean1 * mean1, 0.f);
      rs0 = rsqrtf(v0 + 1e-5f);
      rs1 = rsqrtf(v1 + 1e-5f);
      bar_sync(1 + w, 128);
      PROF(w, 0);
      release(6); release(7);
      if (elect) mbar_arrive(BAR(B_XDONE));
    }

    auto gu_chunk = [&](float (&acc)[32], int f, int slot, int xslot, int hb) {
      const float c0 = rs0 * -1.4426950408889634f, c1 = rs1 * -1.4426950408889634f;
      const float q0 = rs0 * rs0, q1 = rs1 * rs1;
      uint32_t h[4];
#pragma unroll
      for (int i = 0; i < 4; i++) {
        const float ga = acc[f * 8 + 2 * i], gb = acc[f * 8 + 2 * i + 1];
        const float ua = acc[16 + f * 8 + 2 * i], ub = acc[16 + f * 8 + 2 * i + 1];
        const float c = (i & 1) ? c1 : c0, q = (i & 1) ? q1 : q0;
        const float da = 1.f + ex2f(fminf(ga * c, 60.f)), db = 1.f + ex2f(fminf(gb * c, 60.f));
        const float rq = rcpf(da * db) * q;
        h[i] = pack_bf16(ga * ua * (db * rq), gb * ub * (da * rq));
      }
      const int jj = hb * 2 + f;
      sts_u4(area + slot * 8192 + jj * 2048 + t128 * 16, h[0], h[1], h[2], h[3]);
      stg_u4(&g_xbuf[m][p][xslot][w][jj][t128], h[0], h[1], h[2], h[3]);
    };
    auto kv_stage = [&](float (&acc)[32], int c, int hb) {
      const int srow = wq * 16 + (lane & 7) + ((lane >> 3) & 1) * 8;
      const uint32_t base = area + (3 + c) * 8192 + srow * 128;
#pragma unroll
      for (int jj = 0; jj < 2; jj++) {
        const int a = c * 16 + jj * 8;
        uint32_t r0, r1, r2, r3;
        if (c == 0) {
          r0 = pack_bf16(phi_f(acc[a] * rs0), phi_f(acc[a + 1] * rs0));
          r1 = pack_bf16(phi_f(acc[a + 2] * rs1), phi_f(acc[a + 3] * rs1));
          r2 = pack_bf16(phi_f(acc[a + 4] * rs0), phi_f(acc[a + 5] * rs0));
          r3 = pack_bf16(phi_f(acc[a + 6] * rs1), phi_f(acc[a + 7] * rs1));
        } else {
          r0 = pack_bf16(acc[a] * rs0, acc[a + 1] * rs0);
          r1 = pack_bf16(acc[a + 2] * rs1, acc[a + 3] * rs1);
          r2 = pack_bf16(acc[a + 4] * rs0, acc[a + 5] * rs0);
          r3 = pack_bf16(acc[a + 6] * rs1, acc[a + 7] * rs1);
        }
        stmatrix_x4(base + (((hb * 4 + jj * 2 + (lane >> 4)) ^ (srow & 7)) << 4), r0, r1, r2, r3);
      }
    };
    auto q_head = [&](float (&acc)[32], int c, int slot, uint32_t b0, uint32_t b1, uint32_t b2, uint32_t b3, uint32_t z0, uint32_t z1) {
      const int a = c * 8;
      const uint32_t a0 = pack_bf16(phi_f(acc[a] * rs0), phi_f(acc[a + 1] * rs0));
      const uint32_t a1 = pack_bf16(phi_f(acc[a + 2] * rs1), phi_f(acc[a + 3] * rs1));
      const uint32_t a2 = pack_bf16(phi_f(acc[a + 4] * rs0), phi_f(acc[a + 5] * rs0));
      const uint32_t a3 = pack_bf16(phi_f(acc[a + 6] * rs1), phi_f(acc[a + 7] * rs1));
      float n0[4] = {0.f, 0.f, 0.f, 0.f}, n1[4] = {0.f, 0.f, 0.f, 0.f}, dn[4] = {0.f, 0.f, 0.f, 0.f};
      mma_16816(n0, a0, a1, a2, a3, b0, b1);
      mma_16816(n1, a0, a1, a2, a3, b2, b3);
      mma_16816(dn, a0, a1, a2, a3, z0, z1);
      const float i0 = __fdividef(1.f, dn[0] + 1e-6f), i1 = __fdividef(1.f, dn[2] + 1e-6f);
      const uint32_t o0 = pack_bf16(n0[0] * i0, n0[1] * i0), o1 = pack_bf16(n0[2] * i1, n0[3] * i1);
      const uint32_t o2 = pack_bf16(n1[0] * i0, n1[1] * i0), o3 = pack_bf16(n1[2] * i1, n1[3] * i1);
      sts_u4(area + slot * 8192 + c * 2048 + t128 * 16, o0, o1, o2, o3);
      stg_u4(&g_xbuf[m][p][slot][w][c][t128], o0, o1, o2, o3);
    };
    const uint32_t kvb = area + 5 * 8192;
    const uint32_t kvfrag = kvb + ((lane & 7) + ((lane >> 3) & 1) * 8) * 32 + (lane >> 4) * 16;
    auto signal = [&](int e) {
      __syncwarp();
      if (lane == 0) mbar_arrive(BAR(B_EV + w * 8 + e));
    };

    float accB[32];
#pragma unroll 1
    for (int t = 0; t < 5; t++) {
      float accA[32];
      const uint32_t ph = t & 1;
      const int kindP = t == 0 ? K_NONE : ((odd && t <= 2) ? K_KV : K_GU);
      const int kindC = odd ? (t < 2 ? K_KV : K_GU) : (t < 4 ? K_GU : K_Q);
      const int slotP = odd ? t - 3 : t - 1, xslotP = odd ? t + 3 : t - 1;
      const int slotC = odd ? t - 2 : t, xslotC = odd ? t + 4 : t;
      static_for<8>([&](auto kc) {
        constexpr int k = decltype(kc)::value;
        mbar_wait(BAR(B_FULL + k), ph);
        wgmma_fence();
        static_for<8>([&](auto kkc) {
          constexpr int kk = decltype(kkc)::value;
          constexpr int i = ((k & 3) * 8 + kk) * 4;
          constexpr uint32_t lo = desc_lo(stage_off(k) + kk * 1024, 8192);
          if constexpr (k < 4) wgmma_n64_rs<((k & 3) | kk) != 0, lo, kHi64>(accA, A[i], A[i + 1], A[i + 2], A[i + 3], dbase);
          else wgmma_n64_rs<((k & 3) | kk) != 0, lo, kHi64>(accB, A[i], A[i + 1], A[i + 2], A[i + 3], dbase);
        });
        wgmma_commit();
        if (k > 0) {
          wgmma_wait<1>();
          release(k - 1);
        }
        if constexpr (k < 4) {
          if (kindP == K_GU) {
            if (k == 1 || k == 2) gu_chunk(accB, k - 1, slotP, xslotP, 1);
            if (k == 2) signal(t - 1);
          } else if (kindP == K_KV) {
            if (k == 1 || k == 2) kv_stage(accB, k - 1, 1);
            if (k == 3) {
              float kvacc[36];
              fence_proxy_async();
              bar_sync(1 + w, 128);
              wgmma_fence();
              static_for<4>([&](auto kkc) {
                constexpr int kk = decltype(kkc)::value;
                wgmma_n72_ss_tt<kk != 0, desc_lo(3 * 8192 + kk * 2048, 0), desc_lo(4 * 8192 + kk * 2048, 8192 - kk * 2048)>(kvacc, dbase + w * 4096);
              });
              wgmma_commit();
              wgmma_wait<0>();
              float c[8];
#pragma unroll
              for (int i = 0; i < 8; i++)
                c[i] = wq == 0 ? kvacc[i] : (wq == 1 ? kvacc[8 + i] : (wq == 2 ? kvacc[16 + i] : kvacc[24 + i]));
              const int head = (2 * p + t - 1) * 4 + wq;
              float* kvp = &g_kv[par][head][0][0];
              red_add_v2(kvp + g * 16 + 2 * tq, c[0], c[1]);
              red_add_v2(kvp + (g + 8) * 16 + 2 * tq, c[2], c[3]);
              red_add_v2(kvp + g * 16 + 8 + 2 * tq, c[4], c[5]);
              red_add_v2(kvp + (g + 8) * 16 + 8 + 2 * tq, c[6], c[7]);
              if (tq == 0) {
                red_add(&g_z[par][head][g], kvacc[32]);
                red_add(&g_z[par][head][g + 8], kvacc[34]);
              }
              signal(t - 1);
            }
          }
        } else {
          constexpr int c = k - 4;
          if (kindC == K_GU) {
            if (c < 2) gu_chunk(accA, c, slotC, xslotC, 0);
          } else if (kindC == K_KV) {
            if (c == 0 && t == 0) sts_u4(area + 5 * 8192 + t128 * 16, 0x3F803F80u, 0x3F803F80u, 0x3F803F80u, 0x3F803F80u);
            if (c < 2) kv_stage(accA, c, 0);
          } else {
            if (c == 0) mbar_wait(BAR(B_KVREADY), 0);
            uint32_t b0, b1, b2, b3;
            ldmatrix_x4_trans(kvfrag + c * 512, b0, b1, b2, b3);
            const uint32_t z0 = lds_u32(kvb + 4096 + c * 32 + tq * 4), z1 = lds_u32(kvb + 4096 + c * 32 + 16 + tq * 4);
            q_head(accA, c, 4, b0, b1, b2, b3, z0, z1);
          }
        }
      });
      wgmma_wait<0>();
      release(7);
      PROF(w, 1 + 2 * t);
    }
    if (odd) {
      gu_chunk(accB, 0, 2, 8, 1);
      gu_chunk(accB, 1, 2, 8, 1);
    } else {
      uint32_t Bf[4][6];
#pragma unroll
      for (int c = 0; c < 4; c++) {
        ldmatrix_x4_trans(kvfrag + (4 + c) * 512, Bf[c][0], Bf[c][1], Bf[c][2], Bf[c][3]);
        Bf[c][4] = lds_u32(kvb + 4096 + (4 + c) * 32 + tq * 4);
        Bf[c][5] = lds_u32(kvb + 4096 + (4 + c) * 32 + 16 + tq * 4);
      }
      bar_sync(1 + w, 128);
#pragma unroll
      for (int c = 0; c < 4; c++) q_head(accB, c, 5, Bf[c][0], Bf[c][1], Bf[c][2], Bf[c][3], Bf[c][4], Bf[c][5]);
    }
    signal(4);
    PROF(w, 10);

    const int n_own = odd ? 3 : 6;
    auto load_a = [&](int kb) {
      if (kb < n_own) {
#pragma unroll
        for (int jj = 0; jj < 4; jj++) {
          const int i = (kb * 4 + jj) * 4;
          lds_u4(area + kb * 8192 + jj * 2048 + t128 * 16, A[i], A[i + 1], A[i + 2], A[i + 3]);
        }
      } else {
        const int xs = odd ? kb - 3 : kb;
        const int ev = odd ? (kb - 3 < 4 ? kb - 3 : 4) : kb - 6;
        mbar_wait(BAR(B_XIN + w * 6 + ev), 0);
#pragma unroll
        for (int jj = 0; jj < 4; jj++) {
          const int i = (kb * 4 + jj) * 4;
          uint4 v = ldg_cg_u4(&g_xbuf[m][p][xs][w][jj][t128]);
          A[i] = v.x; A[i + 1] = v.y; A[i + 2] = v.z; A[i + 3] = v.w;
        }
      }
    };
#pragma unroll
    for (int kb = 0; kb < 7; kb++) load_a(kb);
    PROF(w, 11);

    const int orow = m * 128 + w * 64 + wq * 16 + g;
    const int ocol = odd * 256 + p * 64 + 2 * tq;
    float ps[32];
    float acc2[2][32];
    static_for<36>([&](auto ic) {
      {
        constexpr int i = decltype(ic)::value, bi = i / 9, kb = i % 9, j = i >> 1, st = j & 7;
        if (bi == 0 && kb == 4) { load_a(7); load_a(8); }
        if ((i & 1) == 0) mbar_wait(BAR(B_FULL + st), (5 + (j >> 3)) & 1);
        wgmma_fence();
        static_for<4>([&](auto kkc) {
          constexpr int kk = decltype(kkc)::value, a = (kb * 4 + kk) * 4;
          wgmma_n64_rs<(kb | kk) != 0, desc_lo(stage_off(st) + (i & 1) * 8192 + kk * 2048, 0), kHi128>(acc2[bi & 1], A[a], A[a + 1], A[a + 2], A[a + 3], dbase);
        });
        wgmma_commit();
        if (i > 0) {
          wgmma_wait<1>();
          if ((i & 1) == 0 && j - 1 <= 9) release((j - 1) & 7);
        }
        if constexpr (bi > 0 && kb == 0) {
          float4* dst = &g_pbuf[m][odd][(p + bi) & 3][bi - 1][w][0][t128];
#pragma unroll
          for (int q = 0; q < 8; q++)
            stg_f4(dst + q * 128, acc2[(bi - 1) & 1][q * 4], acc2[(bi - 1) & 1][q * 4 + 1], acc2[(bi - 1) & 1][q * 4 + 2], acc2[(bi - 1) & 1][q * 4 + 3]);
          signal(5 + bi - 1);
          PROF(w, 12 + 2 * (bi - 1));
        }
        if (bi == 3 && kb == 2) {
          mbar_wait(BAR(B_PIN + w * 3 + 0), 0);
          mbar_wait(BAR(B_PIN + w * 3 + 1), 0);
#pragma unroll
          for (int q = 0; q < 8; q++) {
            const float4 u = ldg_cg_f4(&g_pbuf[m][odd][p][0][w][q][t128]);
            const float4 v = ldg_cg_f4(&g_pbuf[m][odd][p][1][w][q][t128]);
            const uint32_t xa = __ldg((const uint32_t*)(x + (size_t)orow * kD + ocol + q * 8));
            const uint32_t xb = __ldg((const uint32_t*)(x + (size_t)(orow + 8) * kD + ocol + q * 8));
            ps[q * 4 + 0] = u.x + v.x + __uint_as_float(xa << 16);
            ps[q * 4 + 1] = u.y + v.y + __uint_as_float(xa & 0xffff0000u);
            ps[q * 4 + 2] = u.z + v.z + __uint_as_float(xb << 16);
            ps[q * 4 + 3] = u.w + v.w + __uint_as_float(xb & 0xffff0000u);
          }
        }
        if (bi == 3 && kb == 7) {
          mbar_wait(BAR(B_PIN + w * 3 + 2), 0);
#pragma unroll
          for (int q = 0; q < 8; q++) {
            const float4 u = ldg_cg_f4(&g_pbuf[m][odd][p][2][w][q][t128]);
            ps[q * 4 + 0] += u.x; ps[q * 4 + 1] += u.y; ps[q * 4 + 2] += u.z; ps[q * 4 + 3] += u.w;
          }
        }
      }
    });
    wgmma_wait<0>();
    PROF(w, 18);
#pragma unroll
    for (int q = 0; q < 8; q++) {
      *(uint32_t*)(out + (size_t)orow * kD + ocol + q * 8) = pack_bf16(acc2[1][q * 4] + ps[q * 4], acc2[1][q * 4 + 1] + ps[q * 4 + 1]);
      *(uint32_t*)(out + (size_t)(orow + 8) * kD + ocol + q * 8) = pack_bf16(acc2[1][q * 4 + 2] + ps[q * 4 + 2], acc2[1][q * 4 + 3] + ps[q * 4 + 3]);
    }
    PROF(w, 19);
    if (tid == 0) {
      const uint32_t old = atomicAdd(&g_done, 1u);
      if ((old & 127u) == 127u) *(volatile uint32_t*)&g_epoch = epoch + 1u;
    }
  }
#undef BAR
}

typedef CUresult (*EncodeFn)(CUtensorMap*, CUtensorMapDataType, cuuint32_t, void*, const cuuint64_t*, const cuuint64_t*,
                             const cuuint32_t*, const cuuint32_t*, CUtensorMapInterleave, CUtensorMapSwizzle,
                             CUtensorMapL2promotion, CUtensorMapFloatOOBfill);

void make_map(EncodeFn enc, CUtensorMap* tm, const void* ptr, int rows, int cols, bool narrow) {
  cuuint64_t gd[2] = {(cuuint64_t)cols, (cuuint64_t)rows};
  cuuint64_t gs[1] = {(cuuint64_t)cols * 2};
  cuuint32_t bd[2] = {narrow ? 32u : 64u, narrow ? 128u : 64u};
  cuuint32_t es[2] = {1, 1};
  enc(tm, CU_TENSOR_MAP_DATA_TYPE_BFLOAT16, 2, const_cast<void*>(ptr), gd, gs, bd, es, CU_TENSOR_MAP_INTERLEAVE_NONE,
      narrow ? CU_TENSOR_MAP_SWIZZLE_64B : CU_TENSOR_MAP_SWIZZLE_128B, CU_TENSOR_MAP_L2_PROMOTION_L2_256B, CU_TENSOR_MAP_FLOAT_OOB_FILL_NONE);
}

}

extern "C" void kernel_launch(void* const* d_in, const int* in_sizes, int n_in, void* d_out, int out_size) {
  static EncodeFn enc = nullptr;
  if (!enc) {
    void* fn = nullptr;
    cudaDriverEntryPointQueryResult qr;
    cudaGetDriverEntryPoint("cuTensorMapEncodeTiled", &fn, cudaEnableDefault, &qr);
    enc = (EncodeFn)fn;
    cudaFuncSetAttribute(fused_kernel, cudaFuncAttributeMaxDynamicSharedMemorySize, kSmemBytes);
  }
  CUtensorMap tm_x, tm_wqkv, tm_w1, tm_w3, tm_w2, tm_wo;
  make_map(enc, &tm_x, d_in[0], kS, kD, false);
  make_map(enc, &tm_wqkv, d_in[1], kD, 3 * kD, true);
  make_map(enc, &tm_wo, d_in[2], kD, kD, false);
  make_map(enc, &tm_w1, d_in[4], kD, kF, true);
  make_map(enc, &tm_w3, d_in[5], kD, kF, true);
  make_map(enc, &tm_w2, d_in[6], kF, kD, false);
  fused_kernel<<<128, 384, kSmemBytes>>>(tm_x, tm_wqkv, tm_w1, tm_w3, tm_w2, tm_wo, (const __nv_bfloat16*)d_in[0],
                                         (__nv_bfloat16*)d_out);
}
```

```cpp
#include <cuda_runtime.h>
#include <cuda_bf16.h>
#include <cuda.h>
#include <stdint.h>

namespace {

constexpr int kS = 2048, kD = 512, kF = 1792;
constexpr uint32_t kSpinLimit = 1u << 22;

__device__ uint4    g_xbuf[16][4][9][2][4][128];
__device__ float4   g_pbuf[16][2][4][3][2][8][128];
__device__ float    g_kv[2][32][16][16];
__device__ float    g_z[2][32][16];
__device__ uint32_t g_xflag[16][4][9][2];
__device__ uint32_t g_pflag[16][2][4][3][2];
__device__ uint32_t g_kvcnt[4][32];
__device__ uint32_t g_epoch;
__device__ uint32_t g_done;
#define PROF(wg, i) do {} while (0)

__device__ __forceinline__ uint32_t smem_u32(const void* p) { return (uint32_t)__cvta_generic_to_shared(p); }
__device__ __forceinline__ void mbar_init(uint32_t bar, uint32_t cnt) {
  asm volatile("mbarrier.init.shared::cta.b64 [%0], %1;" ::"r"(bar), "r"(cnt) : "memory");
}
__device__ __forceinline__ void mbar_expect_tx(uint32_t bar, uint32_t bytes) {
  asm volatile("mbarrier.arrive.expect_tx.shared::cta.b64 _, [%0], %1;" ::"r"(bar), "r"(bytes) : "memory");
}
__device__ __forceinline__ void mbar_arrive(uint32_t bar) {
  asm volatile("mbarrier.arrive.shared::cta.b64 _, [%0];" ::"r"(bar) : "memory");
}
__device__ __forceinline__ void mbar_wait(uint32_t bar, uint32_t parity) {
  asm volatile(
      "{\n.reg .pred p;\n"
      "LAB_WAIT:\n"
      "mbarrier.try_wait.parity.shared::cta.b64 p, [%0], %1;\n"
      "@p bra DONE;\n"
      "bra LAB_WAIT;\n"
      "DONE:\n}" ::"r"(bar), "r"(parity) : "memory");
}
__device__ __forceinline__ void tma_load_2d(uint32_t dst, const CUtensorMap* tm, uint32_t bar, int c0, int c1) {
  asm volatile(
      "cp.async.bulk.tensor.2d.shared::cluster.global.mbarrier::complete_tx::bytes [%0], [%1, {%3, %4}], [%2];" ::"r"(dst),
      "l"(tm), "r"(bar), "r"(c0), "r"(c1)
      : "memory");
}
__device__ __forceinline__ void tma_load_2d_mc(uint32_t dst, const CUtensorMap* tm, uint32_t bar, int c0, int c1) {
  asm volatile(
      "cp.async.bulk.tensor.2d.shared::cluster.global.mbarrier::complete_tx::bytes.multicast::cluster [%0], [%1, {%3, %4}], [%2], %5;" ::"r"(dst),
      "l"(tm), "r"(bar), "r"(c0), "r"(c1), "h"((uint16_t)3)
      : "memory");
}
__device__ __forceinline__ void mbar_arrive_cluster(uint32_t bar, uint32_t cta) {
  asm volatile("{\n.reg .b32 ra;\nmapa.shared::cluster.u32 ra, %0, %1;\nmbarrier.arrive.shared::cluster.b64 _, [ra];\n}" ::"r"(bar), "r"(cta) : "memory");
}
__device__ __forceinline__ void prefetch_tmap(const CUtensorMap* tm) {
  asm volatile("prefetch.tensormap [%0];" ::"l"(tm) : "memory");
}
__device__ __forceinline__ void wgmma_fence() { asm volatile("wgmma.fence.sync.aligned;" ::: "memory"); }
__device__ __forceinline__ void wgmma_commit() { asm volatile("wgmma.commit_group.sync.aligned;" ::: "memory"); }
template <int N>
__device__ __forceinline__ void wgmma_wait() { asm volatile("wgmma.wait_group.sync.aligned %0;" ::"n"(N) : "memory"); }
__device__ __forceinline__ void bar_sync(int id, int n) { asm volatile("bar.sync %0, %1;" ::"r"(id), "r"(n) : "memory"); }
__device__ __forceinline__ void bar_arrive(int id, int n) { asm volatile("bar.arrive %0, %1;" ::"r"(id), "r"(n) : "memory"); }
__device__ __forceinline__ void fence_proxy_async() { asm volatile("fence.proxy.async.shared::cta;" ::: "memory"); }

__device__ __forceinline__ uint32_t ld_acquire(const uint32_t* p) {
  uint32_t v;
  asm volatile("ld.acquire.gpu.global.u32 %0, [%1];" : "=r"(v) : "l"(p) : "memory");
  return v;
}
__device__ __forceinline__ uint32_t ld_relaxed(const uint32_t* p) {
  uint32_t v;
  asm volatile("ld.relaxed.gpu.global.u32 %0, [%1];" : "=r"(v) : "l"(p));
  return v;
}
__device__ __forceinline__ void cluster_wait() { asm volatile("barrier.cluster.wait.aligned;" ::: "memory"); }
__device__ __forceinline__ void st_relaxed(uint32_t* p, uint32_t v) {
  asm volatile("st.relaxed.gpu.global.u32 [%0], %1;" ::"l"(p), "r"(v) : "memory");
}
__device__ __forceinline__ void wait_flag_eq(const uint32_t* p, uint32_t val) {
  uint32_t it = 0;
  while (ld_acquire(p) != val) {
    if (++it > kSpinLimit) break;
  }
}
__device__ __forceinline__ void wait_count_ge(const uint32_t* p, uint32_t val) {
  uint32_t it = 0;
  while ((int32_t)(ld_acquire(p) - val) < 0) {
    __nanosleep(64);
    if (++it > kSpinLimit) break;
  }
}
__device__ __forceinline__ uint4 ldg_cg_u4(const void* p) {
  uint4 v;
  asm volatile("ld.global.cg.v4.u32 {%0,%1,%2,%3}, [%4];" : "=r"(v.x), "=r"(v.y), "=r"(v.z), "=r"(v.w) : "l"(p) : "memory");
  return v;
}
__device__ __forceinline__ float4 ldg_cg_f4(const void* p) {
  float4 v;
  asm volatile("ld.global.cg.v4.f32 {%0,%1,%2,%3}, [%4];" : "=f"(v.x), "=f"(v.y), "=f"(v.z), "=f"(v.w) : "l"(p) : "memory");
  return v;
}
__device__ __forceinline__ void stg_u4(void* p, uint32_t a, uint32_t b, uint32_t c, uint32_t d) {
  asm volatile("st.global.v4.u32 [%0], {%1,%2,%3,%4};" ::"l"(p), "r"(a), "r"(b), "r"(c), "r"(d) : "memory");
}
__device__ __forceinline__ void stg_f4(void* p, float a, float b, float c, float d) {
  asm volatile("st.global.v4.f32 [%0], {%1,%2,%3,%4};" ::"l"(p), "f"(a), "f"(b), "f"(c), "f"(d) : "memory");
}
__device__ __forceinline__ void sts_u4(uint32_t addr, uint32_t a, uint32_t b, uint32_t c, uint32_t d) {
  asm volatile("st.shared.v4.u32 [%0], {%1,%2,%3,%4};" ::"r"(addr), "r"(a), "r"(b), "r"(c), "r"(d) : "memory");
}
__device__ __forceinline__ void lds_u4(uint32_t addr, uint32_t& a, uint32_t& b, uint32_t& c, uint32_t& d) {
  asm volatile("ld.shared.v4.u32 {%0,%1,%2,%3}, [%4];" : "=r"(a), "=r"(b), "=r"(c), "=r"(d) : "r"(addr) : "memory");
}
__device__ __forceinline__ uint32_t lds_u32(uint32_t addr) {
  uint32_t v;
  asm volatile("ld.shared.u32 %0, [%1];" : "=r"(v) : "r"(addr) : "memory");
  return v;
}
__device__ __forceinline__ void ldmatrix_x4(uint32_t addr, uint32_t& a, uint32_t& b, uint32_t& c, uint32_t& d) {
  asm volatile("ldmatrix.sync.aligned.m8n8.x4.shared.b16 {%0,%1,%2,%3}, [%4];" : "=r"(a), "=r"(b), "=r"(c), "=r"(d) : "r"(addr) : "memory");
}
__device__ __forceinline__ void ldmatrix_x4_trans(uint32_t addr, uint32_t& a, uint32_t& b, uint32_t& c, uint32_t& d) {
  asm volatile("ldmatrix.sync.aligned.m8n8.x4.trans.shared.b16 {%0,%1,%2,%3}, [%4];" : "=r"(a), "=r"(b), "=r"(c), "=r"(d) : "r"(addr) : "memory");
}
__device__ __forceinline__ void stmatrix_x4(uint32_t addr, uint32_t a, uint32_t b, uint32_t c, uint32_t d) {
  asm volatile("stmatrix.sync.aligned.m8n8.x4.shared.b16 [%0], {%1,%2,%3,%4};" ::"r"(addr), "r"(a), "r"(b), "r"(c), "r"(d) : "memory");
}
__device__ __forceinline__ void mma_16816(float (&c)[4], uint32_t a0, uint32_t a1, uint32_t a2, uint32_t a3, uint32_t b0, uint32_t b1) {
  asm volatile(
      "mma.sync.aligned.m16n8k16.row.col.f32.bf16.bf16.f32 {%0,%1,%2,%3}, {%4,%5,%6,%7}, {%8,%9}, {%0,%1,%2,%3};"
      : "+f"(c[0]), "+f"(c[1]), "+f"(c[2]), "+f"(c[3])
      : "r"(a0), "r"(a1), "r"(a2), "r"(a3), "r"(b0), "r"(b1));
}
__device__ __forceinline__ uint32_t pack_bf16(float lo, float hi) {
  uint32_t r;
  asm("cvt.rn.bf16x2.f32 %0, %1, %2;" : "=r"(r) : "f"(hi), "f"(lo));
  return r;
}
__device__ __forceinline__ uint32_t hsub2_bf16(uint32_t a, uint32_t b) {
  uint32_t r;
  asm("sub.rn.bf16x2 %0, %1, %2;" : "=r"(r) : "r"(a), "r"(b));
  return r;
}
__device__ __forceinline__ float ex2f(float x) {
  float r;
  asm("ex2.approx.ftz.f32 %0, %1;" : "=f"(r) : "f"(x));
  return r;
}
__device__ __forceinline__ float rcpf(float x) {
  float r;
  asm("rcp.approx.ftz.f32 %0, %1;" : "=f"(r) : "f"(x));
  return r;
}
__device__ __forceinline__ void red_add_v2(float* p, float a, float b) {
  asm volatile("red.relaxed.gpu.global.add.v2.f32 [%0], {%1,%2};" ::"l"(p), "f"(a), "f"(b) : "memory");
}
__device__ __forceinline__ void red_add(float* p, float a) {
  asm volatile("red.relaxed.gpu.global.add.f32 [%0], %1;" ::"l"(p), "f"(a) : "memory");
}
__device__ __forceinline__ float phi_f(float t) {
  float e = ex2f(t * 1.4426950408889634f);
  return (t > 0.f ? t + 1.f : e) + 1e-6f;
}

#define R8(a, o) "+f"(a[o + 0]), "+f"(a[o + 1]), "+f"(a[o + 2]), "+f"(a[o + 3]), "+f"(a[o + 4]), "+f"(a[o + 5]), "+f"(a[o + 6]), "+f"(a[o + 7])

#define W8(a, o) "=f"(a[o + 0]), "=f"(a[o + 1]), "=f"(a[o + 2]), "=f"(a[o + 3]), "=f"(a[o + 4]), "=f"(a[o + 5]), "=f"(a[o + 6]), "=f"(a[o + 7])
#define D32 "{%0,%1,%2,%3,%4,%5,%6,%7,%8,%9,%10,%11,%12,%13,%14,%15,%16,%17,%18,%19,%20,%21,%22,%23,%24,%25,%26,%27,%28,%29,%30,%31}"
#define D36 "{%0,%1,%2,%3,%4,%5,%6,%7,%8,%9,%10,%11,%12,%13,%14,%15,%16,%17,%18,%19,%20,%21,%22,%23,%24,%25,%26,%27,%28,%29,%30,%31,%32,%33,%34,%35}"

constexpr uint32_t kHi128 = (1024u >> 4) | (1u << 30);
constexpr uint32_t kHi64 = (512u >> 4) | (2u << 30);
__host__ __device__ constexpr uint32_t desc_lo(uint32_t off, uint32_t lbo) { return (off >> 4) | ((lbo >> 4) << 16); }

template <bool ACC, uint32_t LO, uint32_t HI>
__device__ __forceinline__ void wgmma_n64_rs(float (&d)[32], uint32_t a0, uint32_t a1, uint32_t a2, uint32_t a3, uint32_t base) {
  if (ACC) {
    asm volatile(
        "{\n.reg .pred p;\n.reg .b32 lo;\n.reg .b64 dd;\nsetp.eq.b32 p, 0, 0;\nadd.u32 lo, %36, %37;\nmov.b64 dd, {lo, %38};\n"
        "wgmma.mma_async.sync.aligned.m64n64k16.f32.bf16.bf16 " D32 ", {%32,%33,%34,%35}, dd, p, 1, 1, 1;\n}"
        : R8(d, 0), R8(d, 8), R8(d, 16), R8(d, 24)
        : "r"(a0), "r"(a1), "r"(a2), "r"(a3), "r"(base), "n"(LO), "n"(HI));
  } else {
    asm volatile(
        "{\n.reg .pred p;\n.reg .b32 lo;\n.reg .b64 dd;\nsetp.ne.b32 p, 0, 0;\nadd.u32 lo, %36, %37;\nmov.b64 dd, {lo, %38};\n"
        "wgmma.mma_async.sync.aligned.m64n64k16.f32.bf16.bf16 " D32 ", {%32,%33,%34,%35}, dd, p, 1, 1, 1;\n}"
        : W8(d, 0), W8(d, 8), W8(d, 16), W8(d, 24)
        : "r"(a0), "r"(a1), "r"(a2), "r"(a3), "r"(base), "n"(LO), "n"(HI));
  }
}
template <bool ACC, uint32_t LOA, uint32_t LOB>
__device__ __forceinline__ void wgmma_n72_ss_tt(float (&d)[36], uint32_t base) {
  if (ACC) {
    asm volatile(
        "{\n.reg .pred p;\n.reg .b32 lo;\n.reg .b64 da, db;\nsetp.eq.b32 p, 0, 0;\n"
        "add.u32 lo, %36, %37;\nmov.b64 da, {lo, %39};\nadd.u32 lo, %36, %38;\nmov.b64 db, {lo, %39};\n"
        "wgmma.mma_async.sync.aligned.m64n72k16.f32.bf16.bf16 " D36 ", da, db, p, 1, 1, 1, 1;\n}"
        : R8(d, 0), R8(d, 8), R8(d, 16), R8(d, 24), "+f"(d[32]), "+f"(d[33]), "+f"(d[34]), "+f"(d[35])
        : "r"(base), "n"(LOA), "n"(LOB), "n"(kHi128));
  } else {
    asm volatile(
        "{\n.reg .pred p;\n.reg .b32 lo;\n.reg .b64 da, db;\nsetp.ne.b32 p, 0, 0;\n"
        "add.u32 lo, %36, %37;\nmov.b64 da, {lo, %39};\nadd.u32 lo, %36, %38;\nmov.b64 db, {lo, %39};\n"
        "wgmma.mma_async.sync.aligned.m64n72k16.f32.bf16.bf16 " D36 ", da, db, p, 1, 1, 1, 1;\n}"
        : W8(d, 0), W8(d, 8), W8(d, 16), W8(d, 24), "=f"(d[32]), "=f"(d[33]), "=f"(d[34]), "=f"(d[35])
        : "r"(base), "n"(LOA), "n"(LOB), "n"(kHi128));
  }
}

template <int V> struct IC { static constexpr int value = V; };
template <int N, int I = 0, typename F>
__device__ __forceinline__ void static_for(F&& f) {
  if constexpr (I < N) { f(IC<I>{}); static_for<N, I + 1>(f); }
}

__host__ __device__ constexpr uint32_t stage_off(int st) {
  return st < 6 ? 131072u + (uint32_t)st * 16384u : (uint32_t)(st - 6) * 65536u + 49152u;
}

constexpr int B_FULL = 0, B_EMPTY = 8, B_XFULL = 16, B_XDONE = 32, B_KVREADY = 33, B_EV = 34, B_XIN = 50, B_PIN = 62, B_COUNT = 68;
constexpr uint32_t kBarOff = 229376;
constexpr int kSmemBytes = 229376 + 1024;

__host__ __device__ constexpr int p2_bi(int i) { return i < 7 ? 0 : i < 14 ? 1 : i < 16 ? 0 : i < 18 ? 1 : i / 9; }
__host__ __device__ constexpr int p2_kb(int i) { return i < 7 ? i : i < 14 ? i - 7 : i < 16 ? i - 7 : i < 18 ? i - 9 : i % 9; }

enum { K_NONE = 0, K_GU = 1, K_KV = 2, K_Q = 3 };

__global__ void __cluster_dims__(2, 1, 1) __launch_bounds__(384, 1)
fused_kernel(const __grid_constant__ CUtensorMap tm_x, const __grid_constant__ CUtensorMap tm_wqkv,
             const __grid_constant__ CUtensorMap tm_w1, const __grid_constant__ CUtensorMap tm_w3,
             const __grid_constant__ CUtensorMap tm_w2, const __grid_constant__ CUtensorMap tm_wo,
             const __nv_bfloat16* __restrict__ x, __nv_bfloat16* __restrict__ out) {
  extern __shared__ __align__(1024) uint8_t smem_raw[];
  const uint32_t sbase = __shfl_sync(0xffffffffu, smem_u32(smem_raw), 0);
  const uint32_t bars = sbase + kBarOff;
  const int tid = threadIdx.x, lane = tid & 31;
  const int warp = __shfl_sync(0xffffffffu, tid >> 5, 0);
  const int cr = blockIdx.x & 1;
  const int r = (blockIdx.x >> 1) & 7, m = ((blockIdx.x >> 4) << 1) | cr, p = r >> 1, odd = r & 1;
#define BAR(i) (bars + 8u * (uint32_t)(i))
  if (warp == 8) {
    if (lane < 16) mbar_init(BAR(B_XFULL + lane), 1);
    fence_proxy_async();
    __syncwarp();
    if (lane == 0) {
      if (sbase & 1023u) __trap();
      for (int b = 0; b < 8; b++) {
        mbar_expect_tx(BAR(B_XFULL + b), 8192);
        tma_load_2d(sbase + b * 8192, &tm_x, BAR(B_XFULL + b), b * 64, m * 128);
      }
    } else if (lane < 9) {
      mbar_init(BAR(B_FULL + lane - 1), 1);
      mbar_init(BAR(B_EMPTY + lane - 1), 4);
    } else if (lane < 25) {
      mbar_init(BAR(B_EV + lane - 9), 4);
    } else if (lane == 25) {
      mbar_init(BAR(B_XDONE), 2);
      mbar_init(BAR(B_KVREADY), 1);
    }
    if (lane < 18) mbar_init(BAR(B_XIN + lane), 1);
    asm volatile("fence.mbarrier_init.release.cluster;" ::: "memory");
    fence_proxy_async();
  } else if (tid == 288) {
    prefetch_tmap(odd ? &tm_wqkv : (cr ? &tm_w3 : &tm_w1));
  }
  __syncthreads();
  PROF((tid >> 7), 20);
  asm volatile("barrier.cluster.arrive.relaxed.aligned;" ::: "memory");
  const uint32_t epoch = ld_relaxed(&g_epoch);
  const uint32_t tag = epoch + 1u;
  const int par = epoch & 1;

  if (warp >= 8) {
    asm volatile("setmaxnreg.dec.sync.aligned.u32 24;");
    cluster_wait();
    PROF(2, 2);
    if (warp == 8) {
      if (lane == 0) {
        for (int j = 0; j < 10; j++) {
          const CUtensorMap* tm;
          int col;
          if (!odd) {
            if (j < 8) { tm = cr ? &tm_w3 : &tm_w1; col = 7 * p * 64 + j * 32; }
            else { tm = &tm_wqkv; col = 128 * p + (j - 8) * 64 + cr * 32; }
          } else {
            if (j < 4) { tm = &tm_wqkv; col = 512 + cr * 512 + 128 * p + j * 32; }
            else { tm = cr ? &tm_w3 : &tm_w1; col = (7 * p + 4) * 64 + (j - 4) * 32; }
          }
          const int t = j >> 1;
          for (int kq = 0; kq < 4; kq++) {
            const int k = (j & 1) * 4 + kq;
            if (j == 0 && kq == 2) {
              for (int b = 0; b < 8; b++) {
                mbar_expect_tx(BAR(B_XFULL + 8 + b), 8192);
                tma_load_2d(sbase + 65536 + b * 8192, &tm_x, BAR(B_XFULL + 8 + b), b * 64, m * 128 + 64);
              }
            }
            mbar_wait(BAR(B_EMPTY + k), k < 6 ? ((t & 1) ^ 1) : (t & 1));
            mbar_expect_tx(BAR(B_FULL + k), 16384);
            tma_load_2d_mc(sbase + stage_off(k) + cr * 8192, tm, BAR(B_FULL + k), col, kq * 128);
          }
        }
        for (int j = 0; j < 18; j++) {
          const int st = j & 7, n = 5 + (j >> 3);
          const int i = 2 * j + cr;
          const int bi = p2_bi(i), kb = p2_kb(i);
          const int col = odd * 256 + ((p + 1 + bi) & 3) * 64;
          const CUtensorMap* tmk;
          int row;
          if (!odd) {
            if (kb < 4) { tmk = &tm_w2; row = (7 * p + kb) * 64; }
            else if (kb < 6) { tmk = &tm_wo; row = (2 * p + kb - 4) * 64; }
            else { tmk = &tm_w2; row = (7 * p + 4 + kb - 6) * 64; }
          } else {
            if (kb < 3) { tmk = &tm_w2; row = (7 * p + 4 + kb) * 64; }
            else if (kb < 7) { tmk = &tm_w2; row = (7 * p + kb - 3) * 64; }
            else { tmk = &tm_wo; row = (2 * p + kb - 7) * 64; }
          }
          mbar_wait(BAR(B_EMPTY + st), st < 6 ? ((n & 1) ^ 1) : (n & 1));
          mbar_expect_tx(BAR(B_FULL + st), 16384);
          tma_load_2d_mc(sbase + stage_off(st) + cr * 8192, tmk, BAR(B_FULL + st), col, row);
        }
      }
    } else if (warp <= 10) {
      if (lane == 0) {
        const int w = warp - 9;
        for (int e = 0; e < 8; e++) {
          mbar_wait(BAR(B_EV + w * 8 + e), 0);
          __threadfence();
          if (e >= 5) {
            const int bi = e - 5;
            st_relaxed(&g_pflag[m][odd][(p + 1 + bi) & 3][bi][w], tag);
          } else if (!odd) {
            st_relaxed(&g_xflag[m][p][e][w], tag);
          } else {
            if (e < 2) atomicAdd(&g_kvcnt[p][0], 1u);
            else st_relaxed(&g_xflag[m][p][6 + e - 2][w], tag);
          }
        }
      }
    } else {
      if (!odd) {
        {
          const int ce = m * 4 + p;
          float* kvn = &g_kv[par ^ 1][0][0][0];
          for (int i = lane; i < 128; i += 32) kvn[ce * 128 + i] = 0.f;
          if (lane < 8) (&g_z[par ^ 1][0][0])[ce * 8 + lane] = 0.f;
        }
        mbar_wait(BAR(B_XDONE), 0);
        wait_count_ge(&g_kvcnt[p][0], 64u * tag);
        const float* kvp = &g_kv[par][8 * p][0][0];
        const uint32_t dst0 = sbase + 5 * 8192, dst1 = dst0 + 65536;
#pragma unroll 4
        for (int i = 0; i < 16; i++) {
          float4 v = ldg_cg_f4(kvp + (i * 32 + lane) * 4);
          uint32_t lo = pack_bf16(v.x, v.y), hi = pack_bf16(v.z, v.w);
          uint32_t off = (uint32_t)(i * 32 + lane) * 8u;
          asm volatile("st.shared.v2.u32 [%0], {%1,%2};" ::"r"(dst0 + off), "r"(lo), "r"(hi) : "memory");
          asm volatile("st.shared.v2.u32 [%0], {%1,%2};" ::"r"(dst1 + off), "r"(lo), "r"(hi) : "memory");
        }
        {
          float4 v = ldg_cg_f4(&g_z[par][8 * p][0] + lane * 4);
          uint32_t lo = pack_bf16(v.x, v.y), hi = pack_bf16(v.z, v.w);
          uint32_t off = 4096u + (uint32_t)lane * 8u;
          asm volatile("st.shared.v2.u32 [%0], {%1,%2};" ::"r"(dst0 + off), "r"(lo), "r"(hi) : "memory");
          asm volatile("st.shared.v2.u32 [%0], {%1,%2};" ::"r"(dst1 + off), "r"(lo), "r"(hi) : "memory");
        }
        __syncwarp();
        if (lane == 0) mbar_arrive(BAR(B_KVREADY));
      }
      const uint32_t* flag = nullptr;
      if (lane < 12) {
        const int w = lane / 6, idx = lane - w * 6;
        if (odd ? idx < 5 : idx < 3) flag = &g_xflag[m][p][odd ? idx : 6 + idx][w];
      } else if (lane < 18) {
        const int w = (lane - 12) / 3, idx = lane - 12 - w * 3;
        flag = &g_pflag[m][odd][p][idx][w];
      }
      bool pending = flag != nullptr;
      uint32_t it = 0;
      while (__any_sync(0xffffffffu, pending)) {
        if (pending) {
          if (ld_acquire(flag) == tag || it > kSpinLimit) { mbar_arrive(BAR(B_XIN + lane)); pending = false; }
        }
        ++it;
        __nanosleep(32);
      }
    }
  } else {
    asm volatile("setmaxnreg.inc.sync.aligned.u32 240;");
    const int w = warp >> 2, wq = warp & 3, t128 = tid & 127;
    const int g = lane >> 2, tq = lane & 3;
    const uint32_t area = sbase + (uint32_t)w * 65536u;
    const bool elect = (t128 == 0);
    PROF(w, 22);
    const uint32_t dbase = (sbase & 0x3FFFFu) >> 4;
    uint32_t A[144];
    float rs0, rs1;
    auto release = [&](int st) {
      if (elect) { mbar_arrive_cluster(BAR(B_EMPTY + st), 0); mbar_arrive_cluster(BAR(B_EMPTY + st), 1); }
    };

    {
      const int row = wq * 16 + (lane & 7) + ((lane >> 3) & 1) * 8;
      const uint32_t rbase = area + row * 128;
      float s0[2][4] = {}, q0[2][4] = {}, q1[2][4] = {};
      const uint32_t ones = 0x3F803F80u;
#pragma unroll
      for (int b = 0; b < 8; b++) {
        mbar_wait(BAR(B_XFULL + w * 8 + b), 0);
        if (b == 0) PROF(w, 23);
        if (b == 7) PROF(w, 24);
#pragma unroll
        for (int kk = 0; kk < 4; kk++) {
          const int i = (b * 4 + kk) * 4;
          ldmatrix_x4(rbase + b * 8192 + (((kk * 2 + (lane >> 4)) ^ (row & 7)) << 4), A[i], A[i + 1], A[i + 2], A[i + 3]);
        }
#pragma unroll
        for (int kk = 0; kk < 4; kk++) {
          const int i = (b * 4 + kk) * 4;
          mma_16816(s0[kk & 1], A[i], A[i + 1], A[i + 2], A[i + 3], ones, ones);
          mma_16816(q0[kk & 1], A[i], A[i + 1], A[i + 2], A[i + 3], A[i], A[i + 2]);
          mma_16816(q1[kk & 1], A[i], A[i + 1], A[i + 2], A[i + 3], A[i + 1], A[i + 3]);
        }
      }
      const float mean0 = (s0[0][0] + s0[1][0]) * (1.f / 512.f), mean1 = (s0[0][2] + s0[1][2]) * (1.f / 512.f);
      const uint32_t m0 = pack_bf16(mean0, mean0), m1 = pack_bf16(mean1, mean1);
#pragma unroll
      for (int i = 0; i < 128; i += 2) {
        A[i] = hsub2_bf16(A[i], m0);
        A[i + 1] = hsub2_bf16(A[i + 1], m1);
      }
      float v0 = (g & 1) ? q0[0][1] + q0[1][1] : q0[0][0] + q0[1][0];
      float v1 = (g & 1) ? q1[0][3] + q1[1][3] : q1[0][2] + q1[1][2];
      const int src = 4 * g + (g >> 1);
      v0 = __shfl_sync(0xffffffffu, v0, src);
      v1 = __shfl_sync(0xffffffffu, v1, src);
      v0 = fmaxf(v0 * (1.f / 512.f) - mean0 * mean0, 0.f);
      v1 = fmaxf(v1 * (1.f / 512.f) - mean1 * mean1, 0.f);
      rs0 = rsqrtf(v0 + 1e-5f);
      rs1 = rsqrtf(v1 + 1e-5f);
      bar_sync(1 + w, 128);
      cluster_wait();
      PROF(w, 0);
      release(6); release(7);
      if (elect) mbar_arrive(BAR(B_XDONE));
    }

    auto gu_chunk = [&](float (&acc)[32], int f, int slot, int xslot, int hb) {
      const float c0 = rs0 * -1.4426950408889634f, c1 = rs1 * -1.4426950408889634f;
      const float q0 = rs0 * rs0, q1 = rs1 * rs1;
      uint32_t h[4];
#pragma unroll
      for (int i = 0; i < 4; i++) {
        const float ga = acc[f * 8 + 2 * i], gb = acc[f * 8 + 2 * i + 1];
        const float ua = acc[16 + f * 8 + 2 * i], ub = acc[16 + f * 8 + 2 * i + 1];
        const float c = (i & 1) ? c1 : c0, q = (i & 1) ? q1 : q0;
        const float da = 1.f + ex2f(fminf(ga * c, 60.f)), db = 1.f + ex2f(fminf(gb * c, 60.f));
        const float rq = rcpf(da * db) * q;
        h[i] = pack_bf16(ga * ua * (db * rq), gb * ub * (da * rq));
      }
      const int jj = hb * 2 + f;
      sts_u4(area + slot * 8192 + jj * 2048 + t128 * 16, h[0], h[1], h[2], h[3]);
      stg_u4(&g_xbuf[m][p][xslot][w][jj][t128], h[0], h[1], h[2], h[3]);
    };
    auto kv_stage = [&](float (&acc)[32], int c, int hb) {
      const int srow = wq * 16 + (lane & 7) + ((lane >> 3) & 1) * 8;
      const uint32_t base = area + (3 + c) * 8192 + srow * 128;
#pragma unroll
      for (int jj = 0; jj < 2; jj++) {
        const int a = c * 16 + jj * 8;
        uint32_t r0, r1, r2, r3;
        if (c == 0) {
          r0 = pack_bf16(phi_f(acc[a] * rs0), phi_f(acc[a + 1] * rs0));
          r1 = pack_bf16(phi_f(acc[a + 2] * rs1), phi_f(acc[a + 3] * rs1));
          r2 = pack_bf16(phi_f(acc[a + 4] * rs0), phi_f(acc[a + 5] * rs0));
          r3 = pack_bf16(phi_f(acc[a + 6] * rs1), phi_f(acc[a + 7] * rs1));
        } else {
          r0 = pack_bf16(acc[a] * rs0, acc[a + 1] * rs0);
          r1 = pack_bf16(acc[a + 2] * rs1, acc[a + 3] * rs1);
          r2 = pack_bf16(acc[a + 4] * rs0, acc[a + 5] * rs0);
          r3 = pack_bf16(acc[a + 6] * rs1, acc[a + 7] * rs1);
        }
        stmatrix_x4(base + (((hb * 4 + jj * 2 + (lane >> 4)) ^ (srow & 7)) << 4), r0, r1, r2, r3);
      }
    };
    auto q_head = [&](float (&acc)[32], int c, int slot, uint32_t b0, uint32_t b1, uint32_t b2, uint32_t b3, uint32_t z0, uint32_t z1) {
      const int a = c * 8;
      const uint32_t a0 = pack_bf16(phi_f(acc[a] * rs0), phi_f(acc[a + 1] * rs0));
      const uint32_t a1 = pack_bf16(phi_f(acc[a + 2] * rs1), phi_f(acc[a + 3] * rs1));
      const uint32_t a2 = pack_bf16(phi_f(acc[a + 4] * rs0), phi_f(acc[a + 5] * rs0));
      const uint32_t a3 = pack_bf16(phi_f(acc[a + 6] * rs1), phi_f(acc[a + 7] * rs1));
      float n0[4] = {0.f, 0.f, 0.f, 0.f}, n1[4] = {0.f, 0.f, 0.f, 0.f}, dn[4] = {0.f, 0.f, 0.f, 0.f};
      mma_16816(n0, a0, a1, a2, a3, b0, b1);
      mma_16816(n1, a0, a1, a2, a3, b2, b3);
      mma_16816(dn, a0, a1, a2, a3, z0, z1);
      const float i0 = __fdividef(1.f, dn[0] + 1e-6f), i1 = __fdividef(1.f, dn[2] + 1e-6f);
      const uint32_t o0 = pack_bf16(n0[0] * i0, n0[1] * i0), o1 = pack_bf16(n0[2] * i1, n0[3] * i1);
      const uint32_t o2 = pack_bf16(n1[0] * i0, n1[1] * i0), o3 = pack_bf16(n1[2] * i1, n1[3] * i1);
      sts_u4(area + slot * 8192 + c * 2048 + t128 * 16, o0, o1, o2, o3);
      stg_u4(&g_xbuf[m][p][slot][w][c][t128], o0, o1, o2, o3);
    };
    const uint32_t kvb = area + 5 * 8192;
    const uint32_t kvfrag = kvb + ((lane & 7) + ((lane >> 3) & 1) * 8) * 32 + (lane >> 4) * 16;
    auto signal = [&](int e) {
      __syncwarp();
      if (lane == 0) mbar_arrive(BAR(B_EV + w * 8 + e));
    };

    float accB[32];
#pragma unroll 1
    for (int t = 0; t < 5; t++) {
      float accA[32];
      const uint32_t ph = t & 1;
      const int kindP = t == 0 ? K_NONE : ((odd && t <= 2) ? K_KV : K_GU);
      const int kindC = odd ? (t < 2 ? K_KV : K_GU) : (t < 4 ? K_GU : K_Q);
      const int slotP = odd ? t - 3 : t - 1, xslotP = odd ? t + 3 : t - 1;
      const int slotC = odd ? t - 2 : t, xslotC = odd ? t + 4 : t;
      static_for<8>([&](auto kc) {
        constexpr int k = decltype(kc)::value;
        mbar_wait(BAR(B_FULL + k), ph);
        wgmma_fence();
        static_for<8>([&](auto kkc) {
          constexpr int kk = decltype(kkc)::value;
          constexpr int i = ((k & 3) * 8 + kk) * 4;
          constexpr uint32_t lo = desc_lo(stage_off(k) + kk * 1024, 8192);
          if constexpr (k < 4) wgmma_n64_rs<((k & 3) | kk) != 0, lo, kHi64>(accA, A[i], A[i + 1], A[i + 2], A[i + 3], dbase);
          else wgmma_n64_rs<((k & 3) | kk) != 0, lo, kHi64>(accB, A[i], A[i + 1], A[i + 2], A[i + 3], dbase);
        });
        wgmma_commit();
        if (k > 0) {
          wgmma_wait<1>();
          release(k - 1);
        }
        if constexpr (k < 4) {
          if (kindP == K_GU) {
            if (k == 1 || k == 2) gu_chunk(accB, k - 1, slotP, xslotP, 1);
            if (k == 2) signal(t - 1);
          } else if (kindP == K_KV) {
            if (k == 1 || k == 2) kv_stage(accB, k - 1, 1);
            if (k == 3) {
              float kvacc[36];
              fence_proxy_async();
              bar_sync(1 + w, 128);
              wgmma_fence();
              static_for<4>([&](auto kkc) {
                constexpr int kk = decltype(kkc)::value;
                wgmma_n72_ss_tt<kk != 0, desc_lo(3 * 8192 + kk * 2048, 0), desc_lo(4 * 8192 + kk * 2048, 8192 - kk * 2048)>(kvacc, dbase + w * 4096);
              });
              wgmma_commit();
              wgmma_wait<0>();
              float c[8];
#pragma unroll
              for (int i = 0; i < 8; i++)
                c[i] = wq == 0 ? kvacc[i] : (wq == 1 ? kvacc[8 + i] : (wq == 2 ? kvacc[16 + i] : kvacc[24 + i]));
              const int head = (2 * p + t - 1) * 4 + wq;
              float* kvp = &g_kv[par][head][0][0];
              red_add_v2(kvp + g * 16 + 2 * tq, c[0], c[1]);
              red_add_v2(kvp + (g + 8) * 16 + 2 * tq, c[2], c[3]);
              red_add_v2(kvp + g * 16 + 8 + 2 * tq, c[4], c[5]);
              red_add_v2(kvp + (g + 8) * 16 + 8 + 2 * tq, c[6], c[7]);
              if (tq == 0) {
                red_add(&g_z[par][head][g], kvacc[32]);
                red_add(&g_z[par][head][g + 8], kvacc[34]);
              }
              signal(t - 1);
            }
          }
        } else {
          constexpr int c = k - 4;
          if (kindC == K_GU) {
            if (c < 2) gu_chunk(accA, c, slotC, xslotC, 0);
          } else if (kindC == K_KV) {
            if (c == 0 && t == 0) sts_u4(area + 5 * 8192 + t128 * 16, 0x3F803F80u, 0x3F803F80u, 0x3F803F80u, 0x3F803F80u);
            if (c < 2) kv_stage(accA, c, 0);
          } else {
            if (c == 0) mbar_wait(BAR(B_KVREADY), 0);
            uint32_t b0, b1, b2, b3;
            ldmatrix_x4_trans(kvfrag + c * 512, b0, b1, b2, b3);
            const uint32_t z0 = lds_u32(kvb + 4096 + c * 32 + tq * 4), z1 = lds_u32(kvb + 4096 + c * 32 + 16 + tq * 4);
            q_head(accA, c, 4, b0, b1, b2, b3, z0, z1);
          }
        }
      });
      wgmma_wait<0>();
      release(7);
      PROF(w, 1 + 2 * t);
    }
    if (odd) {
      gu_chunk(accB, 0, 2, 8, 1);
      gu_chunk(accB, 1, 2, 8, 1);
    } else {
      uint32_t Bf[4][6];
#pragma unroll
      for (int c = 0; c < 4; c++) {
        ldmatrix_x4_trans(kvfrag + (4 + c) * 512, Bf[c][0], Bf[c][1], Bf[c][2], Bf[c][3]);
        Bf[c][4] = lds_u32(kvb + 4096 + (4 + c) * 32 + tq * 4);
        Bf[c][5] = lds_u32(kvb + 4096 + (4 + c) * 32 + 16 + tq * 4);
      }
      bar_sync(1 + w, 128);
#pragma unroll
      for (int c = 0; c < 4; c++) q_head(accB, c, 5, Bf[c][0], Bf[c][1], Bf[c][2], Bf[c][3], Bf[c][4], Bf[c][5]);
    }
    signal(4);
    PROF(w, 10);

    const int n_own = odd ? 3 : 6;
    auto load_a = [&](int kb) {
      if (kb < n_own) {
#pragma unroll
        for (int jj = 0; jj < 4; jj++) {
          const int i = (kb * 4 + jj) * 4;
          lds_u4(area + kb * 8192 + jj * 2048 + t128 * 16, A[i], A[i + 1], A[i + 2], A[i + 3]);
        }
      } else {
        const int xs = odd ? kb - 3 : kb;
        const int ev = odd ? (kb - 3 < 4 ? kb - 3 : 4) : kb - 6;
        mbar_wait(BAR(B_XIN + w * 6 + ev), 0);
#pragma unroll
        for (int jj = 0; jj < 4; jj++) {
          const int i = (kb * 4 + jj) * 4;
          uint4 v = ldg_cg_u4(&g_xbuf[m][p][xs][w][jj][t128]);
          A[i] = v.x; A[i + 1] = v.y; A[i + 2] = v.z; A[i + 3] = v.w;
        }
      }
    };
#pragma unroll
    for (int kb = 0; kb < 7; kb++) load_a(kb);
    PROF(w, 11);

    const int orow = m * 128 + w * 64 + wq * 16 + g;
    const int ocol = odd * 256 + p * 64 + 2 * tq;
    float acc2[2][32];
    float4 P0[8], P1[8], P2[8];
    uint32_t xr[16];
    auto send = [&](float (&acc)[32], int bi) {
      float4* dst = &g_pbuf[m][odd][(p + 1 + bi) & 3][bi][w][0][t128];
#pragma unroll
      for (int q = 0; q < 8; q++) stg_f4(dst + q * 128, acc[q * 4], acc[q * 4 + 1], acc[q * 4 + 2], acc[q * 4 + 3]);
      signal(5 + bi);
      PROF(w, 12 + 2 * bi);
    };
    static_for<36>([&](auto ic) {
      constexpr int i = decltype(ic)::value, bi = p2_bi(i), kb = p2_kb(i), j = i >> 1, st = j & 7;
      if (i == 9) { load_a(7); load_a(8); }
      if ((i & 1) == 0) mbar_wait(BAR(B_FULL + st), (5 + (j >> 3)) & 1);
      wgmma_fence();
      static_for<4>([&](auto kkc) {
        constexpr int kk = decltype(kkc)::value, a = (kb * 4 + kk) * 4;
        wgmma_n64_rs<(kb | kk) != 0, desc_lo(stage_off(st) + (i & 1) * 8192 + kk * 2048, 0), kHi128>(acc2[bi & 1], A[a], A[a + 1], A[a + 2], A[a + 3], dbase);
      });
      wgmma_commit();
      if (i > 0) {
        wgmma_wait<1>();
        if ((i & 1) == 0 && j - 1 <= 9) release((j - 1) & 7);
      }
      if constexpr (i == 16) send(acc2[0], 0);
      if constexpr (i == 18) send(acc2[1], 1);
      if constexpr (i == 27) send(acc2[0], 2);
      if constexpr (i == 29) {
        mbar_wait(BAR(B_PIN + w * 3 + 0), 0);
#pragma unroll
        for (int q = 0; q < 8; q++) P0[q] = ldg_cg_f4(&g_pbuf[m][odd][p][0][w][q][t128]);
      }
      if constexpr (i == 31) {
        mbar_wait(BAR(B_PIN + w * 3 + 1), 0);
#pragma unroll
        for (int q = 0; q < 8; q++) P1[q] = ldg_cg_f4(&g_pbuf[m][odd][p][1][w][q][t128]);
      }
      if constexpr (i == 32) {
#pragma unroll
        for (int q = 0; q < 8; q++) {
          xr[2 * q] = __ldg((const uint32_t*)(x + (size_t)orow * kD + ocol + q * 8));
          xr[2 * q + 1] = __ldg((const uint32_t*)(x + (size_t)(orow + 8) * kD + ocol + q * 8));
        }
      }
      if constexpr (i == 35) {
        mbar_wait(BAR(B_PIN + w * 3 + 2), 0);
#pragma unroll
        for (int q = 0; q < 8; q++) P2[q] = ldg_cg_f4(&g_pbuf[m][odd][p][2][w][q][t128]);
      }
    });
    wgmma_wait<0>();
    PROF(w, 18);
#pragma unroll
    for (int q = 0; q < 8; q++) {
      const float r0 = acc2[1][q * 4 + 0] + P0[q].x + P1[q].x + P2[q].x + __uint_as_float(xr[2 * q] << 16);
      const float r1 = acc2[1][q * 4 + 1] + P0[q].y + P1[q].y + P2[q].y + __uint_as_float(xr[2 * q] & 0xffff0000u);
      const float r2 = acc2[1][q * 4 + 2] + P0[q].z + P1[q].z + P2[q].z + __uint_as_float(xr[2 * q + 1] << 16);
      const float r3 = acc2[1][q * 4 + 3] + P0[q].w + P1[q].w + P2[q].w + __uint_as_float(xr[2 * q + 1] & 0xffff0000u);
      *(uint32_t*)(out + (size_t)orow * kD + ocol + q * 8) = pack_bf16(r0, r1);
      *(uint32_t*)(out + (size_t)(orow + 8) * kD + ocol + q * 8) = pack_bf16(r2, r3);
    }
    PROF(w, 19);
    if (tid == 0) {
      const uint32_t old = atomicAdd(&g_done, 1u);
      if ((old & 127u) == 127u) *(volatile uint32_t*)&g_epoch = epoch + 1u;
    }
  }
#undef BAR
}

typedef CUresult (*EncodeFn)(CUtensorMap*, CUtensorMapDataType, cuuint32_t, void*, const cuuint64_t*, const cuuint64_t*,
                             const cuuint32_t*, const cuuint32_t*, CUtensorMapInterleave, CUtensorMapSwizzle,
                             CUtensorMapL2promotion, CUtensorMapFloatOOBfill);

void make_map(EncodeFn enc, CUtensorMap* tm, const void* ptr, int rows, int cols, bool narrow) {
  cuuint64_t gd[2] = {(cuuint64_t)cols, (cuuint64_t)rows};
  cuuint64_t gs[1] = {(cuuint64_t)cols * 2};
  cuuint32_t bd[2] = {narrow ? 32u : 64u, narrow ? 128u : 64u};
  cuuint32_t es[2] = {1, 1};
  enc(tm, CU_TENSOR_MAP_DATA_TYPE_BFLOAT16, 2, const_cast<void*>(ptr), gd, gs, bd, es, CU_TENSOR_MAP_INTERLEAVE_NONE,
      narrow ? CU_TENSOR_MAP_SWIZZLE_64B : CU_TENSOR_MAP_SWIZZLE_128B, CU_TENSOR_MAP_L2_PROMOTION_L2_256B, CU_TENSOR_MAP_FLOAT_OOB_FILL_NONE);
}

}

extern "C" void kernel_launch(void* const* d_in, const int* in_sizes, int n_in, void* d_out, int out_size) {
  static EncodeFn enc = nullptr;
  if (!enc) {
    void* fn = nullptr;
    cudaDriverEntryPointQueryResult qr;
    cudaGetDriverEntryPoint("cuTensorMapEncodeTiled", &fn, cudaEnableDefault, &qr);
    enc = (EncodeFn)fn;
    cudaFuncSetAttribute(fused_kernel, cudaFuncAttributeMaxDynamicSharedMemorySize, kSmemBytes);
  }
  CUtensorMap tm_x, tm_wqkv, tm_w1, tm_w3, tm_w2, tm_wo;
  make_map(enc, &tm_x, d_in[0], kS, kD, false);
  make_map(enc, &tm_wqkv, d_in[1], kD, 3 * kD, true);
  make_map(enc, &tm_wo, d_in[2], kD, kD, false);
  make_map(enc, &tm_w1, d_in[4], kD, kF, true);
  make_map(enc, &tm_w3, d_in[5], kD, kF, true);
  make_map(enc, &tm_w2, d_in[6], kF, kD, false);
  fused_kernel<<<128, 384, kSmemBytes>>>(tm_x, tm_wqkv, tm_w1, tm_w3, tm_w2, tm_wo, (const __nv_bfloat16*)d_in[0],
                                         (__nv_bfloat16*)d_out);
}
```

```cpp
#include <cuda_runtime.h>
#include <cuda_bf16.h>
#include <cuda.h>
#include <stdint.h>

namespace {

constexpr int kS = 2048, kD = 512, kF = 1792;
constexpr uint32_t kSpinLimit = 1u << 22;

__device__ uint4    g_xbuf[16][4][9][2][4][128];
__device__ float4   g_pbuf[16][2][4][3][2][8][128];
__device__ float    g_kv[2][32][16][16];
__device__ float    g_z[2][32][16];
__device__ uint32_t g_xflag[16][4][9][2];
__device__ uint32_t g_pflag[16][2][4][3][2];
__device__ uint32_t g_kvcnt[4][32];
__device__ uint32_t g_epoch;
__device__ uint32_t g_done;
#define PROF(wg, i) do {} while (0)

__device__ __forceinline__ uint32_t smem_u32(const void* p) { return (uint32_t)__cvta_generic_to_shared(p); }
__device__ __forceinline__ void mbar_init(uint32_t bar, uint32_t cnt) {
  asm volatile("mbarrier.init.shared::cta.b64 [%0], %1;" ::"r"(bar), "r"(cnt) : "memory");
}
__device__ __forceinline__ void mbar_expect_tx(uint32_t bar, uint32_t bytes) {
  asm volatile("mbarrier.arrive.expect_tx.shared::cta.b64 _, [%0], %1;" ::"r"(bar), "r"(bytes) : "memory");
}
__device__ __forceinline__ void mbar_arrive(uint32_t bar) {
  asm volatile("mbarrier.arrive.shared::cta.b64 _, [%0];" ::"r"(bar) : "memory");
}
__device__ __forceinline__ void mbar_wait(uint32_t bar, uint32_t parity) {
  asm volatile(
      "{\n.reg .pred p;\n"
      "LAB_WAIT:\n"
      "mbarrier.try_wait.parity.shared::cta.b64 p, [%0], %1;\n"
      "@p bra DONE;\n"
      "bra LAB_WAIT;\n"
      "DONE:\n}" ::"r"(bar), "r"(parity) : "memory");
}
__device__ __forceinline__ void tma_load_2d(uint32_t dst, const CUtensorMap* tm, uint32_t bar, int c0, int c1) {
  asm volatile(
      "cp.async.bulk.tensor.2d.shared::cluster.global.mbarrier::complete_tx::bytes [%0], [%1, {%3, %4}], [%2];" ::"r"(dst),
      "l"(tm), "r"(bar), "r"(c0), "r"(c1)
      : "memory");
}
__device__ __forceinline__ void tma_load_2d_mc(uint32_t dst, const CUtensorMap* tm, uint32_t bar, int c0, int c1) {
  asm volatile(
      "cp.async.bulk.tensor.2d.shared::cluster.global.mbarrier::complete_tx::bytes.multicast::cluster [%0], [%1, {%3, %4}], [%2], %5;" ::"r"(dst),
      "l"(tm), "r"(bar), "r"(c0), "r"(c1), "h"((uint16_t)3)
      : "memory");
}
__device__ __forceinline__ void mbar_arrive_cluster(uint32_t bar, uint32_t cta) {
  asm volatile("{\n.reg .b32 ra;\nmapa.shared::cluster.u32 ra, %0, %1;\nmbarrier.arrive.shared::cluster.b64 _, [ra];\n}" ::"r"(bar), "r"(cta) : "memory");
}
__device__ __forceinline__ void prefetch_tmap(const CUtensorMap* tm) {
  asm volatile("prefetch.tensormap [%0];" ::"l"(tm) : "memory");
}
__device__ __forceinline__ void wgmma_fence() { asm volatile("wgmma.fence.sync.aligned;" ::: "memory"); }
__device__ __forceinline__ void wgmma_commit() { asm volatile("wgmma.commit_group.sync.aligned;" ::: "memory"); }
template <int N>
__device__ __forceinline__ void wgmma_wait() { asm volatile("wgmma.wait_group.sync.aligned %0;" ::"n"(N) : "memory"); }
__device__ __forceinline__ void bar_sync(int id, int n) { asm volatile("bar.sync %0, %1;" ::"r"(id), "r"(n) : "memory"); }
__device__ __forceinline__ void bar_arrive(int id, int n) { asm volatile("bar.arrive %0, %1;" ::"r"(id), "r"(n) : "memory"); }
__device__ __forceinline__ void fence_proxy_async() { asm volatile("fence.proxy.async.shared::cta;" ::: "memory"); }

__device__ __forceinline__ uint32_t ld_acquire(const uint32_t* p) {
  uint32_t v;
  asm volatile("ld.acquire.gpu.global.u32 %0, [%1];" : "=r"(v) : "l"(p) : "memory");
  return v;
}
__device__ __forceinline__ uint32_t ld_relaxed(const uint32_t* p) {
  uint32_t v;
  asm volatile("ld.relaxed.gpu.global.u32 %0, [%1];" : "=r"(v) : "l"(p));
  return v;
}
__device__ __forceinline__ void cluster_wait() { asm volatile("barrier.cluster.wait.aligned;" ::: "memory"); }
__device__ __forceinline__ void st_relaxed(uint32_t* p, uint32_t v) {
  asm volatile("st.relaxed.gpu.global.u32 [%0], %1;" ::"l"(p), "r"(v) : "memory");
}
__device__ __forceinline__ void wait_flag_eq(const uint32_t* p, uint32_t val) {
  uint32_t it = 0;
  while (ld_acquire(p) != val) {
    if (++it > kSpinLimit) break;
  }
}
__device__ __forceinline__ void wait_count_ge(const uint32_t* p, uint32_t val) {
  uint32_t it = 0;
  while ((int32_t)(ld_acquire(p) - val) < 0) {
    __nanosleep(64);
    if (++it > kSpinLimit) break;
  }
}
__device__ __forceinline__ uint4 ldg_cg_u4(const void* p) {
  uint4 v;
  asm volatile("ld.global.cg.v4.u32 {%0,%1,%2,%3}, [%4];" : "=r"(v.x), "=r"(v.y), "=r"(v.z), "=r"(v.w) : "l"(p) : "memory");
  return v;
}
__device__ __forceinline__ float4 ldg_cg_f4(const void* p) {
  float4 v;
  asm volatile("ld.global.cg.v4.f32 {%0,%1,%2,%3}, [%4];" : "=f"(v.x), "=f"(v.y), "=f"(v.z), "=f"(v.w) : "l"(p) : "memory");
  return v;
}
__device__ __forceinline__ void stg_u4(void* p, uint32_t a, uint32_t b, uint32_t c, uint32_t d) {
  asm volatile("st.global.v4.u32 [%0], {%1,%2,%3,%4};" ::"l"(p), "r"(a), "r"(b), "r"(c), "r"(d) : "memory");
}
__device__ __forceinline__ void stg_f4(void* p, float a, float b, float c, float d) {
  asm volatile("st.global.v4.f32 [%0], {%1,%2,%3,%4};" ::"l"(p), "f"(a), "f"(b), "f"(c), "f"(d) : "memory");
}
__device__ __forceinline__ void sts_u4(uint32_t addr, uint32_t a, uint32_t b, uint32_t c, uint32_t d) {
  asm volatile("st.shared.v4.u32 [%0], {%1,%2,%3,%4};" ::"r"(addr), "r"(a), "r"(b), "r"(c), "r"(d) : "memory");
}
__device__ __forceinline__ void lds_u4(uint32_t addr, uint32_t& a, uint32_t& b, uint32_t& c, uint32_t& d) {
  asm volatile("ld.shared.v4.u32 {%0,%1,%2,%3}, [%4];" : "=r"(a), "=r"(b), "=r"(c), "=r"(d) : "r"(addr) : "memory");
}
__device__ __forceinline__ uint32_t lds_u32(uint32_t addr) {
  uint32_t v;
  asm volatile("ld.shared.u32 %0, [%1];" : "=r"(v) : "r"(addr) : "memory");
  return v;
}
__device__ __forceinline__ void ldmatrix_x4(uint32_t addr, uint32_t& a, uint32_t& b, uint32_t& c, uint32_t& d) {
  asm volatile("ldmatrix.sync.aligned.m8n8.x4.shared.b16 {%0,%1,%2,%3}, [%4];" : "=r"(a), "=r"(b), "=r"(c), "=r"(d) : "r"(addr) : "memory");
}
__device__ __forceinline__ void ldmatrix_x4_trans(uint32_t addr, uint32_t& a, uint32_t& b, uint32_t& c, uint32_t& d) {
  asm volatile("ldmatrix.sync.aligned.m8n8.x4.trans.shared.b16 {%0,%1,%2,%3}, [%4];" : "=r"(a), "=r"(b), "=r"(c), "=r"(d) : "r"(addr) : "memory");
}
__device__ __forceinline__ void stmatrix_x4(uint32_t addr, uint32_t a, uint32_t b, uint32_t c, uint32_t d) {
  asm volatile("stmatrix.sync.aligned.m8n8.x4.shared.b16 [%0], {%1,%2,%3,%4};" ::"r"(addr), "r"(a), "r"(b), "r"(c), "r"(d) : "memory");
}
__device__ __forceinline__ void mma_16816(float (&c)[4], uint32_t a0, uint32_t a1, uint32_t a2, uint32_t a3, uint32_t b0, uint32_t b1) {
  asm volatile(
      "mma.sync.aligned.m16n8k16.row.col.f32.bf16.bf16.f32 {%0,%1,%2,%3}, {%4,%5,%6,%7}, {%8,%9}, {%0,%1,%2,%3};"
      : "+f"(c[0]), "+f"(c[1]), "+f"(c[2]), "+f"(c[3])
      : "r"(a0), "r"(a1), "r"(a2), "r"(a3), "r"(b0), "r"(b1));
}
__device__ __forceinline__ uint32_t pack_bf16(float lo, float hi) {
  uint32_t r;
  asm("cvt.rn.bf16x2.f32 %0, %1, %2;" : "=r"(r) : "f"(hi), "f"(lo));
  return r;
}
__device__ __forceinline__ uint32_t hsub2_bf16(uint32_t a, uint32_t b) {
  uint32_t r;
  asm("sub.rn.bf16x2 %0, %1, %2;" : "=r"(r) : "r"(a), "r"(b));
  return r;
}
__device__ __forceinline__ float ex2f(float x) {
  float r;
  asm("ex2.approx.ftz.f32 %0, %1;" : "=f"(r) : "f"(x));
  return r;
}
__device__ __forceinline__ float rcpf(float x) {
  float r;
  asm("rcp.approx.ftz.f32 %0, %1;" : "=f"(r) : "f"(x));
  return r;
}
__device__ __forceinline__ void red_add_v2(float* p, float a, float b) {
  asm volatile("red.relaxed.gpu.global.add.v2.f32 [%0], {%1,%2};" ::"l"(p), "f"(a), "f"(b) : "memory");
}
__device__ __forceinline__ void red_add(float* p, float a) {
  asm volatile("red.relaxed.gpu.global.add.f32 [%0], %1;" ::"l"(p), "f"(a) : "memory");
}
__device__ __forceinline__ float phi_f(float t) {
  float e = ex2f(t * 1.4426950408889634f);
  return (t > 0.f ? t + 1.f : e) + 1e-6f;
}

#define R8(a, o) "+f"(a[o + 0]), "+f"(a[o + 1]), "+f"(a[o + 2]), "+f"(a[o + 3]), "+f"(a[o + 4]), "+f"(a[o + 5]), "+f"(a[o + 6]), "+f"(a[o + 7])

#define W8(a, o) "=f"(a[o + 0]), "=f"(a[o + 1]), "=f"(a[o + 2]), "=f"(a[o + 3]), "=f"(a[o + 4]), "=f"(a[o + 5]), "=f"(a[o + 6]), "=f"(a[o + 7])
#define D32 "{%0,%1,%2,%3,%4,%5,%6,%7,%8,%9,%10,%11,%12,%13,%14,%15,%16,%17,%18,%19,%20,%21,%22,%23,%24,%25,%26,%27,%28,%29,%30,%31}"
#define D36 "{%0,%1,%2,%3,%4,%5,%6,%7,%8,%9,%10,%11,%12,%13,%14,%15,%16,%17,%18,%19,%20,%21,%22,%23,%24,%25,%26,%27,%28,%29,%30,%31,%32,%33,%34,%35}"

constexpr uint32_t kHi128 = (1024u >> 4) | (1u << 30);
constexpr uint32_t kHi64 = (512u >> 4) | (2u << 30);
__host__ __device__ constexpr uint32_t desc_lo(uint32_t off, uint32_t lbo) { return (off >> 4) | ((lbo >> 4) << 16); }

template <bool ACC, uint32_t LO, uint32_t HI>
__device__ __forceinline__ void wgmma_n64_rs(float (&d)[32], uint32_t a0, uint32_t a1, uint32_t a2, uint32_t a3, uint32_t base) {
  if (ACC) {
    asm volatile(
        "{\n.reg .pred p;\n.reg .b32 lo;\n.reg .b64 dd;\nsetp.eq.b32 p, 0, 0;\nadd.u32 lo, %36, %37;\nmov.b64 dd, {lo, %38};\n"
        "wgmma.mma_async.sync.aligned.m64n64k16.f32.bf16.bf16 " D32 ", {%32,%33,%34,%35}, dd, p, 1, 1, 1;\n}"
        : R8(d, 0), R8(d, 8), R8(d, 16), R8(d, 24)
        : "r"(a0), "r"(a1), "r"(a2), "r"(a3), "r"(base), "n"(LO), "n"(HI));
  } else {
    asm volatile(
        "{\n.reg .pred p;\n.reg .b32 lo;\n.reg .b64 dd;\nsetp.ne.b32 p, 0, 0;\nadd.u32 lo, %36, %37;\nmov.b64 dd, {lo, %38};\n"
        "wgmma.mma_async.sync.aligned.m64n64k16.f32.bf16.bf16 " D32 ", {%32,%33,%34,%35}, dd, p, 1, 1, 1;\n}"
        : W8(d, 0), W8(d, 8), W8(d, 16), W8(d, 24)
        : "r"(a0), "r"(a1), "r"(a2), "r"(a3), "r"(base), "n"(LO), "n"(HI));
  }
}
template <bool ACC, uint32_t LOA, uint32_t LOB>
__device__ __forceinline__ void wgmma_n72_ss_tt(float (&d)[36], uint32_t base) {
  if (ACC) {
    asm volatile(
        "{\n.reg .pred p;\n.reg .b32 lo;\n.reg .b64 da, db;\nsetp.eq.b32 p, 0, 0;\n"
        "add.u32 lo, %36, %37;\nmov.b64 da, {lo, %39};\nadd.u32 lo, %36, %38;\nmov.b64 db, {lo, %39};\n"
        "wgmma.mma_async.sync.aligned.m64n72k16.f32.bf16.bf16 " D36 ", da, db, p, 1, 1, 1, 1;\n}"
        : R8(d, 0), R8(d, 8), R8(d, 16), R8(d, 24), "+f"(d[32]), "+f"(d[33]), "+f"(d[34]), "+f"(d[35])
        : "r"(base), "n"(LOA), "n"(LOB), "n"(kHi128));
  } else {
    asm volatile(
        "{\n.reg .pred p;\n.reg .b32 lo;\n.reg .b64 da, db;\nsetp.ne.b32 p, 0, 0;\n"
        "add.u32 lo, %36, %37;\nmov.b64 da, {lo, %39};\nadd.u32 lo, %36, %38;\nmov.b64 db, {lo, %39};\n"
        "wgmma.mma_async.sync.aligned.m64n72k16.f32.bf16.bf16 " D36 ", da, db, p, 1, 1, 1, 1;\n}"
        : W8(d, 0), W8(d, 8), W8(d, 16), W8(d, 24), "=f"(d[32]), "=f"(d[33]), "=f"(d[34]), "=f"(d[35])
        : "r"(base), "n"(LOA), "n"(LOB), "n"(kHi128));
  }
}

template <int V> struct IC { static constexpr int value = V; };
template <int N, int I = 0, typename F>
__device__ __forceinline__ void static_for(F&& f) {
  if constexpr (I < N) { f(IC<I>{}); static_for<N, I + 1>(f); }
}

__host__ __device__ constexpr uint32_t stage_off(int st) {
  return st < 6 ? 131072u + (uint32_t)st * 16384u : (uint32_t)(st - 6) * 65536u + 49152u;
}

constexpr int B_FULL = 0, B_EMPTY = 8, B_XFULL = 16, B_XDONE = 32, B_KVREADY = 33, B_EV = 34, B_XIN = 50, B_PIN = 62, B_COUNT = 68;
constexpr uint32_t kBarOff = 229376;
constexpr int kSmemBytes = 229376 + 1024;

__host__ __device__ constexpr int p2_bi(int i) { return i < 7 ? 0 : i < 14 ? 1 : i < 16 ? 0 : i < 18 ? 1 : i / 9; }
__host__ __device__ constexpr int p2_kb(int i) { return i < 7 ? i : i < 14 ? i - 7 : i < 16 ? i - 7 : i < 18 ? i - 9 : i % 9; }

enum { K_NONE = 0, K_GU = 1, K_KV = 2, K_Q = 3 };

__global__ void __cluster_dims__(2, 1, 1) __launch_bounds__(384, 1)
fused_kernel(const __grid_constant__ CUtensorMap tm_x, const __grid_constant__ CUtensorMap tm_wqkv,
             const __grid_constant__ CUtensorMap tm_w1, const __grid_constant__ CUtensorMap tm_w3,
             const __grid_constant__ CUtensorMap tm_w2, const __grid_constant__ CUtensorMap tm_wo,
             const __nv_bfloat16* __restrict__ x, __nv_bfloat16* __restrict__ out) {
  extern __shared__ __align__(1024) uint8_t smem_raw[];
  const uint32_t sbase = __shfl_sync(0xffffffffu, smem_u32(smem_raw), 0);
  const uint32_t bars = sbase + kBarOff;
  const int tid = threadIdx.x, lane = tid & 31;
  const int warp = __shfl_sync(0xffffffffu, tid >> 5, 0);
  const int cr = blockIdx.x & 1;
  const int r = (blockIdx.x >> 1) & 7, m = ((blockIdx.x >> 4) << 1) | cr, p = r >> 1, odd = r & 1;
#define BAR(i) (bars + 8u * (uint32_t)(i))
  if (warp == 8) {
    if (lane < 16) mbar_init(BAR(B_XFULL + lane), 1);
    fence_proxy_async();
    __syncwarp();
    if (lane == 0) {
      if (sbase & 1023u) __trap();
      for (int b = 0; b < 8; b++) {
        mbar_expect_tx(BAR(B_XFULL + b), 8192);
        tma_load_2d(sbase + b * 8192, &tm_x, BAR(B_XFULL + b), b * 64, m * 128);
      }
    } else if (lane < 9) {
      mbar_init(BAR(B_FULL + lane - 1), 1);
      mbar_init(BAR(B_EMPTY + lane - 1), 4);
    } else if (lane < 25) {
      mbar_init(BAR(B_EV + lane - 9), 4);
    } else if (lane == 25) {
      mbar_init(BAR(B_XDONE), 2);
      mbar_init(BAR(B_KVREADY), 1);
    }
    if (lane < 18) mbar_init(BAR(B_XIN + lane), 1);
    asm volatile("fence.mbarrier_init.release.cluster;" ::: "memory");
    fence_proxy_async();
  } else if (tid == 288) {
    prefetch_tmap(odd ? &tm_wqkv : (cr ? &tm_w3 : &tm_w1));
  }
  __syncthreads();
  PROF((tid >> 7), 20);
  asm volatile("barrier.cluster.arrive.relaxed.aligned;" ::: "memory");

  if (warp >= 8) {
    asm volatile("setmaxnreg.dec.sync.aligned.u32 24;");
    cluster_wait();
    PROF(2, 2);
    const uint32_t epoch = warp == 8 ? 0u : ld_relaxed(&g_epoch);
    const uint32_t tag = epoch + 1u;
    const int par = epoch & 1;
    if (warp == 8) {
      if (lane == 0) {
        for (int j = 0; j < 10; j++) {
          const CUtensorMap* tm;
          int col;
          if (!odd) {
            if (j < 8) { tm = cr ? &tm_w3 : &tm_w1; col = 7 * p * 64 + j * 32; }
            else { tm = &tm_wqkv; col = 128 * p + (j - 8) * 64 + cr * 32; }
          } else {
            if (j < 4) { tm = &tm_wqkv; col = 512 + cr * 512 + 128 * p + j * 32; }
            else { tm = cr ? &tm_w3 : &tm_w1; col = (7 * p + 4) * 64 + (j - 4) * 32; }
          }
          const int t = j >> 1;
          for (int kq = 0; kq < 4; kq++) {
            const int k = (j & 1) * 4 + kq;
            if (j == 0 && kq == 2) {
              for (int b = 0; b < 8; b++) {
                mbar_expect_tx(BAR(B_XFULL + 8 + b), 8192);
                tma_load_2d(sbase + 65536 + b * 8192, &tm_x, BAR(B_XFULL + 8 + b), b * 64, m * 128 + 64);
              }
            }
            mbar_wait(BAR(B_EMPTY + k), k < 6 ? ((t & 1) ^ 1) : (t & 1));
            mbar_expect_tx(BAR(B_FULL + k), 16384);
            tma_load_2d_mc(sbase + stage_off(k) + cr * 8192, tm, BAR(B_FULL + k), col, kq * 128);
          }
        }
        for (int j = 0; j < 18; j++) {
          const int st = j & 7, n = 5 + (j >> 3);
          const int i = 2 * j + cr;
          const int bi = p2_bi(i), kb = p2_kb(i);
          const int col = odd * 256 + ((p + 1 + bi) & 3) * 64;
          const CUtensorMap* tmk;
          int row;
          if (!odd) {
            if (kb < 4) { tmk = &tm_w2; row = (7 * p + kb) * 64; }
            else if (kb < 6) { tmk = &tm_wo; row = (2 * p + kb - 4) * 64; }
            else { tmk = &tm_w2; row = (7 * p + 4 + kb - 6) * 64; }
          } else {
            if (kb < 3) { tmk = &tm_w2; row = (7 * p + 4 + kb) * 64; }
            else if (kb < 7) { tmk = &tm_w2; row = (7 * p + kb - 3) * 64; }
            else { tmk = &tm_wo; row = (2 * p + kb - 7) * 64; }
          }
          mbar_wait(BAR(B_EMPTY + st), st < 6 ? ((n & 1) ^ 1) : (n & 1));
          mbar_expect_tx(BAR(B_FULL + st), 16384);
          tma_load_2d_mc(sbase + stage_off(st) + cr * 8192, tmk, BAR(B_FULL + st), col, row);
        }
      }
    } else if (warp <= 10) {
      if (lane == 0) {
        const int w = warp - 9;
        for (int e = 0; e < 8; e++) {
          mbar_wait(BAR(B_EV + w * 8 + e), 0);
          __threadfence();
          if (e >= 5) {
            const int bi = e - 5;
            st_relaxed(&g_pflag[m][odd][(p + 1 + bi) & 3][bi][w], tag);
          } else if (!odd) {
            st_relaxed(&g_xflag[m][p][e][w], tag);
          } else {
            if (e < 2) atomicAdd(&g_kvcnt[p][0], 1u);
            else st_relaxed(&g_xflag[m][p][6 + e - 2][w], tag);
          }
        }
      }
    } else {
      if (!odd) {
        {
          const int ce = m * 4 + p;
          float* kvn = &g_kv[par ^ 1][0][0][0];
          for (int i = lane; i < 128; i += 32) kvn[ce * 128 + i] = 0.f;
          if (lane < 8) (&g_z[par ^ 1][0][0])[ce * 8 + lane] = 0.f;
        }
        mbar_wait(BAR(B_XDONE), 0);
        wait_count_ge(&g_kvcnt[p][0], 64u * tag);
        const float* kvp = &g_kv[par][8 * p][0][0];
        const uint32_t dst0 = sbase + 5 * 8192, dst1 = dst0 + 65536;
#pragma unroll 4
        for (int i = 0; i < 16; i++) {
          float4 v = ldg_cg_f4(kvp + (i * 32 + lane) * 4);
          uint32_t lo = pack_bf16(v.x, v.y), hi = pack_bf16(v.z, v.w);
          uint32_t off = (uint32_t)(i * 32 + lane) * 8u;
          asm volatile("st.shared.v2.u32 [%0], {%1,%2};" ::"r"(dst0 + off), "r"(lo), "r"(hi) : "memory");
          asm volatile("st.shared.v2.u32 [%0], {%1,%2};" ::"r"(dst1 + off), "r"(lo), "r"(hi) : "memory");
        }
        {
          float4 v = ldg_cg_f4(&g_z[par][8 * p][0] + lane * 4);
          uint32_t lo = pack_bf16(v.x, v.y), hi = pack_bf16(v.z, v.w);
          uint32_t off = 4096u + (uint32_t)lane * 8u;
          asm volatile("st.shared.v2.u32 [%0], {%1,%2};" ::"r"(dst0 + off), "r"(lo), "r"(hi) : "memory");
          asm volatile("st.shared.v2.u32 [%0], {%1,%2};" ::"r"(dst1 + off), "r"(lo), "r"(hi) : "memory");
        }
        __syncwarp();
        if (lane == 0) mbar_arrive(BAR(B_KVREADY));
      }
      const uint32_t* flag = nullptr;
      if (lane < 12) {
        const int w = lane / 6, idx = lane - w * 6;
        if (odd ? idx < 5 : idx < 3) flag = &g_xflag[m][p][odd ? idx : 6 + idx][w];
      } else if (lane < 18) {
        const int w = (lane - 12) / 3, idx = lane - 12 - w * 3;
        flag = &g_pflag[m][odd][p][idx][w];
      }
      bool pending = flag != nullptr;
      uint32_t it = 0;
      while (__any_sync(0xffffffffu, pending)) {
        if (pending) {
          if (ld_acquire(flag) == tag || it > kSpinLimit) { mbar_arrive(BAR(B_XIN + lane)); pending = false; }
        }
        ++it;
        __nanosleep(32);
      }
    }
  } else {
    asm volatile("setmaxnreg.inc.sync.aligned.u32 240;");
    const uint32_t epoch = ld_relaxed(&g_epoch);
    const int par = epoch & 1;
    const int w = warp >> 2, wq = warp & 3, t128 = tid & 127;
    const int g = lane >> 2, tq = lane & 3;
    const uint32_t area = sbase + (uint32_t)w * 65536u;
    const bool elect = (t128 == 0);
    PROF(w, 22);
    const uint32_t dbase = (sbase & 0x3FFFFu) >> 4;
    uint32_t A[144];
    float rs0, rs1;
    auto release = [&](int st) {
      if (elect) { mbar_arrive_cluster(BAR(B_EMPTY + st), 0); mbar_arrive_cluster(BAR(B_EMPTY + st), 1); }
    };

    {
      const int row = wq * 16 + (lane & 7) + ((lane >> 3) & 1) * 8;
      const uint32_t rbase = area + row * 128;
      float s0[2][4] = {}, q0[2][4] = {}, q1[2][4] = {};
      const uint32_t ones = 0x3F803F80u;
#pragma unroll
      for (int b = 0; b < 8; b++) {
        mbar_wait(BAR(B_XFULL + w * 8 + b), 0);
        if (b == 0) PROF(w, 23);
        if (b == 7) PROF(w, 24);
#pragma unroll
        for (int kk = 0; kk < 4; kk++) {
          const int i = (b * 4 + kk) * 4;
          ldmatrix_x4(rbase + b * 8192 + (((kk * 2 + (lane >> 4)) ^ (row & 7)) << 4), A[i], A[i + 1], A[i + 2], A[i + 3]);
        }
#pragma unroll
        for (int kk = 0; kk < 4; kk++) {
          const int i = (b * 4 + kk) * 4;
          mma_16816(s0[kk & 1], A[i], A[i + 1], A[i + 2], A[i + 3], ones, ones);
          mma_16816(q0[kk & 1], A[i], A[i + 1], A[i + 2], A[i + 3], A[i], A[i + 2]);
          mma_16816(q1[kk & 1], A[i], A[i + 1], A[i + 2], A[i + 3], A[i + 1], A[i + 3]);
        }
      }
      const float mean0 = (s0[0][0] + s0[1][0]) * (1.f / 512.f), mean1 = (s0[0][2] + s0[1][2]) * (1.f / 512.f);
      const uint32_t m0 = pack_bf16(mean0, mean0), m1 = pack_bf16(mean1, mean1);
#pragma unroll
      for (int i = 0; i < 128; i += 2) {
        A[i] = hsub2_bf16(A[i], m0);
        A[i + 1] = hsub2_bf16(A[i + 1], m1);
      }
      float v0 = (g & 1) ? q0[0][1] + q0[1][1] : q0[0][0] + q0[1][0];
      float v1 = (g & 1) ? q1[0][3] + q1[1][3] : q1[0][2] + q1[1][2];
      const int src = 4 * g + (g >> 1);
      v0 = __shfl_sync(0xffffffffu, v0, src);
      v1 = __shfl_sync(0xffffffffu, v1, src);
      v0 = fmaxf(v0 * (1.f / 512.f) - mean0 * mean0, 0.f);
      v1 = fmaxf(v1 * (1.f / 512.f) - mean1 * mean1, 0.f);
      rs0 = rsqrtf(v0 + 1e-5f);
      rs1 = rsqrtf(v1 + 1e-5f);
      bar_sync(1 + w, 128);
      cluster_wait();
      PROF(w, 0);
      release(6); release(7);
      if (elect) mbar_arrive(BAR(B_XDONE));
    }

    auto gu_chunk = [&](float (&acc)[32], int f, int slot, int xslot, int hb) {
      const float c0 = rs0 * -1.4426950408889634f, c1 = rs1 * -1.4426950408889634f;
      const float q0 = rs0 * rs0, q1 = rs1 * rs1;
      uint32_t h[4];
#pragma unroll
      for (int i = 0; i < 4; i++) {
        const float ga = acc[f * 8 + 2 * i], gb = acc[f * 8 + 2 * i + 1];
        const float ua = acc[16 + f * 8 + 2 * i], ub = acc[16 + f * 8 + 2 * i + 1];
        const float c = (i & 1) ? c1 : c0, q = (i & 1) ? q1 : q0;
        const float da = 1.f + ex2f(fminf(ga * c, 60.f)), db = 1.f + ex2f(fminf(gb * c, 60.f));
        const float rq = rcpf(da * db) * q;
        h[i] = pack_bf16(ga * ua * (db * rq), gb * ub * (da * rq));
      }
      const int jj = hb * 2 + f;
      sts_u4(area + slot * 8192 + jj * 2048 + t128 * 16, h[0], h[1], h[2], h[3]);
      stg_u4(&g_xbuf[m][p][xslot][w][jj][t128], h[0], h[1], h[2], h[3]);
    };
    auto kv_stage = [&](float (&acc)[32], int c, int hb) {
      const int srow = wq * 16 + (lane & 7) + ((lane >> 3) & 1) * 8;
      const uint32_t base = area + (3 + c) * 8192 + srow * 128;
#pragma unroll
      for (int jj = 0; jj < 2; jj++) {
        const int a = c * 16 + jj * 8;
        uint32_t r0, r1, r2, r3;
        if (c == 0) {
          r0 = pack_bf16(phi_f(acc[a] * rs0), phi_f(acc[a + 1] * rs0));
          r1 = pack_bf16(phi_f(acc[a + 2] * rs1), phi_f(acc[a + 3] * rs1));
          r2 = pack_bf16(phi_f(acc[a + 4] * rs0), phi_f(acc[a + 5] * rs0));
          r3 = pack_bf16(phi_f(acc[a + 6] * rs1), phi_f(acc[a + 7] * rs1));
        } else {
          r0 = pack_bf16(acc[a] * rs0, acc[a + 1] * rs0);
          r1 = pack_bf16(acc[a + 2] * rs1, acc[a + 3] * rs1);
          r2 = pack_bf16(acc[a + 4] * rs0, acc[a + 5] * rs0);
          r3 = pack_bf16(acc[a + 6] * rs1, acc[a + 7] * rs1);
        }
        stmatrix_x4(base + (((hb * 4 + jj * 2 + (lane >> 4)) ^ (srow & 7)) << 4), r0, r1, r2, r3);
      }
    };
    auto q_head = [&](float (&acc)[32], int c, int slot, uint32_t b0, uint32_t b1, uint32_t b2, uint32_t b3, uint32_t z0, uint32_t z1) {
      const int a = c * 8;
      const uint32_t a0 = pack_bf16(phi_f(acc[a] * rs0), phi_f(acc[a + 1] * rs0));
      const uint32_t a1 = pack_bf16(phi_f(acc[a + 2] * rs1), phi_f(acc[a + 3] * rs1));
      const uint32_t a2 = pack_bf16(phi_f(acc[a + 4] * rs0), phi_f(acc[a + 5] * rs0));
      const uint32_t a3 = pack_bf16(phi_f(acc[a + 6] * rs1), phi_f(acc[a + 7] * rs1));
      float n0[4] = {0.f, 0.f, 0.f, 0.f}, n1[4] = {0.f, 0.f, 0.f, 0.f}, dn[4] = {0.f, 0.f, 0.f, 0.f};
      mma_16816(n0, a0, a1, a2, a3, b0, b1);
      mma_16816(n1, a0, a1, a2, a3, b2, b3);
      mma_16816(dn, a0, a1, a2, a3, z0, z1);
      const float i0 = __fdividef(1.f, dn[0] + 1e-6f), i1 = __fdividef(1.f, dn[2] + 1e-6f);
      const uint32_t o0 = pack_bf16(n0[0] * i0, n0[1] * i0), o1 = pack_bf16(n0[2] * i1, n0[3] * i1);
      const uint32_t o2 = pack_bf16(n1[0] * i0, n1[1] * i0), o3 = pack_bf16(n1[2] * i1, n1[3] * i1);
      sts_u4(area + slot * 8192 + c * 2048 + t128 * 16, o0, o1, o2, o3);
      stg_u4(&g_xbuf[m][p][slot][w][c][t128], o0, o1, o2, o3);
    };
    const uint32_t kvb = area + 5 * 8192;
    const uint32_t kvfrag = kvb + ((lane & 7) + ((lane >> 3) & 1) * 8) * 32 + (lane >> 4) * 16;
    auto signal = [&](int e) {
      __syncwarp();
      if (lane == 0) mbar_arrive(BAR(B_EV + w * 8 + e));
    };

    float accB[32];
#pragma unroll 1
    for (int t = 0; t < 5; t++) {
      float accA[32];
      const uint32_t ph = t & 1;
      const int kindP = t == 0 ? K_NONE : ((odd && t <= 2) ? K_KV : K_GU);
      const int kindC = odd ? (t < 2 ? K_KV : K_GU) : (t < 4 ? K_GU : K_Q);
      const int slotP = odd ? t - 3 : t - 1, xslotP = odd ? t + 3 : t - 1;
      const int slotC = odd ? t - 2 : t, xslotC = odd ? t + 4 : t;
      static_for<8>([&](auto kc) {
        constexpr int k = decltype(kc)::value;
        mbar_wait(BAR(B_FULL + k), ph);
        wgmma_fence();
        static_for<8>([&](auto kkc) {
          constexpr int kk = decltype(kkc)::value;
          constexpr int i = ((k & 3) * 8 + kk) * 4;
          constexpr uint32_t lo = desc_lo(stage_off(k) + kk * 1024, 8192);
          if constexpr (k < 4) wgmma_n64_rs<((k & 3) | kk) != 0, lo, kHi64>(accA, A[i], A[i + 1], A[i + 2], A[i + 3], dbase);
          else wgmma_n64_rs<((k & 3) | kk) != 0, lo, kHi64>(accB, A[i], A[i + 1], A[i + 2], A[i + 3], dbase);
        });
        wgmma_commit();
        if (k > 0) {
          wgmma_wait<1>();
          release(k - 1);
        }
        if constexpr (k < 4) {
          if (kindP == K_GU) {
            if (k == 1 || k == 2) gu_chunk(accB, k - 1, slotP, xslotP, 1);
            if (k == 2) signal(t - 1);
          } else if (kindP == K_KV) {
            if (k == 1 || k == 2) kv_stage(accB, k - 1, 1);
            if (k == 3) {
              float kvacc[36];
              fence_proxy_async();
              bar_sync(1 + w, 128);
              wgmma_fence();
              static_for<4>([&](auto kkc) {
                constexpr int kk = decltype(kkc)::value;
                wgmma_n72_ss_tt<kk != 0, desc_lo(3 * 8192 + kk * 2048, 0), desc_lo(4 * 8192 + kk * 2048, 8192 - kk * 2048)>(kvacc, dbase + w * 4096);
              });
              wgmma_commit();
              wgmma_wait<0>();
              float c[8];
#pragma unroll
              for (int i = 0; i < 8; i++)
                c[i] = wq == 0 ? kvacc[i] : (wq == 1 ? kvacc[8 + i] : (wq == 2 ? kvacc[16 + i] : kvacc[24 + i]));
              const int head = (2 * p + t - 1) * 4 + wq;
              float* kvp = &g_kv[par][head][0][0];
              red_add_v2(kvp + g * 16 + 2 * tq, c[0], c[1]);
              red_add_v2(kvp + (g + 8) * 16 + 2 * tq, c[2], c[3]);
              red_add_v2(kvp + g * 16 + 8 + 2 * tq, c[4], c[5]);
              red_add_v2(kvp + (g + 8) * 16 + 8 + 2 * tq, c[6], c[7]);
              if (tq == 0) {
                red_add(&g_z[par][head][g], kvacc[32]);
                red_add(&g_z[par][head][g + 8], kvacc[34]);
              }
              signal(t - 1);
            }
          }
        } else {
          constexpr int c = k - 4;
          if (kindC == K_GU) {
            if (c < 2) gu_chunk(accA, c, slotC, xslotC, 0);
          } else if (kindC == K_KV) {
            if (c == 0 && t == 0) sts_u4(area + 5 * 8192 + t128 * 16, 0x3F803F80u, 0x3F803F80u, 0x3F803F80u, 0x3F803F80u);
            if (c < 2) kv_stage(accA, c, 0);
          } else {
            if (c == 0) mbar_wait(BAR(B_KVREADY), 0);
            uint32_t b0, b1, b2, b3;
            ldmatrix_x4_trans(kvfrag + c * 512, b0, b1, b2, b3);
            const uint32_t z0 = lds_u32(kvb + 4096 + c * 32 + tq * 4), z1 = lds_u32(kvb + 4096 + c * 32 + 16 + tq * 4);
            q_head(accA, c, 4, b0, b1, b2, b3, z0, z1);
          }
        }
      });
      wgmma_wait<0>();
      release(7);
      PROF(w, 1 + 2 * t);
    }
    if (odd) {
      gu_chunk(accB, 0, 2, 8, 1);
      gu_chunk(accB, 1, 2, 8, 1);
    } else {
      uint32_t Bf[4][6];
#pragma unroll
      for (int c = 0; c < 4; c++) {
        ldmatrix_x4_trans(kvfrag + (4 + c) * 512, Bf[c][0], Bf[c][1], Bf[c][2], Bf[c][3]);
        Bf[c][4] = lds_u32(kvb + 4096 + (4 + c) * 32 + tq * 4);
        Bf[c][5] = lds_u32(kvb + 4096 + (4 + c) * 32 + 16 + tq * 4);
      }
      bar_sync(1 + w, 128);
#pragma unroll
      for (int c = 0; c < 4; c++) q_head(accB, c, 5, Bf[c][0], Bf[c][1], Bf[c][2], Bf[c][3], Bf[c][4], Bf[c][5]);
    }
    signal(4);
    PROF(w, 10);

    const int n_own = odd ? 3 : 6;
    auto load_a = [&](int kb) {
      if (kb < n_own) {
#pragma unroll
        for (int jj = 0; jj < 4; jj++) {
          const int i = (kb * 4 + jj) * 4;
          lds_u4(area + kb * 8192 + jj * 2048 + t128 * 16, A[i], A[i + 1], A[i + 2], A[i + 3]);
        }
      } else {
        const int xs = odd ? kb - 3 : kb;
        const int ev = odd ? (kb - 3 < 4 ? kb - 3 : 4) : kb - 6;
        mbar_wait(BAR(B_XIN + w * 6 + ev), 0);
#pragma unroll
        for (int jj = 0; jj < 4; jj++) {
          const int i = (kb * 4 + jj) * 4;
          uint4 v = ldg_cg_u4(&g_xbuf[m][p][xs][w][jj][t128]);
          A[i] = v.x; A[i + 1] = v.y; A[i + 2] = v.z; A[i + 3] = v.w;
        }
      }
    };
#pragma unroll
    for (int kb = 0; kb < 7; kb++) load_a(kb);
    PROF(w, 11);

    const int orow = m * 128 + w * 64 + wq * 16 + g;
    const int ocol = odd * 256 + p * 64 + 2 * tq;
    float acc2[2][32];
    float4 P0[8], P1[8], P2[8];
    uint32_t xr[16];
    auto send = [&](float (&acc)[32], int bi) {
      float4* dst = &g_pbuf[m][odd][(p + 1 + bi) & 3][bi][w][0][t128];
#pragma unroll
      for (int q = 0; q < 8; q++) stg_f4(dst + q * 128, acc[q * 4], acc[q * 4 + 1], acc[q * 4 + 2], acc[q * 4 + 3]);
      signal(5 + bi);
      PROF(w, 12 + 2 * bi);
    };
    static_for<36>([&](auto ic) {
      constexpr int i = decltype(ic)::value, bi = p2_bi(i), kb = p2_kb(i), j = i >> 1, st = j & 7;
      if (i == 9) { load_a(7); load_a(8); }
      if ((i & 1) == 0) mbar_wait(BAR(B_FULL + st), (5 + (j >> 3)) & 1);
      wgmma_fence();
      static_for<4>([&](auto kkc) {
        constexpr int kk = decltype(kkc)::value, a = (kb * 4 + kk) * 4;
        wgmma_n64_rs<(kb | kk) != 0, desc_lo(stage_off(st) + (i & 1) * 8192 + kk * 2048, 0), kHi128>(acc2[bi & 1], A[a], A[a + 1], A[a + 2], A[a + 3], dbase);
      });
      wgmma_commit();
      if (i > 0) {
        wgmma_wait<1>();
        if ((i & 1) == 0 && j - 1 <= 9) release((j - 1) & 7);
      }
      if constexpr (i == 16) send(acc2[0], 0);
      if constexpr (i == 18) send(acc2[1], 1);
      if constexpr (i == 27) send(acc2[0], 2);
      if constexpr (i == 29) {
        mbar_wait(BAR(B_PIN + w * 3 + 0), 0);
#pragma unroll
        for (int q = 0; q < 8; q++) P0[q] = ldg_cg_f4(&g_pbuf[m][odd][p][0][w][q][t128]);
      }
      if constexpr (i == 31) {
        mbar_wait(BAR(B_PIN + w * 3 + 1), 0);
#pragma unroll
        for (int q = 0; q < 8; q++) P1[q] = ldg_cg_f4(&g_pbuf[m][odd][p][1][w][q][t128]);
      }
      if constexpr (i == 32) {
#pragma unroll
        for (int q = 0; q < 8; q++) {
          xr[2 * q] = __ldg((const uint32_t*)(x + (size_t)orow * kD + ocol + q * 8));
          xr[2 * q + 1] = __ldg((const uint32_t*)(x + (size_t)(orow + 8) * kD + ocol + q * 8));
        }
      }
      if constexpr (i == 35) {
        mbar_wait(BAR(B_PIN + w * 3 + 2), 0);
#pragma unroll
        for (int q = 0; q < 8; q++) P2[q] = ldg_cg_f4(&g_pbuf[m][odd][p][2][w][q][t128]);
      }
    });
    wgmma_wait<0>();
    PROF(w, 18);
#pragma unroll
    for (int q = 0; q < 8; q++) {
      const float r0 = acc2[1][q * 4 + 0] + P0[q].x + P1[q].x + P2[q].x + __uint_as_float(xr[2 * q] << 16);
      const float r1 = acc2[1][q * 4 + 1] + P0[q].y + P1[q].y + P2[q].y + __uint_as_float(xr[2 * q] & 0xffff0000u);
      const float r2 = acc2[1][q * 4 + 2] + P0[q].z + P1[q].z + P2[q].z + __uint_as_float(xr[2 * q + 1] << 16);
      const float r3 = acc2[1][q * 4 + 3] + P0[q].w + P1[q].w + P2[q].w + __uint_as_float(xr[2 * q + 1] & 0xffff0000u);
      *(uint32_t*)(out + (size_t)orow * kD + ocol + q * 8) = pack_bf16(r0, r1);
      *(uint32_t*)(out + (size_t)(orow + 8) * kD + ocol + q * 8) = pack_bf16(r2, r3);
    }
    PROF(w, 19);
    if (tid == 0) {
      const uint32_t old = atomicAdd(&g_done, 1u);
      if ((old & 127u) == 127u) *(volatile uint32_t*)&g_epoch = epoch + 1u;
    }
  }
#undef BAR
}

typedef CUresult (*EncodeFn)(CUtensorMap*, CUtensorMapDataType, cuuint32_t, void*, const cuuint64_t*, const cuuint64_t*,
                             const cuuint32_t*, const cuuint32_t*, CUtensorMapInterleave, CUtensorMapSwizzle,
                             CUtensorMapL2promotion, CUtensorMapFloatOOBfill);

void make_map(EncodeFn enc, CUtensorMap* tm, const void* ptr, int rows, int cols, bool narrow) {
  cuuint64_t gd[2] = {(cuuint64_t)cols, (cuuint64_t)rows};
  cuuint64_t gs[1] = {(cuuint64_t)cols * 2};
  cuuint32_t bd[2] = {narrow ? 32u : 64u, narrow ? 128u : 64u};
  cuuint32_t es[2] = {1, 1};
  enc(tm, CU_TENSOR_MAP_DATA_TYPE_BFLOAT16, 2, const_cast<void*>(ptr), gd, gs, bd, es, CU_TENSOR_MAP_INTERLEAVE_NONE,
      narrow ? CU_TENSOR_MAP_SWIZZLE_64B : CU_TENSOR_MAP_SWIZZLE_128B, CU_TENSOR_MAP_L2_PROMOTION_L2_256B, CU_TENSOR_MAP_FLOAT_OOB_FILL_NONE);
}

}

extern "C" void kernel_launch(void* const* d_in, const int* in_sizes, int n_in, void* d_out, int out_size) {
  static EncodeFn enc = nullptr;
  if (!enc) {
    void* fn = nullptr;
    cudaDriverEntryPointQueryResult qr;
    cudaGetDriverEntryPoint("cuTensorMapEncodeTiled", &fn, cudaEnableDefault, &qr);
    enc = (EncodeFn)fn;
    cudaFuncSetAttribute(fused_kernel, cudaFuncAttributeMaxDynamicSharedMemorySize, kSmemBytes);
  }
  CUtensorMap tm_x, tm_wqkv, tm_w1, tm_w3, tm_w2, tm_wo;
  make_map(enc, &tm_x, d_in[0], kS, kD, false);
  make_map(enc, &tm_wqkv, d_in[1], kD, 3 * kD, true);
  make_map(enc, &tm_wo, d_in[2], kD, kD, false);
  make_map(enc, &tm_w1, d_in[4], kD, kF, true);
  make_map(enc, &tm_w3, d_in[5], kD, kF, true);
  make_map(enc, &tm_w2, d_in[6], kF, kD, false);
  fused_kernel<<<128, 384, kSmemBytes>>>(tm_x, tm_wqkv, tm_w1, tm_w3, tm_w2, tm_wo, (const __nv_bfloat16*)d_in[0],
                                         (__nv_bfloat16*)d_out);
}
```

```cpp
#include <cuda_runtime.h>
#include <cuda_bf16.h>
#include <cuda.h>
#include <stdint.h>

namespace {

constexpr int kS = 2048, kD = 512, kF = 1792;
constexpr uint32_t kSpinLimit = 1u << 22;

__device__ uint4    g_xbuf[16][4][9][2][4][128];
__device__ float4   g_pbuf[16][2][4][3][2][8][128];
__device__ float    g_kv[2][32][16][16];
__device__ float    g_z[2][32][16];
__device__ uint32_t g_xflag[16][4][9][2];
__device__ uint32_t g_pflag[16][2][4][3][2];
__device__ uint32_t g_kvcnt[4][32];
__device__ uint32_t g_epoch;
__device__ uint32_t g_done;
#define PROF(wg, i) do {} while (0)

__device__ __forceinline__ uint32_t smem_u32(const void* p) { return (uint32_t)__cvta_generic_to_shared(p); }
__device__ __forceinline__ void mbar_init(uint32_t bar, uint32_t cnt) {
  asm volatile("mbarrier.init.shared::cta.b64 [%0], %1;" ::"r"(bar), "r"(cnt) : "memory");
}
__device__ __forceinline__ void mbar_expect_tx(uint32_t bar, uint32_t bytes) {
  asm volatile("mbarrier.arrive.expect_tx.shared::cta.b64 _, [%0], %1;" ::"r"(bar), "r"(bytes) : "memory");
}
__device__ __forceinline__ void mbar_arrive(uint32_t bar) {
  asm volatile("mbarrier.arrive.shared::cta.b64 _, [%0];" ::"r"(bar) : "memory");
}
__device__ __forceinline__ void mbar_wait(uint32_t bar, uint32_t parity) {
  asm volatile(
      "{\n.reg .pred p;\n"
      "LAB_WAIT:\n"
      "mbarrier.try_wait.parity.shared::cta.b64 p, [%0], %1;\n"
      "@p bra DONE;\n"
      "bra LAB_WAIT;\n"
      "DONE:\n}" ::"r"(bar), "r"(parity) : "memory");
}
__device__ __forceinline__ void tma_load_2d(uint32_t dst, const CUtensorMap* tm, uint32_t bar, int c0, int c1) {
  asm volatile(
      "cp.async.bulk.tensor.2d.shared::cluster.global.mbarrier::complete_tx::bytes [%0], [%1, {%3, %4}], [%2];" ::"r"(dst),
      "l"(tm), "r"(bar), "r"(c0), "r"(c1)
      : "memory");
}
__device__ __forceinline__ void tma_load_2d_mc(uint32_t dst, const CUtensorMap* tm, uint32_t bar, int c0, int c1) {
  asm volatile(
      "cp.async.bulk.tensor.2d.shared::cluster.global.mbarrier::complete_tx::bytes.multicast::cluster [%0], [%1, {%3, %4}], [%2], %5;" ::"r"(dst),
      "l"(tm), "r"(bar), "r"(c0), "r"(c1), "h"((uint16_t)3)
      : "memory");
}
__device__ __forceinline__ void mbar_arrive_cluster(uint32_t bar, uint32_t cta) {
  asm volatile("{\n.reg .b32 ra;\nmapa.shared::cluster.u32 ra, %0, %1;\nmbarrier.arrive.shared::cluster.b64 _, [ra];\n}" ::"r"(bar), "r"(cta) : "memory");
}
__device__ __forceinline__ void prefetch_tmap(const CUtensorMap* tm) {
  asm volatile("prefetch.tensormap [%0];" ::"l"(tm) : "memory");
}
__device__ __forceinline__ void wgmma_fence() { asm volatile("wgmma.fence.sync.aligned;" ::: "memory"); }
__device__ __forceinline__ void wgmma_commit() { asm volatile("wgmma.commit_group.sync.aligned;" ::: "memory"); }
template <int N>
__device__ __forceinline__ void wgmma_wait() { asm volatile("wgmma.wait_group.sync.aligned %0;" ::"n"(N) : "memory"); }
__device__ __forceinline__ void bar_sync(int id, int n) { asm volatile("bar.sync %0, %1;" ::"r"(id), "r"(n) : "memory"); }
__device__ __forceinline__ void bar_arrive(int id, int n) { asm volatile("bar.arrive %0, %1;" ::"r"(id), "r"(n) : "memory"); }
__device__ __forceinline__ void fence_proxy_async() { asm volatile("fence.proxy.async.shared::cta;" ::: "memory"); }

__device__ __forceinline__ uint32_t ld_acquire(const uint32_t* p) {
  uint32_t v;
  asm volatile("ld.acquire.gpu.global.u32 %0, [%1];" : "=r"(v) : "l"(p) : "memory");
  return v;
}
__device__ __forceinline__ uint32_t ld_relaxed(const uint32_t* p) {
  uint32_t v;
  asm volatile("ld.relaxed.gpu.global.u32 %0, [%1];" : "=r"(v) : "l"(p));
  return v;
}
__device__ __forceinline__ void cluster_wait() { asm volatile("barrier.cluster.wait.aligned;" ::: "memory"); }
__device__ __forceinline__ void st_relaxed(uint32_t* p, uint32_t v) {
  asm volatile("st.relaxed.gpu.global.u32 [%0], %1;" ::"l"(p), "r"(v) : "memory");
}
__device__ __forceinline__ void wait_flag_eq(const uint32_t* p, uint32_t val) {
  uint32_t it = 0;
  while (ld_acquire(p) != val) {
    if (++it > kSpinLimit) break;
  }
}
__device__ __forceinline__ void wait_count_ge(const uint32_t* p, uint32_t val) {
  uint32_t it = 0;
  while ((int32_t)(ld_acquire(p) - val) < 0) {
    __nanosleep(64);
    if (++it > kSpinLimit) break;
  }
}
__device__ __forceinline__ uint4 ldg_cg_u4(const void* p) {
  uint4 v;
  asm volatile("ld.global.cg.v4.u32 {%0,%1,%2,%3}, [%4];" : "=r"(v.x), "=r"(v.y), "=r"(v.z), "=r"(v.w) : "l"(p) : "memory");
  return v;
}
__device__ __forceinline__ float4 ldg_cg_f4(const void* p) {
  float4 v;
  asm volatile("ld.global.cg.v4.f32 {%0,%1,%2,%3}, [%4];" : "=f"(v.x), "=f"(v.y), "=f"(v.z), "=f"(v.w) : "l"(p) : "memory");
  return v;
}
__device__ __forceinline__ void stg_u4(void* p, uint32_t a, uint32_t b, uint32_t c, uint32_t d) {
  asm volatile("st.global.v4.u32 [%0], {%1,%2,%3,%4};" ::"l"(p), "r"(a), "r"(b), "r"(c), "r"(d) : "memory");
}
__device__ __forceinline__ void stg_f4(void* p, float a, float b, float c, float d) {
  asm volatile("st.global.v4.f32 [%0], {%1,%2,%3,%4};" ::"l"(p), "f"(a), "f"(b), "f"(c), "f"(d) : "memory");
}
__device__ __forceinline__ void sts_u4(uint32_t addr, uint32_t a, uint32_t b, uint32_t c, uint32_t d) {
  asm volatile("st.shared.v4.u32 [%0], {%1,%2,%3,%4};" ::"r"(addr), "r"(a), "r"(b), "r"(c), "r"(d) : "memory");
}
__device__ __forceinline__ void lds_u4(uint32_t addr, uint32_t& a, uint32_t& b, uint32_t& c, uint32_t& d) {
  asm volatile("ld.shared.v4.u32 {%0,%1,%2,%3}, [%4];" : "=r"(a), "=r"(b), "=r"(c), "=r"(d) : "r"(addr) : "memory");
}
__device__ __forceinline__ uint32_t lds_u32(uint32_t addr) {
  uint32_t v;
  asm volatile("ld.shared.u32 %0, [%1];" : "=r"(v) : "r"(addr) : "memory");
  return v;
}
__device__ __forceinline__ void ldmatrix_x4(uint32_t addr, uint32_t& a, uint32_t& b, uint32_t& c, uint32_t& d) {
  asm volatile("ldmatrix.sync.aligned.m8n8.x4.shared.b16 {%0,%1,%2,%3}, [%4];" : "=r"(a), "=r"(b), "=r"(c), "=r"(d) : "r"(addr) : "memory");
}
__device__ __forceinline__ void ldmatrix_x4_trans(uint32_t addr, uint32_t& a, uint32_t& b, uint32_t& c, uint32_t& d) {
  asm volatile("ldmatrix.sync.aligned.m8n8.x4.trans.shared.b16 {%0,%1,%2,%3}, [%4];" : "=r"(a), "=r"(b), "=r"(c), "=r"(d) : "r"(addr) : "memory");
}
__device__ __forceinline__ void stmatrix_x4(uint32_t addr, uint32_t a, uint32_t b, uint32_t c, uint32_t d) {
  asm volatile("stmatrix.sync.aligned.m8n8.x4.shared.b16 [%0], {%1,%2,%3,%4};" ::"r"(addr), "r"(a), "r"(b), "r"(c), "r"(d) : "memory");
}
__device__ __forceinline__ void mma_16816(float (&c)[4], uint32_t a0, uint32_t a1, uint32_t a2, uint32_t a3, uint32_t b0, uint32_t b1) {
  asm volatile(
      "mma.sync.aligned.m16n8k16.row.col.f32.bf16.bf16.f32 {%0,%1,%2,%3}, {%4,%5,%6,%7}, {%8,%9}, {%0,%1,%2,%3};"
      : "+f"(c[0]), "+f"(c[1]), "+f"(c[2]), "+f"(c[3])
      : "r"(a0), "r"(a1), "r"(a2), "r"(a3), "r"(b0), "r"(b1));
}
__device__ __forceinline__ uint32_t pack_bf16(float lo, float hi) {
  uint32_t r;
  asm("cvt.rn.bf16x2.f32 %0, %1, %2;" : "=r"(r) : "f"(hi), "f"(lo));
  return r;
}
__device__ __forceinline__ uint32_t hsub2_bf16(uint32_t a, uint32_t b) {
  uint32_t r;
  asm("sub.rn.bf16x2 %0, %1, %2;" : "=r"(r) : "r"(a), "r"(b));
  return r;
}
__device__ __forceinline__ float ex2f(float x) {
  float r;
  asm("ex2.approx.ftz.f32 %0, %1;" : "=f"(r) : "f"(x));
  return r;
}
__device__ __forceinline__ float rcpf(float x) {
  float r;
  asm("rcp.approx.ftz.f32 %0, %1;" : "=f"(r) : "f"(x));
  return r;
}
__device__ __forceinline__ void red_add_v2(float* p, float a, float b) {
  asm volatile("red.relaxed.gpu.global.add.v2.f32 [%0], {%1,%2};" ::"l"(p), "f"(a), "f"(b) : "memory");
}
__device__ __forceinline__ void red_add(float* p, float a) {
  asm volatile("red.relaxed.gpu.global.add.f32 [%0], %1;" ::"l"(p), "f"(a) : "memory");
}
__device__ __forceinline__ float phi_f(float t) {
  float e = ex2f(t * 1.4426950408889634f);
  return (t > 0.f ? t + 1.f : e) + 1e-6f;
}

#define R8(a, o) "+f"(a[o + 0]), "+f"(a[o + 1]), "+f"(a[o + 2]), "+f"(a[o + 3]), "+f"(a[o + 4]), "+f"(a[o + 5]), "+f"(a[o + 6]), "+f"(a[o + 7])

#define W8(a, o) "=f"(a[o + 0]), "=f"(a[o + 1]), "=f"(a[o + 2]), "=f"(a[o + 3]), "=f"(a[o + 4]), "=f"(a[o + 5]), "=f"(a[o + 6]), "=f"(a[o + 7])
#define D32 "{%0,%1,%2,%3,%4,%5,%6,%7,%8,%9,%10,%11,%12,%13,%14,%15,%16,%17,%18,%19,%20,%21,%22,%23,%24,%25,%26,%27,%28,%29,%30,%31}"
#define D36 "{%0,%1,%2,%3,%4,%5,%6,%7,%8,%9,%10,%11,%12,%13,%14,%15,%16,%17,%18,%19,%20,%21,%22,%23,%24,%25,%26,%27,%28,%29,%30,%31,%32,%33,%34,%35}"

constexpr uint32_t kHi128 = (1024u >> 4) | (1u << 30);
constexpr uint32_t kHi64 = (512u >> 4) | (2u << 30);
__host__ __device__ constexpr uint32_t desc_lo(uint32_t off, uint32_t lbo) { return (off >> 4) | ((lbo >> 4) << 16); }

template <bool ACC, uint32_t LO, uint32_t HI>
__device__ __forceinline__ void wgmma_n64_rs(float (&d)[32], uint32_t a0, uint32_t a1, uint32_t a2, uint32_t a3, uint32_t base) {
  if (ACC) {
    asm volatile(
        "{\n.reg .pred p;\n.reg .b32 lo;\n.reg .b64 dd;\nsetp.eq.b32 p, 0, 0;\nadd.u32 lo, %36, %37;\nmov.b64 dd, {lo, %38};\n"
        "wgmma.mma_async.sync.aligned.m64n64k16.f32.bf16.bf16 " D32 ", {%32,%33,%34,%35}, dd, p, 1, 1, 1;\n}"
        : R8(d, 0), R8(d, 8), R8(d, 16), R8(d, 24)
        : "r"(a0), "r"(a1), "r"(a2), "r"(a3), "r"(base), "n"(LO), "n"(HI));
  } else {
    asm volatile(
        "{\n.reg .pred p;\n.reg .b32 lo;\n.reg .b64 dd;\nsetp.ne.b32 p, 0, 0;\nadd.u32 lo, %36, %37;\nmov.b64 dd, {lo, %38};\n"
        "wgmma.mma_async.sync.aligned.m64n64k16.f32.bf16.bf16 " D32 ", {%32,%33,%34,%35}, dd, p, 1, 1, 1;\n}"
        : W8(d, 0), W8(d, 8), W8(d, 16), W8(d, 24)
        : "r"(a0), "r"(a1), "r"(a2), "r"(a3), "r"(base), "n"(LO), "n"(HI));
  }
}
template <bool ACC, uint32_t LOA, uint32_t LOB>
__device__ __forceinline__ void wgmma_n72_ss_tt(float (&d)[36], uint32_t base) {
  if (ACC) {
    asm volatile(
        "{\n.reg .pred p;\n.reg .b32 lo;\n.reg .b64 da, db;\nsetp.eq.b32 p, 0, 0;\n"
        "add.u32 lo, %36, %37;\nmov.b64 da, {lo, %39};\nadd.u32 lo, %36, %38;\nmov.b64 db, {lo, %39};\n"
        "wgmma.mma_async.sync.aligned.m64n72k16.f32.bf16.bf16 " D36 ", da, db, p, 1, 1, 1, 1;\n}"
        : R8(d, 0), R8(d, 8), R8(d, 16), R8(d, 24), "+f"(d[32]), "+f"(d[33]), "+f"(d[34]), "+f"(d[35])
        : "r"(base), "n"(LOA), "n"(LOB), "n"(kHi128));
  } else {
    asm volatile(
        "{\n.reg .pred p;\n.reg .b32 lo;\n.reg .b64 da, db;\nsetp.ne.b32 p, 0, 0;\n"
        "add.u32 lo, %36, %37;\nmov.b64 da, {lo, %39};\nadd.u32 lo, %36, %38;\nmov.b64 db, {lo, %39};\n"
        "wgmma.mma_async.sync.aligned.m64n72k16.f32.bf16.bf16 " D36 ", da, db, p, 1, 1, 1, 1;\n}"
        : W8(d, 0), W8(d, 8), W8(d, 16), W8(d, 24), "=f"(d[32]), "=f"(d[33]), "=f"(d[34]), "=f"(d[35])
        : "r"(base), "n"(LOA), "n"(LOB), "n"(kHi128));
  }
}

template <int V> struct IC { static constexpr int value = V; };
template <int N, int I = 0, typename F>
__device__ __forceinline__ void static_for(F&& f) {
  if constexpr (I < N) { f(IC<I>{}); static_for<N, I + 1>(f); }
}

__host__ __device__ constexpr uint32_t stage_off(int st) {
  return st < 6 ? 131072u + (uint32_t)st * 16384u : (uint32_t)(st - 6) * 65536u + 49152u;
}

constexpr int B_FULL = 0, B_EMPTY = 8, B_XFULL = 16, B_XDONE = 32, B_KVREADY = 33, B_EV = 34, B_XIN = 50, B_PIN = 62, B_COUNT = 68;
constexpr uint32_t kBarOff = 229376;
constexpr int kSmemBytes = 229376 + 1024;

__host__ __device__ constexpr int p2_bi(int i) { return i < 7 ? 0 : i < 14 ? 1 : i < 16 ? 0 : i < 18 ? 1 : i / 9; }
__host__ __device__ constexpr int p2_kb(int i) { return i < 7 ? i : i < 14 ? i - 7 : i < 16 ? i - 7 : i < 18 ? i - 9 : i % 9; }

enum { K_NONE = 0, K_GU = 1, K_KV = 2, K_Q = 3 };

__global__ void __cluster_dims__(2, 1, 1) __launch_bounds__(384, 1)
fused_kernel(const __grid_constant__ CUtensorMap tm_x, const __grid_constant__ CUtensorMap tm_wqkv,
             const __grid_constant__ CUtensorMap tm_w1, const __grid_constant__ CUtensorMap tm_w3,
             const __grid_constant__ CUtensorMap tm_w2, const __grid_constant__ CUtensorMap tm_wo,
             const __nv_bfloat16* __restrict__ x, __nv_bfloat16* __restrict__ out) {
  extern __shared__ __align__(1024) uint8_t smem_raw[];
  const uint32_t sbase = __shfl_sync(0xffffffffu, smem_u32(smem_raw), 0);
  const uint32_t bars = sbase + kBarOff;
  const int tid = threadIdx.x, lane = tid & 31;
  const int warp = __shfl_sync(0xffffffffu, tid >> 5, 0);
  const int cr = blockIdx.x & 1;
  const int r = (blockIdx.x >> 1) & 7, m = ((blockIdx.x >> 4) << 1) | cr, p = r >> 1, odd = r & 1;
#define BAR(i) (bars + 8u * (uint32_t)(i))
  if (warp == 8) {
    if (lane < 16) { mbar_init(BAR(B_XFULL + lane), 1); mbar_init(BAR(B_EV + lane), 4); }
    else if (lane < 24) { mbar_init(BAR(B_FULL + lane - 16), 1); mbar_init(BAR(B_EMPTY + lane - 16), 4); }
    else if (lane == 24) { mbar_init(BAR(B_XDONE), 2); mbar_init(BAR(B_KVREADY), 1); }
    if (lane < 18) mbar_init(BAR(B_XIN + lane), 1);
    asm volatile("fence.mbarrier_init.release.cluster;" ::: "memory");
    fence_proxy_async();
    __syncwarp();
  }
  asm volatile("barrier.cluster.arrive.relaxed.aligned;" ::: "memory");
  PROF((tid >> 7), 21);
  if (tid == 256) {
    if (sbase & 1023u) __trap();
    for (int b = 0; b < 8; b++) {
      mbar_expect_tx(BAR(B_XFULL + b), 8192);
      tma_load_2d(sbase + b * 8192, &tm_x, BAR(B_XFULL + b), b * 64, m * 128);
    }
  } else if (tid == 288) {
    prefetch_tmap(odd ? &tm_wqkv : (cr ? &tm_w3 : &tm_w1));
  }
  __syncthreads();
  PROF((tid >> 7), 20);

  if (warp >= 8) {
    asm volatile("setmaxnreg.dec.sync.aligned.u32 24;");
    PROF(2, 3);
    cluster_wait();
    PROF(2, 2);
    const uint32_t epoch = warp == 8 ? 0u : ld_relaxed(&g_epoch);
    const uint32_t tag = epoch + 1u;
    const int par = epoch & 1;
    if (warp == 8) {
      if (lane == 0) {
        for (int j = 0; j < 10; j++) {
          const CUtensorMap* tm;
          int col;
          if (!odd) {
            if (j < 8) { tm = cr ? &tm_w3 : &tm_w1; col = 7 * p * 64 + j * 32; }
            else { tm = &tm_wqkv; col = 128 * p + (j - 8) * 64 + cr * 32; }
          } else {
            if (j < 4) { tm = &tm_wqkv; col = 512 + cr * 512 + 128 * p + j * 32; }
            else { tm = cr ? &tm_w3 : &tm_w1; col = (7 * p + 4) * 64 + (j - 4) * 32; }
          }
          const int t = j >> 1;
          for (int kq = 0; kq < 4; kq++) {
            const int k = (j & 1) * 4 + kq;
            if (j == 0 && kq == 2) {
              for (int b = 0; b < 8; b++) {
                mbar_expect_tx(BAR(B_XFULL + 8 + b), 8192);
                tma_load_2d(sbase + 65536 + b * 8192, &tm_x, BAR(B_XFULL + 8 + b), b * 64, m * 128 + 64);
              }
            }
            mbar_wait(BAR(B_EMPTY + k), k < 6 ? ((t & 1) ^ 1) : (t & 1));
            mbar_expect_tx(BAR(B_FULL + k), 16384);
            tma_load_2d_mc(sbase + stage_off(k) + cr * 8192, tm, BAR(B_FULL + k), col, kq * 128);
          }
        }
        for (int j = 0; j < 18; j++) {
          const int st = j & 7, n = 5 + (j >> 3);
          const int i = 2 * j + cr;
          const int bi = p2_bi(i), kb = p2_kb(i);
          const int col = odd * 256 + ((p + 1 + bi) & 3) * 64;
          const CUtensorMap* tmk;
          int row;
          if (!odd) {
            if (kb < 4) { tmk = &tm_w2; row = (7 * p + kb) * 64; }
            else if (kb < 6) { tmk = &tm_wo; row = (2 * p + kb - 4) * 64; }
            else { tmk = &tm_w2; row = (7 * p + 4 + kb - 6) * 64; }
          } else {
            if (kb < 3) { tmk = &tm_w2; row = (7 * p + 4 + kb) * 64; }
            else if (kb < 7) { tmk = &tm_w2; row = (7 * p + kb - 3) * 64; }
            else { tmk = &tm_wo; row = (2 * p + kb - 7) * 64; }
          }
          mbar_wait(BAR(B_EMPTY + st), st < 6 ? ((n & 1) ^ 1) : (n & 1));
          mbar_expect_tx(BAR(B_FULL + st), 16384);
          tma_load_2d_mc(sbase + stage_off(st) + cr * 8192, tmk, BAR(B_FULL + st), col, row);
        }
      }
    } else if (warp <= 10) {
      if (lane == 0) {
        const int w = warp - 9;
        for (int e = 0; e < 8; e++) {
          mbar_wait(BAR(B_EV + w * 8 + e), 0);
          __threadfence();
          if (e >= 5) {
            const int bi = e - 5;
            st_relaxed(&g_pflag[m][odd][(p + 1 + bi) & 3][bi][w], tag);
          } else if (!odd) {
            st_relaxed(&g_xflag[m][p][e][w], tag);
          } else {
            if (e < 2) atomicAdd(&g_kvcnt[p][0], 1u);
            else st_relaxed(&g_xflag[m][p][6 + e - 2][w], tag);
          }
        }
      }
    } else {
      if (!odd) {
        {
          const int ce = m * 4 + p;
          float* kvn = &g_kv[par ^ 1][0][0][0];
          for (int i = lane; i < 128; i += 32) kvn[ce * 128 + i] = 0.f;
          if (lane < 8) (&g_z[par ^ 1][0][0])[ce * 8 + lane] = 0.f;
        }
        mbar_wait(BAR(B_XDONE), 0);
        wait_count_ge(&g_kvcnt[p][0], 64u * tag);
        const float* kvp = &g_kv[par][8 * p][0][0];
        const uint32_t dst0 = sbase + 5 * 8192, dst1 = dst0 + 65536;
#pragma unroll 4
        for (int i = 0; i < 16; i++) {
          float4 v = ldg_cg_f4(kvp + (i * 32 + lane) * 4);
          uint32_t lo = pack_bf16(v.x, v.y), hi = pack_bf16(v.z, v.w);
          uint32_t off = (uint32_t)(i * 32 + lane) * 8u;
          asm volatile("st.shared.v2.u32 [%0], {%1,%2};" ::"r"(dst0 + off), "r"(lo), "r"(hi) : "memory");
          asm volatile("st.shared.v2.u32 [%0], {%1,%2};" ::"r"(dst1 + off), "r"(lo), "r"(hi) : "memory");
        }
        {
          float4 v = ldg_cg_f4(&g_z[par][8 * p][0] + lane * 4);
          uint32_t lo = pack_bf16(v.x, v.y), hi = pack_bf16(v.z, v.w);
          uint32_t off = 4096u + (uint32_t)lane * 8u;
          asm volatile("st.shared.v2.u32 [%0], {%1,%2};" ::"r"(dst0 + off), "r"(lo), "r"(hi) : "memory");
          asm volatile("st.shared.v2.u32 [%0], {%1,%2};" ::"r"(dst1 + off), "r"(lo), "r"(hi) : "memory");
        }
        __syncwarp();
        if (lane == 0) mbar_arrive(BAR(B_KVREADY));
      }
      const uint32_t* flag = nullptr;
      if (lane < 12) {
        const int w = lane / 6, idx = lane - w * 6;
        if (odd ? idx < 5 : idx < 3) flag = &g_xflag[m][p][odd ? idx : 6 + idx][w];
      } else if (lane < 18) {
        const int w = (lane - 12) / 3, idx = lane - 12 - w * 3;
        flag = &g_pflag[m][odd][p][idx][w];
      }
      bool pending = flag != nullptr;
      uint32_t it = 0;
      while (__any_sync(0xffffffffu, pending)) {
        if (pending) {
          if (ld_acquire(flag) == tag || it > kSpinLimit) { mbar_arrive(BAR(B_XIN + lane)); pending = false; }
        }
        ++it;
        __nanosleep(32);
      }
    }
  } else {
    asm volatile("setmaxnreg.inc.sync.aligned.u32 240;");
    const uint32_t epoch = ld_relaxed(&g_epoch);
    const int par = epoch & 1;
    const int w = warp >> 2, wq = warp & 3, t128 = tid & 127;
    const int g = lane >> 2, tq = lane & 3;
    const uint32_t area = sbase + (uint32_t)w * 65536u;
    const bool elect = (t128 == 0);
    PROF(w, 22);
    const uint32_t dbase = (sbase & 0x3FFFFu) >> 4;
    uint32_t A[144];
    float rs0, rs1;
    auto release = [&](int st) {
      if (elect) { mbar_arrive_cluster(BAR(B_EMPTY + st), 0); mbar_arrive_cluster(BAR(B_EMPTY + st), 1); }
    };

    {
      const int row = wq * 16 + (lane & 7) + ((lane >> 3) & 1) * 8;
      const uint32_t rbase = area + row * 128;
      float s0[2][4] = {}, q0[2][4] = {}, q1[2][4] = {};
      const uint32_t ones = 0x3F803F80u;
#pragma unroll
      for (int b = 0; b < 8; b++) {
        mbar_wait(BAR(B_XFULL + w * 8 + b), 0);
        if (b == 0) PROF(w, 23);
        if (b == 7) PROF(w, 24);
#pragma unroll
        for (int kk = 0; kk < 4; kk++) {
          const int i = (b * 4 + kk) * 4;
          ldmatrix_x4(rbase + b * 8192 + (((kk * 2 + (lane >> 4)) ^ (row & 7)) << 4), A[i], A[i + 1], A[i + 2], A[i + 3]);
        }
#pragma unroll
        for (int kk = 0; kk < 4; kk++) {
          const int i = (b * 4 + kk) * 4;
          mma_16816(s0[kk & 1], A[i], A[i + 1], A[i + 2], A[i + 3], ones, ones);
          mma_16816(q0[kk & 1], A[i], A[i + 1], A[i + 2], A[i + 3], A[i], A[i + 2]);
          mma_16816(q1[kk & 1], A[i], A[i + 1], A[i + 2], A[i + 3], A[i + 1], A[i + 3]);
        }
      }
      const float mean0 = (s0[0][0] + s0[1][0]) * (1.f / 512.f), mean1 = (s0[0][2] + s0[1][2]) * (1.f / 512.f);
      const uint32_t m0 = pack_bf16(mean0, mean0), m1 = pack_bf16(mean1, mean1);
#pragma unroll
      for (int i = 0; i < 128; i += 2) {
        A[i] = hsub2_bf16(A[i], m0);
        A[i + 1] = hsub2_bf16(A[i + 1], m1);
      }
      float v0 = (g & 1) ? q0[0][1] + q0[1][1] : q0[0][0] + q0[1][0];
      float v1 = (g & 1) ? q1[0][3] + q1[1][3] : q1[0][2] + q1[1][2];
      const int src = 4 * g + (g >> 1);
      v0 = __shfl_sync(0xffffffffu, v0, src);
      v1 = __shfl_sync(0xffffffffu, v1, src);
      v0 = fmaxf(v0 * (1.f / 512.f) - mean0 * mean0, 0.f);
      v1 = fmaxf(v1 * (1.f / 512.f) - mean1 * mean1, 0.f);
      rs0 = rsqrtf(v0 + 1e-5f);
      rs1 = rsqrtf(v1 + 1e-5f);
      bar_sync(1 + w, 128);
      cluster_wait();
      PROF(w, 0);
      release(6); release(7);
      if (elect) mbar_arrive(BAR(B_XDONE));
    }

    auto gu_chunk = [&](float (&acc)[32], int f, int slot, int xslot, int hb) {
      const float c0 = rs0 * -1.4426950408889634f, c1 = rs1 * -1.4426950408889634f;
      const float q0 = rs0 * rs0, q1 = rs1 * rs1;
      uint32_t h[4];
#pragma unroll
      for (int i = 0; i < 4; i++) {
        const float ga = acc[f * 8 + 2 * i], gb = acc[f * 8 + 2 * i + 1];
        const float ua = acc[16 + f * 8 + 2 * i], ub = acc[16 + f * 8 + 2 * i + 1];
        const float c = (i & 1) ? c1 : c0, q = (i & 1) ? q1 : q0;
        const float da = 1.f + ex2f(fminf(ga * c, 60.f)), db = 1.f + ex2f(fminf(gb * c, 60.f));
        const float rq = rcpf(da * db) * q;
        h[i] = pack_bf16(ga * ua * (db * rq), gb * ub * (da * rq));
      }
      const int jj = hb * 2 + f;
      sts_u4(area + slot * 8192 + jj * 2048 + t128 * 16, h[0], h[1], h[2], h[3]);
      stg_u4(&g_xbuf[m][p][xslot][w][jj][t128], h[0], h[1], h[2], h[3]);
    };
    auto kv_stage = [&](float (&acc)[32], int c, int hb) {
      const int srow = wq * 16 + (lane & 7) + ((lane >> 3) & 1) * 8;
      const uint32_t base = area + (3 + c) * 8192 + srow * 128;
#pragma unroll
      for (int jj = 0; jj < 2; jj++) {
        const int a = c * 16 + jj * 8;
        uint32_t r0, r1, r2, r3;
        if (c == 0) {
          r0 = pack_bf16(phi_f(acc[a] * rs0), phi_f(acc[a + 1] * rs0));
          r1 = pack_bf16(phi_f(acc[a + 2] * rs1), phi_f(acc[a + 3] * rs1));
          r2 = pack_bf16(phi_f(acc[a + 4] * rs0), phi_f(acc[a + 5] * rs0));
          r3 = pack_bf16(phi_f(acc[a + 6] * rs1), phi_f(acc[a + 7] * rs1));
        } else {
          r0 = pack_bf16(acc[a] * rs0, acc[a + 1] * rs0);
          r1 = pack_bf16(acc[a + 2] * rs1, acc[a + 3] * rs1);
          r2 = pack_bf16(acc[a + 4] * rs0, acc[a + 5] * rs0);
          r3 = pack_bf16(acc[a + 6] * rs1, acc[a + 7] * rs1);
        }
        stmatrix_x4(base + (((hb * 4 + jj * 2 + (lane >> 4)) ^ (srow & 7)) << 4), r0, r1, r2, r3);
      }
    };
    auto q_head = [&](float (&acc)[32], int c, int slot, uint32_t b0, uint32_t b1, uint32_t b2, uint32_t b3, uint32_t z0, uint32_t z1) {
      const int a = c * 8;
      const uint32_t a0 = pack_bf16(phi_f(acc[a] * rs0), phi_f(acc[a + 1] * rs0));
      const uint32_t a1 = pack_bf16(phi_f(acc[a + 2] * rs1), phi_f(acc[a + 3] * rs1));
      const uint32_t a2 = pack_bf16(phi_f(acc[a + 4] * rs0), phi_f(acc[a + 5] * rs0));
      const uint32_t a3 = pack_bf16(phi_f(acc[a + 6] * rs1), phi_f(acc[a + 7] * rs1));
      float n0[4] = {0.f, 0.f, 0.f, 0.f}, n1[4] = {0.f, 0.f, 0.f, 0.f}, dn[4] = {0.f, 0.f, 0.f, 0.f};
      mma_16816(n0, a0, a1, a2, a3, b0, b1);
      mma_16816(n1, a0, a1, a2, a3, b2, b3);
      mma_16816(dn, a0, a1, a2, a3, z0, z1);
      const float i0 = __fdividef(1.f, dn[0] + 1e-6f), i1 = __fdividef(1.f, dn[2] + 1e-6f);
      const uint32_t o0 = pack_bf16(n0[0] * i0, n0[1] * i0), o1 = pack_bf16(n0[2] * i1, n0[3] * i1);
      const uint32_t o2 = pack_bf16(n1[0] * i0, n1[1] * i0), o3 = pack_bf16(n1[2] * i1, n1[3] * i1);
      sts_u4(area + slot * 8192 + c * 2048 + t128 * 16, o0, o1, o2, o3);
      stg_u4(&g_xbuf[m][p][slot][w][c][t128], o0, o1, o2, o3);
    };
    const uint32_t kvb = area + 5 * 8192;
    const uint32_t kvfrag = kvb + ((lane & 7) + ((lane >> 3) & 1) * 8) * 32 + (lane >> 4) * 16;
    auto signal = [&](int e) {
      __syncwarp();
      if (lane == 0) mbar_arrive(BAR(B_EV + w * 8 + e));
    };

    float accB[32];
#pragma unroll 1
    for (int t = 0; t < 5; t++) {
      float accA[32];
      const uint32_t ph = t & 1;
      const int kindP = t == 0 ? K_NONE : ((odd && t <= 2) ? K_KV : K_GU);
      const int kindC = odd ? (t < 2 ? K_KV : K_GU) : (t < 4 ? K_GU : K_Q);
      const int slotP = odd ? t - 3 : t - 1, xslotP = odd ? t + 3 : t - 1;
      const int slotC = odd ? t - 2 : t, xslotC = odd ? t + 4 : t;
      static_for<8>([&](auto kc) {
        constexpr int k = decltype(kc)::value;
        mbar_wait(BAR(B_FULL + k), ph);
        wgmma_fence();
        static_for<8>([&](auto kkc) {
          constexpr int kk = decltype(kkc)::value;
          constexpr int i = ((k & 3) * 8 + kk) * 4;
          constexpr uint32_t lo = desc_lo(stage_off(k) + kk * 1024, 8192);
          if constexpr (k < 4) wgmma_n64_rs<((k & 3) | kk) != 0, lo, kHi64>(accA, A[i], A[i + 1], A[i + 2], A[i + 3], dbase);
          else wgmma_n64_rs<((k & 3) | kk) != 0, lo, kHi64>(accB, A[i], A[i + 1], A[i + 2], A[i + 3], dbase);
        });
        wgmma_commit();
        if (k > 0) {
          wgmma_wait<1>();
          release(k - 1);
        }
        if constexpr (k < 4) {
          if (kindP == K_GU) {
            if (k == 1 || k == 2) gu_chunk(accB, k - 1, slotP, xslotP, 1);
            if (k == 2) signal(t - 1);
          } else if (kindP == K_KV) {
            if (k == 1 || k == 2) kv_stage(accB, k - 1, 1);
            if (k == 3) {
              float kvacc[36];
              fence_proxy_async();
              bar_sync(1 + w, 128);
              wgmma_fence();
              static_for<4>([&](auto kkc) {
                constexpr int kk = decltype(kkc)::value;
                wgmma_n72_ss_tt<kk != 0, desc_lo(3 * 8192 + kk * 2048, 0), desc_lo(4 * 8192 + kk * 2048, 8192 - kk * 2048)>(kvacc, dbase + w * 4096);
              });
              wgmma_commit();
              wgmma_wait<0>();
              float c[8];
#pragma unroll
              for (int i = 0; i < 8; i++)
                c[i] = wq == 0 ? kvacc[i] : (wq == 1 ? kvacc[8 + i] : (wq == 2 ? kvacc[16 + i] : kvacc[24 + i]));
              const int head = (2 * p + t - 1) * 4 + wq;
              float* kvp = &g_kv[par][head][0][0];
              red_add_v2(kvp + g * 16 + 2 * tq, c[0], c[1]);
              red_add_v2(kvp + (g + 8) * 16 + 2 * tq, c[2], c[3]);
              red_add_v2(kvp + g * 16 + 8 + 2 * tq, c[4], c[5]);
              red_add_v2(kvp + (g + 8) * 16 + 8 + 2 * tq, c[6], c[7]);
              if (tq == 0) {
                red_add(&g_z[par][head][g], kvacc[32]);
                red_add(&g_z[par][head][g + 8], kvacc[34]);
              }
              signal(t - 1);
            }
          }
        } else {
          constexpr int c = k - 4;
          if (kindC == K_GU) {
            if (c < 2) gu_chunk(accA, c, slotC, xslotC, 0);
          } else if (kindC == K_KV) {
            if (c == 0 && t == 0) sts_u4(area + 5 * 8192 + t128 * 16, 0x3F803F80u, 0x3F803F80u, 0x3F803F80u, 0x3F803F80u);
            if (c < 2) kv_stage(accA, c, 0);
          } else {
            if (c == 0) mbar_wait(BAR(B_KVREADY), 0);
            uint32_t b0, b1, b2, b3;
            ldmatrix_x4_trans(kvfrag + c * 512, b0, b1, b2, b3);
            const uint32_t z0 = lds_u32(kvb + 4096 + c * 32 + tq * 4), z1 = lds_u32(kvb + 4096 + c * 32 + 16 + tq * 4);
            q_head(accA, c, 4, b0, b1, b2, b3, z0, z1);
          }
        }
      });
      wgmma_wait<0>();
      release(7);
      PROF(w, 1 + 2 * t);
    }
    if (odd) {
      gu_chunk(accB, 0, 2, 8, 1);
      gu_chunk(accB, 1, 2, 8, 1);
    } else {
      uint32_t Bf[4][6];
#pragma unroll
      for (int c = 0; c < 4; c++) {
        ldmatrix_x4_trans(kvfrag + (4 + c) * 512, Bf[c][0], Bf[c][1], Bf[c][2], Bf[c][3]);
        Bf[c][4] = lds_u32(kvb + 4096 + (4 + c) * 32 + tq * 4);
        Bf[c][5] = lds_u32(kvb + 4096 + (4 + c) * 32 + 16 + tq * 4);
      }
      bar_sync(1 + w, 128);
#pragma unroll
      for (int c = 0; c < 4; c++) q_head(accB, c, 5, Bf[c][0], Bf[c][1], Bf[c][2], Bf[c][3], Bf[c][4], Bf[c][5]);
    }
    signal(4);
    PROF(w, 10);

    const int n_own = odd ? 3 : 6;
    auto load_a = [&](int kb) {
      if (kb < n_own) {
#pragma unroll
        for (int jj = 0; jj < 4; jj++) {
          const int i = (kb * 4 + jj) * 4;
          lds_u4(area + kb * 8192 + jj * 2048 + t128 * 16, A[i], A[i + 1], A[i + 2], A[i + 3]);
        }
      } else {
        const int xs = odd ? kb - 3 : kb;
        const int ev = odd ? (kb - 3 < 4 ? kb - 3 : 4) : kb - 6;
        mbar_wait(BAR(B_XIN + w * 6 + ev), 0);
#pragma unroll
        for (int jj = 0; jj < 4; jj++) {
          const int i = (kb * 4 + jj) * 4;
          uint4 v = ldg_cg_u4(&g_xbuf[m][p][xs][w][jj][t128]);
          A[i] = v.x; A[i + 1] = v.y; A[i + 2] = v.z; A[i + 3] = v.w;
        }
      }
    };
#pragma unroll
    for (int kb = 0; kb < 7; kb++) load_a(kb);
    PROF(w, 11);

    const int orow = m * 128 + w * 64 + wq * 16 + g;
    const int ocol = odd * 256 + p * 64 + 2 * tq;
    float acc2[2][32];
    float4 P0[8], P1[8], P2[8];
    uint32_t xr[16];
    auto send = [&](float (&acc)[32], int bi) {
      float4* dst = &g_pbuf[m][odd][(p + 1 + bi) & 3][bi][w][0][t128];
#pragma unroll
      for (int q = 0; q < 8; q++) stg_f4(dst + q * 128, acc[q * 4], acc[q * 4 + 1], acc[q * 4 + 2], acc[q * 4 + 3]);
      signal(5 + bi);
      PROF(w, 12 + 2 * bi);
    };
    static_for<36>([&](auto ic) {
      constexpr int i = decltype(ic)::value, bi = p2_bi(i), kb = p2_kb(i), j = i >> 1, st = j & 7;
      if (i == 9) { load_a(7); load_a(8); }
      if ((i & 1) == 0) mbar_wait(BAR(B_FULL + st), (5 + (j >> 3)) & 1);
      wgmma_fence();
      static_for<4>([&](auto kkc) {
        constexpr int kk = decltype(kkc)::value, a = (kb * 4 + kk) * 4;
        wgmma_n64_rs<(kb | kk) != 0, desc_lo(stage_off(st) + (i & 1) * 8192 + kk * 2048, 0), kHi128>(acc2[bi & 1], A[a], A[a + 1], A[a + 2], A[a + 3], dbase);
      });
      wgmma_commit();
      if (i > 0) {
        wgmma_wait<1>();
        if ((i & 1) == 0 && j - 1 <= 9) release((j - 1) & 7);
      }
      if constexpr (i == 16) send(acc2[0], 0);
      if constexpr (i == 18) send(acc2[1], 1);
      if constexpr (i == 27) send(acc2[0], 2);
      if constexpr (i == 29) {
        mbar_wait(BAR(B_PIN + w * 3 + 0), 0);
#pragma unroll
        for (int q = 0; q < 8; q++) P0[q] = ldg_cg_f4(&g_pbuf[m][odd][p][0][w][q][t128]);
      }
      if constexpr (i == 31) {
        mbar_wait(BAR(B_PIN + w * 3 + 1), 0);
#pragma unroll
        for (int q = 0; q < 8; q++) P1[q] = ldg_cg_f4(&g_pbuf[m][odd][p][1][w][q][t128]);
      }
      if constexpr (i == 32) {
#pragma unroll
        for (int q = 0; q < 8; q++) {
          xr[2 * q] = __ldg((const uint32_t*)(x + (size_t)orow * kD + ocol + q * 8));
          xr[2 * q + 1] = __ldg((const uint32_t*)(x + (size_t)(orow + 8) * kD + ocol + q * 8));
        }
      }
      if constexpr (i == 35) {
        mbar_wait(BAR(B_PIN + w * 3 + 2), 0);
#pragma unroll
        for (int q = 0; q < 8; q++) P2[q] = ldg_cg_f4(&g_pbuf[m][odd][p][2][w][q][t128]);
      }
    });
    wgmma_wait<0>();
    PROF(w, 18);
#pragma unroll
    for (int q = 0; q < 8; q++) {
      const float r0 = acc2[1][q * 4 + 0] + P0[q].x + P1[q].x + P2[q].x + __uint_as_float(xr[2 * q] << 16);
      const float r1 = acc2[1][q * 4 + 1] + P0[q].y + P1[q].y + P2[q].y + __uint_as_float(xr[2 * q] & 0xffff0000u);
      const float r2 = acc2[1][q * 4 + 2] + P0[q].z + P1[q].z + P2[q].z + __uint_as_float(xr[2 * q + 1] << 16);
      const float r3 = acc2[1][q * 4 + 3] + P0[q].w + P1[q].w + P2[q].w + __uint_as_float(xr[2 * q + 1] & 0xffff0000u);
      *(uint32_t*)(out + (size_t)orow * kD + ocol + q * 8) = pack_bf16(r0, r1);
      *(uint32_t*)(out + (size_t)(orow + 8) * kD + ocol + q * 8) = pack_bf16(r2, r3);
    }
    PROF(w, 19);
    if (tid == 0) {
      const uint32_t old = atomicAdd(&g_done, 1u);
      if ((old & 127u) == 127u) *(volatile uint32_t*)&g_epoch = epoch + 1u;
    }
  }
#undef BAR
}

typedef CUresult (*EncodeFn)(CUtensorMap*, CUtensorMapDataType, cuuint32_t, void*, const cuuint64_t*, const cuuint64_t*,
                             const cuuint32_t*, const cuuint32_t*, CUtensorMapInterleave, CUtensorMapSwizzle,
                             CUtensorMapL2promotion, CUtensorMapFloatOOBfill);

void make_map(EncodeFn enc, CUtensorMap* tm, const void* ptr, int rows, int cols, bool narrow) {
  cuuint64_t gd[2] = {(cuuint64_t)cols, (cuuint64_t)rows};
  cuuint64_t gs[1] = {(cuuint64_t)cols * 2};
  cuuint32_t bd[2] = {narrow ? 32u : 64u, narrow ? 128u : 64u};
  cuuint32_t es[2] = {1, 1};
  enc(tm, CU_TENSOR_MAP_DATA_TYPE_BFLOAT16, 2, const_cast<void*>(ptr), gd, gs, bd, es, CU_TENSOR_MAP_INTERLEAVE_NONE,
      narrow ? CU_TENSOR_MAP_SWIZZLE_64B : CU_TENSOR_MAP_SWIZZLE_128B, CU_TENSOR_MAP_L2_PROMOTION_L2_256B, CU_TENSOR_MAP_FLOAT_OOB_FILL_NONE);
}

}

extern "C" void kernel_launch(void* const* d_in, const int* in_sizes, int n_in, void* d_out, int out_size) {
  static EncodeFn enc = nullptr;
  if (!enc) {
    void* fn = nullptr;
    cudaDriverEntryPointQueryResult qr;
    cudaGetDriverEntryPoint("cuTensorMapEncodeTiled", &fn, cudaEnableDefault, &qr);
    enc = (EncodeFn)fn;
    cudaFuncSetAttribute(fused_kernel, cudaFuncAttributeMaxDynamicSharedMemorySize, kSmemBytes);
  }
  CUtensorMap tm_x, tm_wqkv, tm_w1, tm_w3, tm_w2, tm_wo;
  make_map(enc, &tm_x, d_in[0], kS, kD, false);
  make_map(enc, &tm_wqkv, d_in[1], kD, 3 * kD, true);
  make_map(enc, &tm_wo, d_in[2], kD, kD, false);
  make_map(enc, &tm_w1, d_in[4], kD, kF, true);
  make_map(enc, &tm_w3, d_in[5], kD, kF, true);
  make_map(enc, &tm_w2, d_in[6], kF, kD, false);
  fused_kernel<<<128, 384, kSmemBytes>>>(tm_x, tm_wqkv, tm_w1, tm_w3, tm_w2, tm_wo, (const __nv_bfloat16*)d_in[0],
                                         (__nv_bfloat16*)d_out);
}
```

```cpp
#include <cuda_runtime.h>
#include <cuda_bf16.h>
#include <cuda.h>
#include <stdint.h>

namespace {

constexpr int kS = 2048, kD = 512, kF = 1792;
constexpr uint32_t kSpinLimit = 1u << 22;

__device__ uint4    g_xbuf[16][4][9][2][4][128];
__device__ float4   g_pbuf[16][2][4][3][2][8][128];
__device__ float    g_kv[2][32][16][16];
__device__ float    g_z[2][32][16];
__device__ uint32_t g_xflag[16][4][9][2];
__device__ uint32_t g_pflag[16][2][4][3][2];
__device__ uint32_t g_kvcnt[4][32];
__device__ uint32_t g_epoch;
__device__ uint32_t g_done;
#define PROF(wg, i) do {} while (0)

__device__ __forceinline__ uint32_t smem_u32(const void* p) { return (uint32_t)__cvta_generic_to_shared(p); }
__device__ __forceinline__ void mbar_init(uint32_t bar, uint32_t cnt) {
  asm volatile("mbarrier.init.shared::cta.b64 [%0], %1;" ::"r"(bar), "r"(cnt) : "memory");
}
__device__ __forceinline__ void mbar_expect_tx(uint32_t bar, uint32_t bytes) {
  asm volatile("mbarrier.arrive.expect_tx.shared::cta.b64 _, [%0], %1;" ::"r"(bar), "r"(bytes) : "memory");
}
__device__ __forceinline__ void mbar_arrive(uint32_t bar) {
  asm volatile("mbarrier.arrive.shared::cta.b64 _, [%0];" ::"r"(bar) : "memory");
}
__device__ __forceinline__ void mbar_wait(uint32_t bar, uint32_t parity) {
  asm volatile(
      "{\n.reg .pred p;\n"
      "LAB_WAIT:\n"
      "mbarrier.try_wait.parity.shared::cta.b64 p, [%0], %1;\n"
      "@p bra DONE;\n"
      "bra LAB_WAIT;\n"
      "DONE:\n}" ::"r"(bar), "r"(parity) : "memory");
}
__device__ __forceinline__ void tma_load_2d(uint32_t dst, const CUtensorMap* tm, uint32_t bar, int c0, int c1) {
  asm volatile(
      "cp.async.bulk.tensor.2d.shared::cluster.global.mbarrier::complete_tx::bytes [%0], [%1, {%3, %4}], [%2];" ::"r"(dst),
      "l"(tm), "r"(bar), "r"(c0), "r"(c1)
      : "memory");
}
__device__ __forceinline__ void tma_load_2d_mc(uint32_t dst, const CUtensorMap* tm, uint32_t bar, int c0, int c1) {
  asm volatile(
      "cp.async.bulk.tensor.2d.shared::cluster.global.mbarrier::complete_tx::bytes.multicast::cluster [%0], [%1, {%3, %4}], [%2], %5;" ::"r"(dst),
      "l"(tm), "r"(bar), "r"(c0), "r"(c1), "h"((uint16_t)3)
      : "memory");
}
__device__ __forceinline__ void mbar_arrive_cluster(uint32_t bar, uint32_t cta) {
  asm volatile("{\n.reg .b32 ra;\nmapa.shared::cluster.u32 ra, %0, %1;\nmbarrier.arrive.shared::cluster.b64 _, [ra];\n}" ::"r"(bar), "r"(cta) : "memory");
}
__device__ __forceinline__ void prefetch_tmap(const CUtensorMap* tm) {
  asm volatile("prefetch.tensormap [%0];" ::"l"(tm) : "memory");
}
__device__ __forceinline__ void wgmma_fence() { asm volatile("wgmma.fence.sync.aligned;" ::: "memory"); }
__device__ __forceinline__ void wgmma_commit() { asm volatile("wgmma.commit_group.sync.aligned;" ::: "memory"); }
template <int N>
__device__ __forceinline__ void wgmma_wait() { asm volatile("wgmma.wait_group.sync.aligned %0;" ::"n"(N) : "memory"); }
__device__ __forceinline__ void bar_sync(int id, int n) { asm volatile("bar.sync %0, %1;" ::"r"(id), "r"(n) : "memory"); }
__device__ __forceinline__ void bar_arrive(int id, int n) { asm volatile("bar.arrive %0, %1;" ::"r"(id), "r"(n) : "memory"); }
__device__ __forceinline__ void fence_proxy_async() { asm volatile("fence.proxy.async.shared::cta;" ::: "memory"); }

__device__ __forceinline__ uint32_t ld_acquire(const uint32_t* p) {
  uint32_t v;
  asm volatile("ld.acquire.gpu.global.u32 %0, [%1];" : "=r"(v) : "l"(p) : "memory");
  return v;
}
__device__ __forceinline__ uint32_t ld_relaxed(const uint32_t* p) {
  uint32_t v;
  asm volatile("ld.relaxed.gpu.global.u32 %0, [%1];" : "=r"(v) : "l"(p));
  return v;
}
__device__ __forceinline__ void cluster_wait() { asm volatile("barrier.cluster.wait.aligned;" ::: "memory"); }
__device__ __forceinline__ void st_relaxed(uint32_t* p, uint32_t v) {
  asm volatile("st.relaxed.gpu.global.u32 [%0], %1;" ::"l"(p), "r"(v) : "memory");
}
__device__ __forceinline__ void wait_flag_eq(const uint32_t* p, uint32_t val) {
  uint32_t it = 0;
  while (ld_acquire(p) != val) {
    if (++it > kSpinLimit) break;
  }
}
__device__ __forceinline__ void wait_count_ge(const uint32_t* p, uint32_t val) {
  uint32_t it = 0;
  while ((int32_t)(ld_acquire(p) - val) < 0) {
    __nanosleep(64);
    if (++it > kSpinLimit) break;
  }
}
__device__ __forceinline__ uint4 ldg_cg_u4(const void* p) {
  uint4 v;
  asm volatile("ld.global.cg.v4.u32 {%0,%1,%2,%3}, [%4];" : "=r"(v.x), "=r"(v.y), "=r"(v.z), "=r"(v.w) : "l"(p) : "memory");
  return v;
}
__device__ __forceinline__ float4 ldg_cg_f4(const void* p) {
  float4 v;
  asm volatile("ld.global.cg.v4.f32 {%0,%1,%2,%3}, [%4];" : "=f"(v.x), "=f"(v.y), "=f"(v.z), "=f"(v.w) : "l"(p) : "memory");
  return v;
}
__device__ __forceinline__ void stg_u4(void* p, uint32_t a, uint32_t b, uint32_t c, uint32_t d) {
  asm volatile("st.global.v4.u32 [%0], {%1,%2,%3,%4};" ::"l"(p), "r"(a), "r"(b), "r"(c), "r"(d) : "memory");
}
__device__ __forceinline__ void stg_f4(void* p, float a, float b, float c, float d) {
  asm volatile("st.global.v4.f32 [%0], {%1,%2,%3,%4};" ::"l"(p), "f"(a), "f"(b), "f"(c), "f"(d) : "memory");
}
__device__ __forceinline__ void sts_u4(uint32_t addr, uint32_t a, uint32_t b, uint32_t c, uint32_t d) {
  asm volatile("st.shared.v4.u32 [%0], {%1,%2,%3,%4};" ::"r"(addr), "r"(a), "r"(b), "r"(c), "r"(d) : "memory");
}
__device__ __forceinline__ void lds_u4(uint32_t addr, uint32_t& a, uint32_t& b, uint32_t& c, uint32_t& d) {
  asm volatile("ld.shared.v4.u32 {%0,%1,%2,%3}, [%4];" : "=r"(a), "=r"(b), "=r"(c), "=r"(d) : "r"(addr) : "memory");
}
__device__ __forceinline__ uint32_t lds_u32(uint32_t addr) {
  uint32_t v;
  asm volatile("ld.shared.u32 %0, [%1];" : "=r"(v) : "r"(addr) : "memory");
  return v;
}
__device__ __forceinline__ void ldmatrix_x4(uint32_t addr, uint32_t& a, uint32_t& b, uint32_t& c, uint32_t& d) {
  asm volatile("ldmatrix.sync.aligned.m8n8.x4.shared.b16 {%0,%1,%2,%3}, [%4];" : "=r"(a), "=r"(b), "=r"(c), "=r"(d) : "r"(addr) : "memory");
}
__device__ __forceinline__ void ldmatrix_x4_trans(uint32_t addr, uint32_t& a, uint32_t& b, uint32_t& c, uint32_t& d) {
  asm volatile("ldmatrix.sync.aligned.m8n8.x4.trans.shared.b16 {%0,%1,%2,%3}, [%4];" : "=r"(a), "=r"(b), "=r"(c), "=r"(d) : "r"(addr) : "memory");
}
__device__ __forceinline__ void stmatrix_x4(uint32_t addr, uint32_t a, uint32_t b, uint32_t c, uint32_t d) {
  asm volatile("stmatrix.sync.aligned.m8n8.x4.shared.b16 [%0], {%1,%2,%3,%4};" ::"r"(addr), "r"(a), "r"(b), "r"(c), "r"(d) : "memory");
}
__device__ __forceinline__ void mma_16816(float (&c)[4], uint32_t a0, uint32_t a1, uint32_t a2, uint32_t a3, uint32_t b0, uint32_t b1) {
  asm volatile(
      "mma.sync.aligned.m16n8k16.row.col.f32.bf16.bf16.f32 {%0,%1,%2,%3}, {%4,%5,%6,%7}, {%8,%9}, {%0,%1,%2,%3};"
      : "+f"(c[0]), "+f"(c[1]), "+f"(c[2]), "+f"(c[3])
      : "r"(a0), "r"(a1), "r"(a2), "r"(a3), "r"(b0), "r"(b1));
}
__device__ __forceinline__ uint32_t pack_bf16(float lo, float hi) {
  uint32_t r;
  asm("cvt.rn.bf16x2.f32 %0, %1, %2;" : "=r"(r) : "f"(hi), "f"(lo));
  return r;
}
__device__ __forceinline__ uint32_t hsub2_bf16(uint32_t a, uint32_t b) {
  uint32_t r;
  asm("sub.rn.bf16x2 %0, %1, %2;" : "=r"(r) : "r"(a), "r"(b));
  return r;
}
__device__ __forceinline__ float ex2f(float x) {
  float r;
  asm("ex2.approx.ftz.f32 %0, %1;" : "=f"(r) : "f"(x));
  return r;
}
__device__ __forceinline__ float rcpf(float x) {
  float r;
  asm("rcp.approx.ftz.f32 %0, %1;" : "=f"(r) : "f"(x));
  return r;
}
__device__ __forceinline__ void red_add_v2(float* p, float a, float b) {
  asm volatile("red.relaxed.gpu.global.add.v2.f32 [%0], {%1,%2};" ::"l"(p), "f"(a), "f"(b) : "memory");
}
__device__ __forceinline__ void red_add(float* p, float a) {
  asm volatile("red.relaxed.gpu.global.add.f32 [%0], %1;" ::"l"(p), "f"(a) : "memory");
}
__device__ __forceinline__ float phi_f(float t) {
  float e = ex2f(t * 1.4426950408889634f);
  return (t > 0.f ? t + 1.f : e) + 1e-6f;
}

#define R8(a, o) "+f"(a[o + 0]), "+f"(a[o + 1]), "+f"(a[o + 2]), "+f"(a[o + 3]), "+f"(a[o + 4]), "+f"(a[o + 5]), "+f"(a[o + 6]), "+f"(a[o + 7])

#define W8(a, o) "=f"(a[o + 0]), "=f"(a[o + 1]), "=f"(a[o + 2]), "=f"(a[o + 3]), "=f"(a[o + 4]), "=f"(a[o + 5]), "=f"(a[o + 6]), "=f"(a[o + 7])
#define D32 "{%0,%1,%2,%3,%4,%5,%6,%7,%8,%9,%10,%11,%12,%13,%14,%15,%16,%17,%18,%19,%20,%21,%22,%23,%24,%25,%26,%27,%28,%29,%30,%31}"
#define D36 "{%0,%1,%2,%3,%4,%5,%6,%7,%8,%9,%10,%11,%12,%13,%14,%15,%16,%17,%18,%19,%20,%21,%22,%23,%24,%25,%26,%27,%28,%29,%30,%31,%32,%33,%34,%35}"

constexpr uint32_t kHi128 = (1024u >> 4) | (1u << 30);
constexpr uint32_t kHi64 = (512u >> 4) | (2u << 30);
__host__ __device__ constexpr uint32_t desc_lo(uint32_t off, uint32_t lbo) { return (off >> 4) | ((lbo >> 4) << 16); }

template <bool ACC, uint32_t LO, uint32_t HI>
__device__ __forceinline__ void wgmma_n64_rs(float (&d)[32], uint32_t a0, uint32_t a1, uint32_t a2, uint32_t a3, uint32_t base) {
  if (ACC) {
    asm volatile(
        "{\n.reg .pred p;\n.reg .b32 lo;\n.reg .b64 dd;\nsetp.eq.b32 p, 0, 0;\nadd.u32 lo, %36, %37;\nmov.b64 dd, {lo, %38};\n"
        "wgmma.mma_async.sync.aligned.m64n64k16.f32.bf16.bf16 " D32 ", {%32,%33,%34,%35}, dd, p, 1, 1, 1;\n}"
        : R8(d, 0), R8(d, 8), R8(d, 16), R8(d, 24)
        : "r"(a0), "r"(a1), "r"(a2), "r"(a3), "r"(base), "n"(LO), "n"(HI));
  } else {
    asm volatile(
        "{\n.reg .pred p;\n.reg .b32 lo;\n.reg .b64 dd;\nsetp.ne.b32 p, 0, 0;\nadd.u32 lo, %36, %37;\nmov.b64 dd, {lo, %38};\n"
        "wgmma.mma_async.sync.aligned.m64n64k16.f32.bf16.bf16 " D32 ", {%32,%33,%34,%35}, dd, p, 1, 1, 1;\n}"
        : W8(d, 0), W8(d, 8), W8(d, 16), W8(d, 24)
        : "r"(a0), "r"(a1), "r"(a2), "r"(a3), "r"(base), "n"(LO), "n"(HI));
  }
}
template <bool ACC, uint32_t LOA, uint32_t LOB>
__device__ __forceinline__ void wgmma_n72_ss_tt(float (&d)[36], uint32_t base) {
  if (ACC) {
    asm volatile(
        "{\n.reg .pred p;\n.reg .b32 lo;\n.reg .b64 da, db;\nsetp.eq.b32 p, 0, 0;\n"
        "add.u32 lo, %36, %37;\nmov.b64 da, {lo, %39};\nadd.u32 lo, %36, %38;\nmov.b64 db, {lo, %39};\n"
        "wgmma.mma_async.sync.aligned.m64n72k16.f32.bf16.bf16 " D36 ", da, db, p, 1, 1, 1, 1;\n}"
        : R8(d, 0), R8(d, 8), R8(d, 16), R8(d, 24), "+f"(d[32]), "+f"(d[33]), "+f"(d[34]), "+f"(d[35])
        : "r"(base), "n"(LOA), "n"(LOB), "n"(kHi128));
  } else {
    asm volatile(
        "{\n.reg .pred p;\n.reg .b32 lo;\n.reg .b64 da, db;\nsetp.ne.b32 p, 0, 0;\n"
        "add.u32 lo, %36, %37;\nmov.b64 da, {lo, %39};\nadd.u32 lo, %36, %38;\nmov.b64 db, {lo, %39};\n"
        "wgmma.mma_async.sync.aligned.m64n72k16.f32.bf16.bf16 " D36 ", da, db, p, 1, 1, 1, 1;\n}"
        : W8(d, 0), W8(d, 8), W8(d, 16), W8(d, 24), "=f"(d[32]), "=f"(d[33]), "=f"(d[34]), "=f"(d[35])
        : "r"(base), "n"(LOA), "n"(LOB), "n"(kHi128));
  }
}

template <int V> struct IC { static constexpr int value = V; };
template <int N, int I = 0, typename F>
__device__ __forceinline__ void static_for(F&& f) {
  if constexpr (I < N) { f(IC<I>{}); static_for<N, I + 1>(f); }
}

__host__ __device__ constexpr uint32_t stage_off(int st) {
  return st < 6 ? 131072u + (uint32_t)st * 16384u : (uint32_t)(st - 6) * 65536u + 49152u;
}

constexpr int B_FULL = 0, B_EMPTY = 8, B_XFULL = 16, B_XDONE = 32, B_KVREADY = 33, B_EV = 34, B_XIN = 50, B_PIN = 62, B_COUNT = 68;
constexpr uint32_t kBarOff = 229376;
constexpr int kSmemBytes = 229376 + 1024;

__host__ __device__ constexpr int p2_bi(int i) { return i < 7 ? 0 : i < 14 ? 1 : i < 16 ? 0 : i < 18 ? 1 : i / 9; }
__host__ __device__ constexpr int p2_kb(int i) { return i < 7 ? i : i < 14 ? i - 7 : i < 16 ? i - 7 : i < 18 ? i - 9 : i % 9; }

enum { K_NONE = 0, K_GU = 1, K_KV = 2, K_Q = 3 };

__global__ void __cluster_dims__(2, 1, 1) __launch_bounds__(384, 1)
fused_kernel(const __grid_constant__ CUtensorMap tm_x, const __grid_constant__ CUtensorMap tm_wqkv,
             const __grid_constant__ CUtensorMap tm_w1, const __grid_constant__ CUtensorMap tm_w3,
             const __grid_constant__ CUtensorMap tm_w2, const __grid_constant__ CUtensorMap tm_wo,
             const __nv_bfloat16* __restrict__ x, __nv_bfloat16* __restrict__ out) {
  extern __shared__ __align__(1024) uint8_t smem_raw[];
  const uint32_t sbase = __shfl_sync(0xffffffffu, smem_u32(smem_raw), 0);
  const uint32_t bars = sbase + kBarOff;
  const int tid = threadIdx.x, lane = tid & 31;
  const int warp = __shfl_sync(0xffffffffu, tid >> 5, 0);
  const int cr = blockIdx.x & 1;
  const int r = (blockIdx.x >> 1) & 7, m = ((blockIdx.x >> 4) << 1) | cr, p = r >> 1, odd = r & 1;
#define BAR(i) (bars + 8u * (uint32_t)(i))
  if (warp == 8) {
    if (lane == 0) {
#pragma unroll
      for (int i = 0; i < 16; i++) { mbar_init(BAR(B_XFULL + i), 1); mbar_init(BAR(B_EV + i), 4); }
#pragma unroll
      for (int i = 0; i < 8; i++) { mbar_init(BAR(B_FULL + i), 1); mbar_init(BAR(B_EMPTY + i), 4); }
#pragma unroll
      for (int i = 0; i < 18; i++) mbar_init(BAR(B_XIN + i), 1);
      mbar_init(BAR(B_XDONE), 2);
      mbar_init(BAR(B_KVREADY), 1);
    }
    asm volatile("fence.mbarrier_init.release.cluster;" ::: "memory");
    fence_proxy_async();
    __syncwarp();
  }
  asm volatile("barrier.cluster.arrive.relaxed.aligned;" ::: "memory");
  PROF((tid >> 7), 21);
  if (tid == 256) {
    if (sbase & 1023u) __trap();
    for (int b = 0; b < 8; b++) {
      mbar_expect_tx(BAR(B_XFULL + b), 8192);
      tma_load_2d(sbase + b * 8192, &tm_x, BAR(B_XFULL + b), b * 64, m * 128);
    }
  } else if (tid == 288) {
    prefetch_tmap(odd ? &tm_wqkv : (cr ? &tm_w3 : &tm_w1));
  }
  __syncthreads();
  PROF((tid >> 7), 20);

  if (warp >= 8) {
    asm volatile("setmaxnreg.dec.sync.aligned.u32 24;");
    PROF(2, 3);
    cluster_wait();
    PROF(2, 2);
    const uint32_t epoch = warp == 8 ? 0u : ld_relaxed(&g_epoch);
    const uint32_t tag = epoch + 1u;
    const int par = epoch & 1;
    if (warp == 8) {
      if (lane == 0) {
        for (int j = 0; j < 10; j++) {
          const CUtensorMap* tm;
          int col;
          if (!odd) {
            if (j < 8) { tm = cr ? &tm_w3 : &tm_w1; col = 7 * p * 64 + j * 32; }
            else { tm = &tm_wqkv; col = 128 * p + (j - 8) * 64 + cr * 32; }
          } else {
            if (j < 4) { tm = &tm_wqkv; col = 512 + cr * 512 + 128 * p + j * 32; }
            else { tm = cr ? &tm_w3 : &tm_w1; col = (7 * p + 4) * 64 + (j - 4) * 32; }
          }
          const int t = j >> 1;
          for (int kq = 0; kq < 4; kq++) {
            const int k = (j & 1) * 4 + kq;
            if (j == 0 && kq == 2) {
              for (int b = 0; b < 8; b++) {
                mbar_expect_tx(BAR(B_XFULL + 8 + b), 8192);
                tma_load_2d(sbase + 65536 + b * 8192, &tm_x, BAR(B_XFULL + 8 + b), b * 64, m * 128 + 64);
              }
            }
            mbar_wait(BAR(B_EMPTY + k), k < 6 ? ((t & 1) ^ 1) : (t & 1));
            mbar_expect_tx(BAR(B_FULL + k), 16384);
            tma_load_2d_mc(sbase + stage_off(k) + cr * 8192, tm, BAR(B_FULL + k), col, kq * 128);
          }
        }
        for (int j = 0; j < 18; j++) {
          const int st = j & 7, n = 5 + (j >> 3);
          const int i = 2 * j + cr;
          const int bi = p2_bi(i), kb = p2_kb(i);
          const int col = odd * 256 + ((p + 1 + bi) & 3) * 64;
          const CUtensorMap* tmk;
          int row;
          if (!odd) {
            if (kb < 4) { tmk = &tm_w2; row = (7 * p + kb) * 64; }
            else if (kb < 6) { tmk = &tm_wo; row = (2 * p + kb - 4) * 64; }
            else { tmk = &tm_w2; row = (7 * p + 4 + kb - 6) * 64; }
          } else {
            if (kb < 3) { tmk = &tm_w2; row = (7 * p + 4 + kb) * 64; }
            else if (kb < 7) { tmk = &tm_w2; row = (7 * p + kb - 3) * 64; }
            else { tmk = &tm_wo; row = (2 * p + kb - 7) * 64; }
          }
          mbar_wait(BAR(B_EMPTY + st), st < 6 ? ((n & 1) ^ 1) : (n & 1));
          mbar_expect_tx(BAR(B_FULL + st), 16384);
          tma_load_2d_mc(sbase + stage_off(st) + cr * 8192, tmk, BAR(B_FULL + st), col, row);
        }
      }
    } else if (warp <= 10) {
      if (lane == 0) {
        const int w = warp - 9;
        for (int e = 0; e < 8; e++) {
          mbar_wait(BAR(B_EV + w * 8 + e), 0);
          __threadfence();
          if (e >= 5) {
            const int bi = e - 5;
            st_relaxed(&g_pflag[m][odd][(p + 1 + bi) & 3][bi][w], tag);
          } else if (!odd) {
            st_relaxed(&g_xflag[m][p][e][w], tag);
          } else {
            if (e < 2) atomicAdd(&g_kvcnt[p][0], 1u);
            else st_relaxed(&g_xflag[m][p][6 + e - 2][w], tag);
          }
        }
      }
    } else {
      if (!odd) {
        {
          const int ce = m * 4 + p;
          float* kvn = &g_kv[par ^ 1][0][0][0];
          for (int i = lane; i < 128; i += 32) kvn[ce * 128 + i] = 0.f;
          if (lane < 8) (&g_z[par ^ 1][0][0])[ce * 8 + lane] = 0.f;
        }
        mbar_wait(BAR(B_XDONE), 0);
        wait_count_ge(&g_kvcnt[p][0], 64u * tag);
        const float* kvp = &g_kv[par][8 * p][0][0];
        const uint32_t dst0 = sbase + 5 * 8192, dst1 = dst0 + 65536;
#pragma unroll 4
        for (int i = 0; i < 16; i++) {
          float4 v = ldg_cg_f4(kvp + (i * 32 + lane) * 4);
          uint32_t lo = pack_bf16(v.x, v.y), hi = pack_bf16(v.z, v.w);
          uint32_t off = (uint32_t)(i * 32 + lane) * 8u;
          asm volatile("st.shared.v2.u32 [%0], {%1,%2};" ::"r"(dst0 + off), "r"(lo), "r"(hi) : "memory");
          asm volatile("st.shared.v2.u32 [%0], {%1,%2};" ::"r"(dst1 + off), "r"(lo), "r"(hi) : "memory");
        }
        {
          float4 v = ldg_cg_f4(&g_z[par][8 * p][0] + lane * 4);
          uint32_t lo = pack_bf16(v.x, v.y), hi = pack_bf16(v.z, v.w);
          uint32_t off = 4096u + (uint32_t)lane * 8u;
          asm volatile("st.shared.v2.u32 [%0], {%1,%2};" ::"r"(dst0 + off), "r"(lo), "r"(hi) : "memory");
          asm volatile("st.shared.v2.u32 [%0], {%1,%2};" ::"r"(dst1 + off), "r"(lo), "r"(hi) : "memory");
        }
        __syncwarp();
        if (lane == 0) mbar_arrive(BAR(B_KVREADY));
      }
      const uint32_t* flag = nullptr;
      if (lane < 12) {
        const int w = lane / 6, idx = lane - w * 6;
        if (odd ? idx < 5 : idx < 3) flag = &g_xflag[m][p][odd ? idx : 6 + idx][w];
      } else if (lane < 18) {
        const int w = (lane - 12) / 3, idx = lane - 12 - w * 3;
        flag = &g_pflag[m][odd][p][idx][w];
      }
      bool pending = flag != nullptr;
      uint32_t it = 0;
      while (__any_sync(0xffffffffu, pending)) {
        if (pending) {
          if (ld_acquire(flag) == tag || it > kSpinLimit) { mbar_arrive(BAR(B_XIN + lane)); pending = false; }
        }
        ++it;
        __nanosleep(32);
      }
    }
  } else {
    asm volatile("setmaxnreg.inc.sync.aligned.u32 240;");
    const uint32_t epoch = ld_relaxed(&g_epoch);
    const int par = epoch & 1;
    const int w = warp >> 2, wq = warp & 3, t128 = tid & 127;
    const int g = lane >> 2, tq = lane & 3;
    const uint32_t area = sbase + (uint32_t)w * 65536u;
    const bool elect = (t128 == 0);
    PROF(w, 22);
    const uint32_t dbase = (sbase & 0x3FFFFu) >> 4;
    uint32_t A[144];
    float rs0, rs1;
    auto release = [&](int st) {
      if (elect) { mbar_arrive_cluster(BAR(B_EMPTY + st), 0); mbar_arrive_cluster(BAR(B_EMPTY + st), 1); }
    };

    {
      const int row = wq * 16 + (lane & 7) + ((lane >> 3) & 1) * 8;
      const uint32_t rbase = area + row * 128;
      float s0[2][4] = {}, q0[2][4] = {}, q1[2][4] = {};
      const uint32_t ones = 0x3F803F80u;
#pragma unroll
      for (int b = 0; b < 8; b++) {
        mbar_wait(BAR(B_XFULL + w * 8 + b), 0);
        if (b == 0) PROF(w, 23);
        if (b == 7) PROF(w, 24);
#pragma unroll
        for (int kk = 0; kk < 4; kk++) {
          const int i = (b * 4 + kk) * 4;
          ldmatrix_x4(rbase + b * 8192 + (((kk * 2 + (lane >> 4)) ^ (row & 7)) << 4), A[i], A[i + 1], A[i + 2], A[i + 3]);
        }
#pragma unroll
        for (int kk = 0; kk < 4; kk++) {
          const int i = (b * 4 + kk) * 4;
          mma_16816(s0[kk & 1], A[i], A[i + 1], A[i + 2], A[i + 3], ones, ones);
          mma_16816(q0[kk & 1], A[i], A[i + 1], A[i + 2], A[i + 3], A[i], A[i + 2]);
          mma_16816(q1[kk & 1], A[i], A[i + 1], A[i + 2], A[i + 3], A[i + 1], A[i + 3]);
        }
      }
      const float mean0 = (s0[0][0] + s0[1][0]) * (1.f / 512.f), mean1 = (s0[0][2] + s0[1][2]) * (1.f / 512.f);
      const uint32_t m0 = pack_bf16(mean0, mean0), m1 = pack_bf16(mean1, mean1);
#pragma unroll
      for (int i = 0; i < 128; i += 2) {
        A[i] = hsub2_bf16(A[i], m0);
        A[i + 1] = hsub2_bf16(A[i + 1], m1);
      }
      float v0 = (g & 1) ? q0[0][1] + q0[1][1] : q0[0][0] + q0[1][0];
      float v1 = (g & 1) ? q1[0][3] + q1[1][3] : q1[0][2] + q1[1][2];
      const int src = 4 * g + (g >> 1);
      v0 = __shfl_sync(0xffffffffu, v0, src);
      v1 = __shfl_sync(0xffffffffu, v1, src);
      v0 = fmaxf(v0 * (1.f / 512.f) - mean0 * mean0, 0.f);
      v1 = fmaxf(v1 * (1.f / 512.f) - mean1 * mean1, 0.f);
      rs0 = rsqrtf(v0 + 1e-5f);
      rs1 = rsqrtf(v1 + 1e-5f);
      bar_sync(1 + w, 128);
      cluster_wait();
      PROF(w, 0);
      release(6); release(7);
      if (elect) mbar_arrive(BAR(B_XDONE));
    }

    auto gu_chunk = [&](float (&acc)[32], int f, int slot, int xslot, int hb) {
      const float c0 = rs0 * -1.4426950408889634f, c1 = rs1 * -1.4426950408889634f;
      const float q0 = rs0 * rs0, q1 = rs1 * rs1;
      uint32_t h[4];
#pragma unroll
      for (int i = 0; i < 4; i++) {
        const float ga = acc[f * 8 + 2 * i], gb = acc[f * 8 + 2 * i + 1];
        const float ua = acc[16 + f * 8 + 2 * i], ub = acc[16 + f * 8 + 2 * i + 1];
        const float c = (i & 1) ? c1 : c0, q = (i & 1) ? q1 : q0;
        const float da = 1.f + ex2f(fminf(ga * c, 60.f)), db = 1.f + ex2f(fminf(gb * c, 60.f));
        const float rq = rcpf(da * db) * q;
        h[i] = pack_bf16(ga * ua * (db * rq), gb * ub * (da * rq));
      }
      const int jj = hb * 2 + f;
      sts_u4(area + slot * 8192 + jj * 2048 + t128 * 16, h[0], h[1], h[2], h[3]);
      stg_u4(&g_xbuf[m][p][xslot][w][jj][t128], h[0], h[1], h[2], h[3]);
    };
    auto kv_stage = [&](float (&acc)[32], int c, int hb) {
      const int srow = wq * 16 + (lane & 7) + ((lane >> 3) & 1) * 8;
      const uint32_t base = area + (3 + c) * 8192 + srow * 128;
#pragma unroll
      for (int jj = 0; jj < 2; jj++) {
        const int a = c * 16 + jj * 8;
        uint32_t r0, r1, r2, r3;
        if (c == 0) {
          r0 = pack_bf16(phi_f(acc[a] * rs0), phi_f(acc[a + 1] * rs0));
          r1 = pack_bf16(phi_f(acc[a + 2] * rs1), phi_f(acc[a + 3] * rs1));
          r2 = pack_bf16(phi_f(acc[a + 4] * rs0), phi_f(acc[a + 5] * rs0));
          r3 = pack_bf16(phi_f(acc[a + 6] * rs1), phi_f(acc[a + 7] * rs1));
        } else {
          r0 = pack_bf16(acc[a] * rs0, acc[a + 1] * rs0);
          r1 = pack_bf16(acc[a + 2] * rs1, acc[a + 3] * rs1);
          r2 = pack_bf16(acc[a + 4] * rs0, acc[a + 5] * rs0);
          r3 = pack_bf16(acc[a + 6] * rs1, acc[a + 7] * rs1);
        }
        stmatrix_x4(base + (((hb * 4 + jj * 2 + (lane >> 4)) ^ (srow & 7)) << 4), r0, r1, r2, r3);
      }
    };
    auto q_head = [&](float (&acc)[32], int c, int slot, uint32_t b0, uint32_t b1, uint32_t b2, uint32_t b3, uint32_t z0, uint32_t z1) {
      const int a = c * 8;
      const uint32_t a0 = pack_bf16(phi_f(acc[a] * rs0), phi_f(acc[a + 1] * rs0));
      const uint32_t a1 = pack_bf16(phi_f(acc[a + 2] * rs1), phi_f(acc[a + 3] * rs1));
      const uint32_t a2 = pack_bf16(phi_f(acc[a + 4] * rs0), phi_f(acc[a + 5] * rs0));
      const uint32_t a3 = pack_bf16(phi_f(acc[a + 6] * rs1), phi_f(acc[a + 7] * rs1));
      float n0[4] = {0.f, 0.f, 0.f, 0.f}, n1[4] = {0.f, 0.f, 0.f, 0.f}, dn[4] = {0.f, 0.f, 0.f, 0.f};
      mma_16816(n0, a0, a1, a2, a3, b0, b1);
      mma_16816(n1, a0, a1, a2, a3, b2, b3);
      mma_16816(dn, a0, a1, a2, a3, z0, z1);
      const float i0 = __fdividef(1.f, dn[0] + 1e-6f), i1 = __fdividef(1.f, dn[2] + 1e-6f);
      const uint32_t o0 = pack_bf16(n0[0] * i0, n0[1] * i0), o1 = pack_bf16(n0[2] * i1, n0[3] * i1);
      const uint32_t o2 = pack_bf16(n1[0] * i0, n1[1] * i0), o3 = pack_bf16(n1[2] * i1, n1[3] * i1);
      sts_u4(area + slot * 8192 + c * 2048 + t128 * 16, o0, o1, o2, o3);
      stg_u4(&g_xbuf[m][p][slot][w][c][t128], o0, o1, o2, o3);
    };
    const uint32_t kvb = area + 5 * 8192;
    const uint32_t kvfrag = kvb + ((lane & 7) + ((lane >> 3) & 1) * 8) * 32 + (lane >> 4) * 16;
    auto signal = [&](int e) {
      __syncwarp();
      if (lane == 0) mbar_arrive(BAR(B_EV + w * 8 + e));
    };

    float accB[32];
#pragma unroll 1
    for (int t = 0; t < 5; t++) {
      float accA[32];
      const uint32_t ph = t & 1;
      const int kindP = t == 0 ? K_NONE : ((odd && t <= 2) ? K_KV : K_GU);
      const int kindC = odd ? (t < 2 ? K_KV : K_GU) : (t < 4 ? K_GU : K_Q);
      const int slotP = odd ? t - 3 : t - 1, xslotP = odd ? t + 3 : t - 1;
      const int slotC = odd ? t - 2 : t, xslotC = odd ? t + 4 : t;
      static_for<8>([&](auto kc) {
        constexpr int k = decltype(kc)::value;
        mbar_wait(BAR(B_FULL + k), ph);
        wgmma_fence();
        static_for<8>([&](auto kkc) {
          constexpr int kk = decltype(kkc)::value;
          constexpr int i = ((k & 3) * 8 + kk) * 4;
          constexpr uint32_t lo = desc_lo(stage_off(k) + kk * 1024, 8192);
          if constexpr (k < 4) wgmma_n64_rs<((k & 3) | kk) != 0, lo, kHi64>(accA, A[i], A[i + 1], A[i + 2], A[i + 3], dbase);
          else wgmma_n64_rs<((k & 3) | kk) != 0, lo, kHi64>(accB, A[i], A[i + 1], A[i + 2], A[i + 3], dbase);
        });
        wgmma_commit();
        if (k > 0) {
          wgmma_wait<1>();
          release(k - 1);
        }
        if constexpr (k < 4) {
          if (kindP == K_GU) {
            if (k == 1 || k == 2) gu_chunk(accB, k - 1, slotP, xslotP, 1);
            if (k == 2) signal(t - 1);
          } else if (kindP == K_KV) {
            if (k == 1 || k == 2) kv_stage(accB, k - 1, 1);
            if (k == 3) {
              float kvacc[36];
              fence_proxy_async();
              bar_sync(1 + w, 128);
              wgmma_fence();
              static_for<4>([&](auto kkc) {
                constexpr int kk = decltype(kkc)::value;
                wgmma_n72_ss_tt<kk != 0, desc_lo(3 * 8192 + kk * 2048, 0), desc_lo(4 * 8192 + kk * 2048, 8192 - kk * 2048)>(kvacc, dbase + w * 4096);
              });
              wgmma_commit();
              wgmma_wait<0>();
              float c[8];
#pragma unroll
              for (int i = 0; i < 8; i++)
                c[i] = wq == 0 ? kvacc[i] : (wq == 1 ? kvacc[8 + i] : (wq == 2 ? kvacc[16 + i] : kvacc[24 + i]));
              const int head = (2 * p + t - 1) * 4 + wq;
              float* kvp = &g_kv[par][head][0][0];
              red_add_v2(kvp + g * 16 + 2 * tq, c[0], c[1]);
              red_add_v2(kvp + (g + 8) * 16 + 2 * tq, c[2], c[3]);
              red_add_v2(kvp + g * 16 + 8 + 2 * tq, c[4], c[5]);
              red_add_v2(kvp + (g + 8) * 16 + 8 + 2 * tq, c[6], c[7]);
              if (tq == 0) {
                red_add(&g_z[par][head][g], kvacc[32]);
                red_add(&g_z[par][head][g + 8], kvacc[34]);
              }
              signal(t - 1);
            }
          }
        } else {
          constexpr int c = k - 4;
          if (kindC == K_GU) {
            if (c < 2) gu_chunk(accA, c, slotC, xslotC, 0);
          } else if (kindC == K_KV) {
            if (c == 0 && t == 0) sts_u4(area + 5 * 8192 + t128 * 16, 0x3F803F80u, 0x3F803F80u, 0x3F803F80u, 0x3F803F80u);
            if (c < 2) kv_stage(accA, c, 0);
          } else {
            if (c == 0) mbar_wait(BAR(B_KVREADY), 0);
            uint32_t b0, b1, b2, b3;
            ldmatrix_x4_trans(kvfrag + c * 512, b0, b1, b2, b3);
            const uint32_t z0 = lds_u32(kvb + 4096 + c * 32 + tq * 4), z1 = lds_u32(kvb + 4096 + c * 32 + 16 + tq * 4);
            q_head(accA, c, 4, b0, b1, b2, b3, z0, z1);
          }
        }
      });
      wgmma_wait<0>();
      release(7);
      PROF(w, 1 + 2 * t);
    }
    if (odd) {
      gu_chunk(accB, 0, 2, 8, 1);
      gu_chunk(accB, 1, 2, 8, 1);
    } else {
      uint32_t Bf[4][6];
#pragma unroll
      for (int c = 0; c < 4; c++) {
        ldmatrix_x4_trans(kvfrag + (4 + c) * 512, Bf[c][0], Bf[c][1], Bf[c][2], Bf[c][3]);
        Bf[c][4] = lds_u32(kvb + 4096 + (4 + c) * 32 + tq * 4);
        Bf[c][5] = lds_u32(kvb + 4096 + (4 + c) * 32 + 16 + tq * 4);
      }
      bar_sync(1 + w, 128);
#pragma unroll
      for (int c = 0; c < 4; c++) q_head(accB, c, 5, Bf[c][0], Bf[c][1], Bf[c][2], Bf[c][3], Bf[c][4], Bf[c][5]);
    }
    signal(4);
    PROF(w, 10);

    const int n_own = odd ? 3 : 6;
    auto load_a = [&](int kb) {
      if (kb < n_own) {
#pragma unroll
        for (int jj = 0; jj < 4; jj++) {
          const int i = (kb * 4 + jj) * 4;
          lds_u4(area + kb * 8192 + jj * 2048 + t128 * 16, A[i], A[i + 1], A[i + 2], A[i + 3]);
        }
      } else {
        const int xs = odd ? kb - 3 : kb;
        const int ev = odd ? (kb - 3 < 4 ? kb - 3 : 4) : kb - 6;
        mbar_wait(BAR(B_XIN + w * 6 + ev), 0);
#pragma unroll
        for (int jj = 0; jj < 4; jj++) {
          const int i = (kb * 4 + jj) * 4;
          uint4 v = ldg_cg_u4(&g_xbuf[m][p][xs][w][jj][t128]);
          A[i] = v.x; A[i + 1] = v.y; A[i + 2] = v.z; A[i + 3] = v.w;
        }
      }
    };
#pragma unroll
    for (int kb = 0; kb < 7; kb++) load_a(kb);
    PROF(w, 11);

    const int orow = m * 128 + w * 64 + wq * 16 + g;
    const int ocol = odd * 256 + p * 64 + 2 * tq;
    float acc2[2][32];
    float4 P0[8], P1[8], P2[8];
    uint32_t xr[16];
    auto send = [&](float (&acc)[32], int bi) {
      float4* dst = &g_pbuf[m][odd][(p + 1 + bi) & 3][bi][w][0][t128];
#pragma unroll
      for (int q = 0; q < 8; q++) stg_f4(dst + q * 128, acc[q * 4], acc[q * 4 + 1], acc[q * 4 + 2], acc[q * 4 + 3]);
      signal(5 + bi);
      PROF(w, 12 + 2 * bi);
    };
    static_for<36>([&](auto ic) {
      constexpr int i = decltype(ic)::value, bi = p2_bi(i), kb = p2_kb(i), j = i >> 1, st = j & 7;
      if (i == 9) { load_a(7); load_a(8); }
      if ((i & 1) == 0) mbar_wait(BAR(B_FULL + st), (5 + (j >> 3)) & 1);
      wgmma_fence();
      static_for<4>([&](auto kkc) {
        constexpr int kk = decltype(kkc)::value, a = (kb * 4 + kk) * 4;
        wgmma_n64_rs<(kb | kk) != 0, desc_lo(stage_off(st) + (i & 1) * 8192 + kk * 2048, 0), kHi128>(acc2[bi & 1], A[a], A[a + 1], A[a + 2], A[a + 3], dbase);
      });
      wgmma_commit();
      if (i > 0) {
        wgmma_wait<1>();
        if ((i & 1) == 0 && j - 1 <= 9) release((j - 1) & 7);
      }
      if constexpr (i == 16) send(acc2[0], 0);
      if constexpr (i == 18) send(acc2[1], 1);
      if constexpr (i == 27) send(acc2[0], 2);
      if constexpr (i == 29) {
        mbar_wait(BAR(B_PIN + w * 3 + 0), 0);
#pragma unroll
        for (int q = 0; q < 8; q++) P0[q] = ldg_cg_f4(&g_pbuf[m][odd][p][0][w][q][t128]);
      }
      if constexpr (i == 31) {
        mbar_wait(BAR(B_PIN + w * 3 + 1), 0);
#pragma unroll
        for (int q = 0; q < 8; q++) P1[q] = ldg_cg_f4(&g_pbuf[m][odd][p][1][w][q][t128]);
      }
      if constexpr (i == 32) {
#pragma unroll
        for (int q = 0; q < 8; q++) {
          xr[2 * q] = __ldg((const uint32_t*)(x + (size_t)orow * kD + ocol + q * 8));
          xr[2 * q + 1] = __ldg((const uint32_t*)(x + (size_t)(orow + 8) * kD + ocol + q * 8));
        }
      }
      if constexpr (i == 35) {
        mbar_wait(BAR(B_PIN + w * 3 + 2), 0);
#pragma unroll
        for (int q = 0; q < 8; q++) P2[q] = ldg_cg_f4(&g_pbuf[m][odd][p][2][w][q][t128]);
      }
    });
    wgmma_wait<0>();
    PROF(w, 18);
#pragma unroll
    for (int q = 0; q < 8; q++) {
      const float r0 = acc2[1][q * 4 + 0] + P0[q].x + P1[q].x + P2[q].x + __uint_as_float(xr[2 * q] << 16);
      const float r1 = acc2[1][q * 4 + 1] + P0[q].y + P1[q].y + P2[q].y + __uint_as_float(xr[2 * q] & 0xffff0000u);
      const float r2 = acc2[1][q * 4 + 2] + P0[q].z + P1[q].z + P2[q].z + __uint_as_float(xr[2 * q + 1] << 16);
      const float r3 = acc2[1][q * 4 + 3] + P0[q].w + P1[q].w + P2[q].w + __uint_as_float(xr[2 * q + 1] & 0xffff0000u);
      *(uint32_t*)(out + (size_t)orow * kD + ocol + q * 8) = pack_bf16(r0, r1);
      *(uint32_t*)(out + (size_t)(orow + 8) * kD + ocol + q * 8) = pack_bf16(r2, r3);
    }
    PROF(w, 19);
    if (tid == 0) {
      const uint32_t old = atomicAdd(&g_done, 1u);
      if ((old & 127u) == 127u) *(volatile uint32_t*)&g_epoch = epoch + 1u;
    }
  }
#undef BAR
}

typedef CUresult (*EncodeFn)(CUtensorMap*, CUtensorMapDataType, cuuint32_t, void*, const cuuint64_t*, const cuuint64_t*,
                             const cuuint32_t*, const cuuint32_t*, CUtensorMapInterleave, CUtensorMapSwizzle,
                             CUtensorMapL2promotion, CUtensorMapFloatOOBfill);

void make_map(EncodeFn enc, CUtensorMap* tm, const void* ptr, int rows, int cols, bool narrow) {
  cuuint64_t gd[2] = {(cuuint64_t)cols, (cuuint64_t)rows};
  cuuint64_t gs[1] = {(cuuint64_t)cols * 2};
  cuuint32_t bd[2] = {narrow ? 32u : 64u, narrow ? 128u : 64u};
  cuuint32_t es[2] = {1, 1};
  enc(tm, CU_TENSOR_MAP_DATA_TYPE_BFLOAT16, 2, const_cast<void*>(ptr), gd, gs, bd, es, CU_TENSOR_MAP_INTERLEAVE_NONE,
      narrow ? CU_TENSOR_MAP_SWIZZLE_64B : CU_TENSOR_MAP_SWIZZLE_128B, CU_TENSOR_MAP_L2_PROMOTION_L2_256B, CU_TENSOR_MAP_FLOAT_OOB_FILL_NONE);
}

}

extern "C" void kernel_launch(void* const* d_in, const int* in_sizes, int n_in, void* d_out, int out_size) {
  static EncodeFn enc = nullptr;
  if (!enc) {
    void* fn = nullptr;
    cudaDriverEntryPointQueryResult qr;
    cudaGetDriverEntryPoint("cuTensorMapEncodeTiled", &fn, cudaEnableDefault, &qr);
    enc = (EncodeFn)fn;
    cudaFuncSetAttribute(fused_kernel, cudaFuncAttributeMaxDynamicSharedMemorySize, kSmemBytes);
  }
  CUtensorMap tm_x, tm_wqkv, tm_w1, tm_w3, tm_w2, tm_wo;
  make_map(enc, &tm_x, d_in[0], kS, kD, false);
  make_map(enc, &tm_wqkv, d_in[1], kD, 3 * kD, true);
  make_map(enc, &tm_wo, d_in[2], kD, kD, false);
  make_map(enc, &tm_w1, d_in[4], kD, kF, true);
  make_map(enc, &tm_w3, d_in[5], kD, kF, true);
  make_map(enc, &tm_w2, d_in[6], kF, kD, false);
  fused_kernel<<<128, 384, kSmemBytes>>>(tm_x, tm_wqkv, tm_w1, tm_w3, tm_w2, tm_wo, (const __nv_bfloat16*)d_in[0],
                                         (__nv_bfloat16*)d_out);
}
```

```cpp
#include <cuda_runtime.h>
#include <cuda_bf16.h>
#include <cuda.h>
#include <stdint.h>

namespace {

constexpr int kS = 2048, kD = 512, kF = 1792;
constexpr uint32_t kSpinLimit = 1u << 22;

__device__ uint4    g_xbuf[16][4][9][2][4][128];
__device__ uint4    g_pbuf[16][2][4][3][2][8][128];
__device__ float    g_kv[2][32][16][16];
__device__ float    g_z[2][32][16];
__device__ uint32_t g_kvcnt[4][32];
__device__ uint32_t g_epoch;
__device__ uint32_t g_done;
#define PROF(wg, i) do {} while (0)

__device__ __forceinline__ uint32_t smem_u32(const void* p) { return (uint32_t)__cvta_generic_to_shared(p); }
__device__ __forceinline__ void mbar_init(uint32_t bar, uint32_t cnt) {
  asm volatile("mbarrier.init.shared::cta.b64 [%0], %1;" ::"r"(bar), "r"(cnt) : "memory");
}
__device__ __forceinline__ void mbar_expect_tx(uint32_t bar, uint32_t bytes) {
  asm volatile("mbarrier.arrive.expect_tx.shared::cta.b64 _, [%0], %1;" ::"r"(bar), "r"(bytes) : "memory");
}
__device__ __forceinline__ void mbar_arrive(uint32_t bar) {
  asm volatile("mbarrier.arrive.shared::cta.b64 _, [%0];" ::"r"(bar) : "memory");
}
__device__ __forceinline__ void mbar_wait(uint32_t bar, uint32_t parity) {
  asm volatile(
      "{\n.reg .pred p;\n"
      "LAB_WAIT:\n"
      "mbarrier.try_wait.parity.shared::cta.b64 p, [%0], %1;\n"
      "@p bra DONE;\n"
      "bra LAB_WAIT;\n"
      "DONE:\n}" ::"r"(bar), "r"(parity) : "memory");
}
__device__ __forceinline__ void tma_load_2d(uint32_t dst, const CUtensorMap* tm, uint32_t bar, int c0, int c1) {
  asm volatile(
      "cp.async.bulk.tensor.2d.shared::cluster.global.mbarrier::complete_tx::bytes [%0], [%1, {%3, %4}], [%2];" ::"r"(dst),
      "l"(tm), "r"(bar), "r"(c0), "r"(c1)
      : "memory");
}
__device__ __forceinline__ void tma_load_2d_mc(uint32_t dst, const CUtensorMap* tm, uint32_t bar, int c0, int c1) {
  asm volatile(
      "cp.async.bulk.tensor.2d.shared::cluster.global.mbarrier::complete_tx::bytes.multicast::cluster [%0], [%1, {%3, %4}], [%2], %5;" ::"r"(dst),
      "l"(tm), "r"(bar), "r"(c0), "r"(c1), "h"((uint16_t)3)
      : "memory");
}
__device__ __forceinline__ void mbar_arrive_cluster(uint32_t bar, uint32_t cta) {
  asm volatile("{\n.reg .b32 ra;\nmapa.shared::cluster.u32 ra, %0, %1;\nmbarrier.arrive.shared::cluster.b64 _, [ra];\n}" ::"r"(bar), "r"(cta) : "memory");
}
__device__ __forceinline__ void prefetch_tmap(const CUtensorMap* tm) {
  asm volatile("prefetch.tensormap [%0];" ::"l"(tm) : "memory");
}
__device__ __forceinline__ void wgmma_fence() { asm volatile("wgmma.fence.sync.aligned;" ::: "memory"); }
__device__ __forceinline__ void wgmma_commit() { asm volatile("wgmma.commit_group.sync.aligned;" ::: "memory"); }
template <int N>
__device__ __forceinline__ void wgmma_wait() { asm volatile("wgmma.wait_group.sync.aligned %0;" ::"n"(N) : "memory"); }
__device__ __forceinline__ void bar_sync(int id, int n) { asm volatile("bar.sync %0, %1;" ::"r"(id), "r"(n) : "memory"); }
__device__ __forceinline__ void bar_arrive(int id, int n) { asm volatile("bar.arrive %0, %1;" ::"r"(id), "r"(n) : "memory"); }
__device__ __forceinline__ void fence_proxy_async() { asm volatile("fence.proxy.async.shared::cta;" ::: "memory"); }

__device__ __forceinline__ uint32_t ld_acquire(const uint32_t* p) {
  uint32_t v;
  asm volatile("ld.acquire.gpu.global.u32 %0, [%1];" : "=r"(v) : "l"(p) : "memory");
  return v;
}
__device__ __forceinline__ uint32_t ld_relaxed(const uint32_t* p) {
  uint32_t v;
  asm volatile("ld.relaxed.gpu.global.u32 %0, [%1];" : "=r"(v) : "l"(p));
  return v;
}
__device__ __forceinline__ void cluster_wait() { asm volatile("barrier.cluster.wait.aligned;" ::: "memory"); }
__device__ __forceinline__ void st_relaxed(uint32_t* p, uint32_t v) {
  asm volatile("st.relaxed.gpu.global.u32 [%0], %1;" ::"l"(p), "r"(v) : "memory");
}
__device__ __forceinline__ void wait_flag_eq(const uint32_t* p, uint32_t val) {
  uint32_t it = 0;
  while (ld_acquire(p) != val) {
    if (++it > kSpinLimit) break;
  }
}
__device__ __forceinline__ void wait_count_ge(const uint32_t* p, uint32_t val) {
  uint32_t it = 0;
  while ((int32_t)(ld_acquire(p) - val) < 0) {
    __nanosleep(64);
    if (++it > kSpinLimit) break;
  }
}
__device__ __forceinline__ void ldg_poll_u4(const void* p, uint32_t& a, uint32_t& b, uint32_t& c, uint32_t& d) {
  asm volatile("ld.relaxed.gpu.global.v4.u32 {%0,%1,%2,%3}, [%4];" : "=r"(a), "=r"(b), "=r"(c), "=r"(d) : "l"(p) : "memory");
}
__device__ __forceinline__ void recv_u4(void* p, uint32_t& a, uint32_t& b, uint32_t& c, uint32_t& d) {
  uint32_t it = 0;
  while (min(min(a, b), min(c, d)) == 0u) {
    if (++it > kSpinLimit) break;
    ldg_poll_u4(p, a, b, c, d);
  }
  a = ~a; b = ~b; c = ~c; d = ~d;
  asm volatile("st.global.v4.u32 [%0], {%1,%1,%1,%1};" ::"l"(p), "r"(0u) : "memory");
}
__device__ __forceinline__ void send_u4(void* p, uint32_t a, uint32_t b, uint32_t c, uint32_t d) {
  asm volatile("st.relaxed.gpu.global.v4.u32 [%0], {%1,%2,%3,%4};" ::"l"(p), "r"(~a), "r"(~b), "r"(~c), "r"(~d) : "memory");
}
__device__ __forceinline__ float4 ldg_cg_f4(const void* p) {
  float4 v;
  asm volatile("ld.global.cg.v4.f32 {%0,%1,%2,%3}, [%4];" : "=f"(v.x), "=f"(v.y), "=f"(v.z), "=f"(v.w) : "l"(p) : "memory");
  return v;
}
__device__ __forceinline__ void stg_u4(void* p, uint32_t a, uint32_t b, uint32_t c, uint32_t d) {
  asm volatile("st.global.v4.u32 [%0], {%1,%2,%3,%4};" ::"l"(p), "r"(a), "r"(b), "r"(c), "r"(d) : "memory");
}
__device__ __forceinline__ void stg_f4(void* p, float a, float b, float c, float d) {
  asm volatile("st.global.v4.f32 [%0], {%1,%2,%3,%4};" ::"l"(p), "f"(a), "f"(b), "f"(c), "f"(d) : "memory");
}
__device__ __forceinline__ void sts_u4(uint32_t addr, uint32_t a, uint32_t b, uint32_t c, uint32_t d) {
  asm volatile("st.shared.v4.u32 [%0], {%1,%2,%3,%4};" ::"r"(addr), "r"(a), "r"(b), "r"(c), "r"(d) : "memory");
}
__device__ __forceinline__ void lds_u4(uint32_t addr, uint32_t& a, uint32_t& b, uint32_t& c, uint32_t& d) {
  asm volatile("ld.shared.v4.u32 {%0,%1,%2,%3}, [%4];" : "=r"(a), "=r"(b), "=r"(c), "=r"(d) : "r"(addr) : "memory");
}
__device__ __forceinline__ uint32_t lds_u32(uint32_t addr) {
  uint32_t v;
  asm volatile("ld.shared.u32 %0, [%1];" : "=r"(v) : "r"(addr) : "memory");
  return v;
}
__device__ __forceinline__ void ldmatrix_x4(uint32_t addr, uint32_t& a, uint32_t& b, uint32_t& c, uint32_t& d) {
  asm volatile("ldmatrix.sync.aligned.m8n8.x4.shared.b16 {%0,%1,%2,%3}, [%4];" : "=r"(a), "=r"(b), "=r"(c), "=r"(d) : "r"(addr) : "memory");
}
__device__ __forceinline__ void ldmatrix_x4_trans(uint32_t addr, uint32_t& a, uint32_t& b, uint32_t& c, uint32_t& d) {
  asm volatile("ldmatrix.sync.aligned.m8n8.x4.trans.shared.b16 {%0,%1,%2,%3}, [%4];" : "=r"(a), "=r"(b), "=r"(c), "=r"(d) : "r"(addr) : "memory");
}
__device__ __forceinline__ void stmatrix_x4(uint32_t addr, uint32_t a, uint32_t b, uint32_t c, uint32_t d) {
  asm volatile("stmatrix.sync.aligned.m8n8.x4.shared.b16 [%0], {%1,%2,%3,%4};" ::"r"(addr), "r"(a), "r"(b), "r"(c), "r"(d) : "memory");
}
__device__ __forceinline__ void mma_16816(float (&c)[4], uint32_t a0, uint32_t a1, uint32_t a2, uint32_t a3, uint32_t b0, uint32_t b1) {
  asm volatile(
      "mma.sync.aligned.m16n8k16.row.col.f32.bf16.bf16.f32 {%0,%1,%2,%3}, {%4,%5,%6,%7}, {%8,%9}, {%0,%1,%2,%3};"
      : "+f"(c[0]), "+f"(c[1]), "+f"(c[2]), "+f"(c[3])
      : "r"(a0), "r"(a1), "r"(a2), "r"(a3), "r"(b0), "r"(b1));
}
__device__ __forceinline__ uint32_t pack_bf16(float lo, float hi) {
  uint32_t r;
  asm("cvt.rn.bf16x2.f32 %0, %1, %2;" : "=r"(r) : "f"(hi), "f"(lo));
  return r;
}
__device__ __forceinline__ uint32_t hsub2_bf16(uint32_t a, uint32_t b) {
  uint32_t r;
  asm("sub.rn.bf16x2 %0, %1, %2;" : "=r"(r) : "r"(a), "r"(b));
  return r;
}
__device__ __forceinline__ float ex2f(float x) {
  float r;
  asm("ex2.approx.ftz.f32 %0, %1;" : "=f"(r) : "f"(x));
  return r;
}
__device__ __forceinline__ float rcpf(float x) {
  float r;
  asm("rcp.approx.ftz.f32 %0, %1;" : "=f"(r) : "f"(x));
  return r;
}
__device__ __forceinline__ void red_add_v2(float* p, float a, float b) {
  asm volatile("red.relaxed.gpu.global.add.v2.f32 [%0], {%1,%2};" ::"l"(p), "f"(a), "f"(b) : "memory");
}
__device__ __forceinline__ void red_add(float* p, float a) {
  asm volatile("red.relaxed.gpu.global.add.f32 [%0], %1;" ::"l"(p), "f"(a) : "memory");
}
__device__ __forceinline__ float phi_f(float t) {
  float e = ex2f(t * 1.4426950408889634f);
  return (t > 0.f ? t + 1.f : e) + 1e-6f;
}

#define R8(a, o) "+f"(a[o + 0]), "+f"(a[o + 1]), "+f"(a[o + 2]), "+f"(a[o + 3]), "+f"(a[o + 4]), "+f"(a[o + 5]), "+f"(a[o + 6]), "+f"(a[o + 7])

#define W8(a, o) "=f"(a[o + 0]), "=f"(a[o + 1]), "=f"(a[o + 2]), "=f"(a[o + 3]), "=f"(a[o + 4]), "=f"(a[o + 5]), "=f"(a[o + 6]), "=f"(a[o + 7])
#define D32 "{%0,%1,%2,%3,%4,%5,%6,%7,%8,%9,%10,%11,%12,%13,%14,%15,%16,%17,%18,%19,%20,%21,%22,%23,%24,%25,%26,%27,%28,%29,%30,%31}"
#define D36 "{%0,%1,%2,%3,%4,%5,%6,%7,%8,%9,%10,%11,%12,%13,%14,%15,%16,%17,%18,%19,%20,%21,%22,%23,%24,%25,%26,%27,%28,%29,%30,%31,%32,%33,%34,%35}"

constexpr uint32_t kHi128 = (1024u >> 4) | (1u << 30);
constexpr uint32_t kHi64 = (512u >> 4) | (2u << 30);
__host__ __device__ constexpr uint32_t desc_lo(uint32_t off, uint32_t lbo) { return (off >> 4) | ((lbo >> 4) << 16); }

template <bool ACC, uint32_t LO, uint32_t HI>
__device__ __forceinline__ void wgmma_n64_rs(float (&d)[32], uint32_t a0, uint32_t a1, uint32_t a2, uint32_t a3, uint32_t base) {
  if (ACC) {
    asm volatile(
        "{\n.reg .pred p;\n.reg .b32 lo;\n.reg .b64 dd;\nsetp.eq.b32 p, 0, 0;\nadd.u32 lo, %36, %37;\nmov.b64 dd, {lo, %38};\n"
        "wgmma.mma_async.sync.aligned.m64n64k16.f32.bf16.bf16 " D32 ", {%32,%33,%34,%35}, dd, p, 1, 1, 1;\n}"
        : R8(d, 0), R8(d, 8), R8(d, 16), R8(d, 24)
        : "r"(a0), "r"(a1), "r"(a2), "r"(a3), "r"(base), "n"(LO), "n"(HI));
  } else {
    asm volatile(
        "{\n.reg .pred p;\n.reg .b32 lo;\n.reg .b64 dd;\nsetp.ne.b32 p, 0, 0;\nadd.u32 lo, %36, %37;\nmov.b64 dd, {lo, %38};\n"
        "wgmma.mma_async.sync.aligned.m64n64k16.f32.bf16.bf16 " D32 ", {%32,%33,%34,%35}, dd, p, 1, 1, 1;\n}"
        : W8(d, 0), W8(d, 8), W8(d, 16), W8(d, 24)
        : "r"(a0), "r"(a1), "r"(a2), "r"(a3), "r"(base), "n"(LO), "n"(HI));
  }
}
template <bool ACC, uint32_t LOA, uint32_t LOB>
__device__ __forceinline__ void wgmma_n72_ss_tt(float (&d)[36], uint32_t base) {
  if (ACC) {
    asm volatile(
        "{\n.reg .pred p;\n.reg .b32 lo;\n.reg .b64 da, db;\nsetp.eq.b32 p, 0, 0;\n"
        "add.u32 lo, %36, %37;\nmov.b64 da, {lo, %39};\nadd.u32 lo, %36, %38;\nmov.b64 db, {lo, %39};\n"
        "wgmma.mma_async.sync.aligned.m64n72k16.f32.bf16.bf16 " D36 ", da, db, p, 1, 1, 1, 1;\n}"
        : R8(d, 0), R8(d, 8), R8(d, 16), R8(d, 24), "+f"(d[32]), "+f"(d[33]), "+f"(d[34]), "+f"(d[35])
        : "r"(base), "n"(LOA), "n"(LOB), "n"(kHi128));
  } else {
    asm volatile(
        "{\n.reg .pred p;\n.reg .b32 lo;\n.reg .b64 da, db;\nsetp.ne.b32 p, 0, 0;\n"
        "add.u32 lo, %36, %37;\nmov.b64 da, {lo, %39};\nadd.u32 lo, %36, %38;\nmov.b64 db, {lo, %39};\n"
        "wgmma.mma_async.sync.aligned.m64n72k16.f32.bf16.bf16 " D36 ", da, db, p, 1, 1, 1, 1;\n}"
        : W8(d, 0), W8(d, 8), W8(d, 16), W8(d, 24), "=f"(d[32]), "=f"(d[33]), "=f"(d[34]), "=f"(d[35])
        : "r"(base), "n"(LOA), "n"(LOB), "n"(kHi128));
  }
}

template <int V> struct IC { static constexpr int value = V; };
template <int N, int I = 0, typename F>
__device__ __forceinline__ void static_for(F&& f) {
  if constexpr (I < N) { f(IC<I>{}); static_for<N, I + 1>(f); }
}

__host__ __device__ constexpr uint32_t stage_off(int st) {
  return st < 6 ? 131072u + (uint32_t)st * 16384u : (uint32_t)(st - 6) * 65536u + 49152u;
}

constexpr int B_FULL = 0, B_EMPTY = 8, B_XFULL = 16, B_XDONE = 32, B_KVREADY = 33, B_EV = 34, B_COUNT = 38;
constexpr uint32_t kBarOff = 229376;
constexpr int kSmemBytes = 229376 + 1024;

__host__ __device__ constexpr int p2_bi(int i) { return i < 7 ? 0 : i < 14 ? 1 : i < 16 ? 0 : i < 18 ? 1 : i / 9; }
__host__ __device__ constexpr int p2_kb(int i) { return i < 7 ? i : i < 14 ? i - 7 : i < 16 ? i - 7 : i < 18 ? i - 9 : i % 9; }

enum { K_NONE = 0, K_GU = 1, K_KV = 2, K_Q = 3 };

__global__ void __cluster_dims__(2, 1, 1) __launch_bounds__(384, 1)
fused_kernel(const __grid_constant__ CUtensorMap tm_x, const __grid_constant__ CUtensorMap tm_wqkv,
             const __grid_constant__ CUtensorMap tm_w1, const __grid_constant__ CUtensorMap tm_w3,
             const __grid_constant__ CUtensorMap tm_w2, const __grid_constant__ CUtensorMap tm_wo,
             const __nv_bfloat16* __restrict__ x, __nv_bfloat16* __restrict__ out) {
  extern __shared__ __align__(1024) uint8_t smem_raw[];
  const uint32_t sbase = __shfl_sync(0xffffffffu, smem_u32(smem_raw), 0);
  const uint32_t bars = sbase + kBarOff;
  const int tid = threadIdx.x, lane = tid & 31;
  const int warp = __shfl_sync(0xffffffffu, tid >> 5, 0);
  const int cr = blockIdx.x & 1;
  const int r = (blockIdx.x >> 1) & 7, m = ((blockIdx.x >> 4) << 1) | cr, p = r >> 1, odd = r & 1;
#define BAR(i) (bars + 8u * (uint32_t)(i))
  if (tid == 256) {
    if (sbase & 1023u) __trap();
#pragma unroll
    for (int i = 0; i < 16; i++) mbar_init(BAR(B_XFULL + i), 1);
    fence_proxy_async();
#pragma unroll
    for (int b = 0; b < 16; b++) {
      mbar_expect_tx(BAR(B_XFULL + b), 8192);
      tma_load_2d(sbase + (b >> 3) * 65536 + (b & 7) * 8192, &tm_x, BAR(B_XFULL + b), (b & 7) * 64, m * 128 + (b >> 3) * 64);
    }
#pragma unroll
    for (int i = 0; i < 8; i++) { mbar_init(BAR(B_FULL + i), 1); mbar_init(BAR(B_EMPTY + i), 4); }
#pragma unroll
    for (int i = 0; i < 4; i++) mbar_init(BAR(B_EV + i), 4);
    mbar_init(BAR(B_XDONE), 2);
    mbar_init(BAR(B_KVREADY), 1);
    asm volatile("fence.mbarrier_init.release.cluster;" ::: "memory");
    fence_proxy_async();
  } else if (tid == 288) {
    prefetch_tmap(odd ? &tm_wqkv : (cr ? &tm_w3 : &tm_w1));
  }
  __syncwarp();
  asm volatile("barrier.cluster.arrive.relaxed.aligned;" ::: "memory");
  PROF((tid >> 7), 21);
  __syncthreads();

  if (warp >= 8) {
    asm volatile("setmaxnreg.dec.sync.aligned.u32 24;");
    PROF(2, 3);
    cluster_wait();
    PROF(2, 2);
    const uint32_t epoch = warp == 8 ? 0u : ld_relaxed(&g_epoch);
    const uint32_t tag = epoch + 1u;
    const int par = epoch & 1;
    if (warp == 8) {
      if (lane == 0) {
        for (int j = 0; j < 10; j++) {
          const CUtensorMap* tm;
          int col;
          if (!odd) {
            if (j < 8) { tm = cr ? &tm_w3 : &tm_w1; col = 7 * p * 64 + j * 32; }
            else { tm = &tm_wqkv; col = 128 * p + (j - 8) * 64 + cr * 32; }
          } else {
            if (j < 4) { tm = &tm_wqkv; col = 512 + cr * 512 + 128 * p + j * 32; }
            else { tm = cr ? &tm_w3 : &tm_w1; col = (7 * p + 4) * 64 + (j - 4) * 32; }
          }
          const int t = j >> 1;
          for (int kq = 0; kq < 4; kq++) {
            const int k = (j & 1) * 4 + kq;
            mbar_wait(BAR(B_EMPTY + k), k < 6 ? ((t & 1) ^ 1) : (t & 1));
            mbar_expect_tx(BAR(B_FULL + k), 16384);
            tma_load_2d_mc(sbase + stage_off(k) + cr * 8192, tm, BAR(B_FULL + k), col, kq * 128);
          }
        }
        for (int j = 0; j < 18; j++) {
          const int st = j & 7, n = 5 + (j >> 3);
          const int i = 2 * j + cr;
          const int bi = p2_bi(i), kb = p2_kb(i);
          const int col = odd * 256 + ((p + 1 + bi) & 3) * 64;
          const CUtensorMap* tmk;
          int row;
          if (!odd) {
            if (kb < 4) { tmk = &tm_w2; row = (7 * p + kb) * 64; }
            else if (kb < 6) { tmk = &tm_wo; row = (2 * p + kb - 4) * 64; }
            else { tmk = &tm_w2; row = (7 * p + 4 + kb - 6) * 64; }
          } else {
            if (kb < 3) { tmk = &tm_w2; row = (7 * p + 4 + kb) * 64; }
            else if (kb < 7) { tmk = &tm_w2; row = (7 * p + kb - 3) * 64; }
            else { tmk = &tm_wo; row = (2 * p + kb - 7) * 64; }
          }
          mbar_wait(BAR(B_EMPTY + st), st < 6 ? ((n & 1) ^ 1) : (n & 1));
          mbar_expect_tx(BAR(B_FULL + st), 16384);
          tma_load_2d_mc(sbase + stage_off(st) + cr * 8192, tmk, BAR(B_FULL + st), col, row);
        }
      }
    } else if (warp <= 10) {
      if (lane == 0 && odd) {
        const int w = warp - 9;
        for (int e = 0; e < 2; e++) {
          mbar_wait(BAR(B_EV + w * 2 + e), 0);
          __threadfence();
          atomicAdd(&g_kvcnt[p][0], 1u);
        }
      }
    } else {
      if (!odd) {
        {
          const int ce = m * 4 + p;
          float* kvn = &g_kv[par ^ 1][0][0][0];
          for (int i = lane; i < 128; i += 32) kvn[ce * 128 + i] = 0.f;
          if (lane < 8) (&g_z[par ^ 1][0][0])[ce * 8 + lane] = 0.f;
        }
        mbar_wait(BAR(B_XDONE), 0);
        wait_count_ge(&g_kvcnt[p][0], 64u * tag);
        const float* kvp = &g_kv[par][8 * p][0][0];
        const uint32_t dst0 = sbase + 5 * 8192, dst1 = dst0 + 65536;
#pragma unroll 4
        for (int i = 0; i < 16; i++) {
          float4 v = ldg_cg_f4(kvp + (i * 32 + lane) * 4);
          uint32_t lo = pack_bf16(v.x, v.y), hi = pack_bf16(v.z, v.w);
          uint32_t off = (uint32_t)(i * 32 + lane) * 8u;
          asm volatile("st.shared.v2.u32 [%0], {%1,%2};" ::"r"(dst0 + off), "r"(lo), "r"(hi) : "memory");
          asm volatile("st.shared.v2.u32 [%0], {%1,%2};" ::"r"(dst1 + off), "r"(lo), "r"(hi) : "memory");
        }
        {
          float4 v = ldg_cg_f4(&g_z[par][8 * p][0] + lane * 4);
          uint32_t lo = pack_bf16(v.x, v.y), hi = pack_bf16(v.z, v.w);
          uint32_t off = 4096u + (uint32_t)lane * 8u;
          asm volatile("st.shared.v2.u32 [%0], {%1,%2};" ::"r"(dst0 + off), "r"(lo), "r"(hi) : "memory");
          asm volatile("st.shared.v2.u32 [%0], {%1,%2};" ::"r"(dst1 + off), "r"(lo), "r"(hi) : "memory");
        }
        __syncwarp();
        if (lane == 0) mbar_arrive(BAR(B_KVREADY));
      }
    }
  } else {
    asm volatile("setmaxnreg.inc.sync.aligned.u32 240;");
    const uint32_t epoch = ld_relaxed(&g_epoch);
    const int par = epoch & 1;
    const int w = warp >> 2, wq = warp & 3, t128 = tid & 127;
    const int g = lane >> 2, tq = lane & 3;
    const uint32_t area = sbase + (uint32_t)w * 65536u;
    const bool elect = (t128 == 0);
    PROF(w, 22);
    const uint32_t dbase = (sbase & 0x3FFFFu) >> 4;
    uint32_t A[144];
    float rs0, rs1;
    auto release = [&](int st) {
      if (elect) { mbar_arrive_cluster(BAR(B_EMPTY + st), 0); mbar_arrive_cluster(BAR(B_EMPTY + st), 1); }
    };

    {
      const int row = wq * 16 + (lane & 7) + ((lane >> 3) & 1) * 8;
      const uint32_t rbase = area + row * 128;
      float s0[2][4] = {}, q0[2][4] = {}, q1[2][4] = {};
      const uint32_t ones = 0x3F803F80u;
#pragma unroll
      for (int b = 0; b < 8; b++) {
        mbar_wait(BAR(B_XFULL + w * 8 + b), 0);
        if (b == 0) PROF(w, 23);
        if (b == 7) PROF(w, 24);
#pragma unroll
        for (int kk = 0; kk < 4; kk++) {
          const int i = (b * 4 + kk) * 4;
          ldmatrix_x4(rbase + b * 8192 + (((kk * 2 + (lane >> 4)) ^ (row & 7)) << 4), A[i], A[i + 1], A[i + 2], A[i + 3]);
        }
#pragma unroll
        for (int kk = 0; kk < 4; kk++) {
          const int i = (b * 4 + kk) * 4;
          mma_16816(s0[kk & 1], A[i], A[i + 1], A[i + 2], A[i + 3], ones, ones);
          mma_16816(q0[kk & 1], A[i], A[i + 1], A[i + 2], A[i + 3], A[i], A[i + 2]);
          mma_16816(q1[kk & 1], A[i], A[i + 1], A[i + 2], A[i + 3], A[i + 1], A[i + 3]);
        }
      }
      const float mean0 = (s0[0][0] + s0[1][0]) * (1.f / 512.f), mean1 = (s0[0][2] + s0[1][2]) * (1.f / 512.f);
      const uint32_t m0 = pack_bf16(mean0, mean0), m1 = pack_bf16(mean1, mean1);
#pragma unroll
      for (int i = 0; i < 128; i += 2) {
        A[i] = hsub2_bf16(A[i], m0);
        A[i + 1] = hsub2_bf16(A[i + 1], m1);
      }
      float v0 = (g & 1) ? q0[0][1] + q0[1][1] : q0[0][0] + q0[1][0];
      float v1 = (g & 1) ? q1[0][3] + q1[1][3] : q1[0][2] + q1[1][2];
      const int src = 4 * g + (g >> 1);
      v0 = __shfl_sync(0xffffffffu, v0, src);
      v1 = __shfl_sync(0xffffffffu, v1, src);
      v0 = fmaxf(v0 * (1.f / 512.f) - mean0 * mean0, 0.f);
      v1 = fmaxf(v1 * (1.f / 512.f) - mean1 * mean1, 0.f);
      rs0 = rsqrtf(v0 + 1e-5f);
      rs1 = rsqrtf(v1 + 1e-5f);
      bar_sync(1 + w, 128);
      cluster_wait();
      PROF(w, 0);
      release(6); release(7);
      if (elect) mbar_arrive(BAR(B_XDONE));
    }

    auto gu_chunk = [&](float (&acc)[32], int f, int slot, int xslot, int hb) {
      const float c0 = rs0 * -1.4426950408889634f, c1 = rs1 * -1.4426950408889634f;
      const float q0 = rs0 * rs0, q1 = rs1 * rs1;
      uint32_t h[4];
#pragma unroll
      for (int i = 0; i < 4; i++) {
        const float ga = acc[f * 8 + 2 * i], gb = acc[f * 8 + 2 * i + 1];
        const float ua = acc[16 + f * 8 + 2 * i], ub = acc[16 + f * 8 + 2 * i + 1];
        const float c = (i & 1) ? c1 : c0, q = (i & 1) ? q1 : q0;
        const float da = 1.f + ex2f(fminf(ga * c, 60.f)), db = 1.f + ex2f(fminf(gb * c, 60.f));
        const float rq = rcpf(da * db) * q;
        h[i] = pack_bf16(ga * ua * (db * rq), gb * ub * (da * rq));
      }
      const int jj = hb * 2 + f;
      sts_u4(area + slot * 8192 + jj * 2048 + t128 * 16, h[0], h[1], h[2], h[3]);
      send_u4(&g_xbuf[m][p][xslot][w][jj][t128], h[0], h[1], h[2], h[3]);
    };
    auto kv_stage = [&](float (&acc)[32], int c, int hb) {
      const int srow = wq * 16 + (lane & 7) + ((lane >> 3) & 1) * 8;
      const uint32_t base = area + (3 + c) * 8192 + srow * 128;
#pragma unroll
      for (int jj = 0; jj < 2; jj++) {
        const int a = c * 16 + jj * 8;
        uint32_t r0, r1, r2, r3;
        if (c == 0) {
          r0 = pack_bf16(phi_f(acc[a] * rs0), phi_f(acc[a + 1] * rs0));
          r1 = pack_bf16(phi_f(acc[a + 2] * rs1), phi_f(acc[a + 3] * rs1));
          r2 = pack_bf16(phi_f(acc[a + 4] * rs0), phi_f(acc[a + 5] * rs0));
          r3 = pack_bf16(phi_f(acc[a + 6] * rs1), phi_f(acc[a + 7] * rs1));
        } else {
          r0 = pack_bf16(acc[a] * rs0, acc[a + 1] * rs0);
          r1 = pack_bf16(acc[a + 2] * rs1, acc[a + 3] * rs1);
          r2 = pack_bf16(acc[a + 4] * rs0, acc[a + 5] * rs0);
          r3 = pack_bf16(acc[a + 6] * rs1, acc[a + 7] * rs1);
        }
        stmatrix_x4(base + (((hb * 4 + jj * 2 + (lane >> 4)) ^ (srow & 7)) << 4), r0, r1, r2, r3);
      }
    };
    auto q_head = [&](float (&acc)[32], int c, int slot, uint32_t b0, uint32_t b1, uint32_t b2, uint32_t b3, uint32_t z0, uint32_t z1) {
      const int a = c * 8;
      const uint32_t a0 = pack_bf16(phi_f(acc[a] * rs0), phi_f(acc[a + 1] * rs0));
      const uint32_t a1 = pack_bf16(phi_f(acc[a + 2] * rs1), phi_f(acc[a + 3] * rs1));
      const uint32_t a2 = pack_bf16(phi_f(acc[a + 4] * rs0), phi_f(acc[a + 5] * rs0));
      const uint32_t a3 = pack_bf16(phi_f(acc[a + 6] * rs1), phi_f(acc[a + 7] * rs1));
      float n0[4] = {0.f, 0.f, 0.f, 0.f}, n1[4] = {0.f, 0.f, 0.f, 0.f}, dn[4] = {0.f, 0.f, 0.f, 0.f};
      mma_16816(n0, a0, a1, a2, a3, b0, b1);
      mma_16816(n1, a0, a1, a2, a3, b2, b3);
      mma_16816(dn, a0, a1, a2, a3, z0, z1);
      const float i0 = __fdividef(1.f, dn[0] + 1e-6f), i1 = __fdividef(1.f, dn[2] + 1e-6f);
      const uint32_t o0 = pack_bf16(n0[0] * i0, n0[1] * i0), o1 = pack_bf16(n0[2] * i1, n0[3] * i1);
      const uint32_t o2 = pack_bf16(n1[0] * i0, n1[1] * i0), o3 = pack_bf16(n1[2] * i1, n1[3] * i1);
      sts_u4(area + slot * 8192 + c * 2048 + t128 * 16, o0, o1, o2, o3);
      send_u4(&g_xbuf[m][p][slot][w][c][t128], o0, o1, o2, o3);
    };
    const uint32_t kvb = area + 5 * 8192;
    const uint32_t kvfrag = kvb + ((lane & 7) + ((lane >> 3) & 1) * 8) * 32 + (lane >> 4) * 16;
    auto signal = [&](int e) {
      __syncwarp();
      if (lane == 0) mbar_arrive(BAR(B_EV + w * 2 + e));
    };

    float accB[32];
#pragma unroll 1
    for (int t = 0; t < 5; t++) {
      float accA[32];
      const uint32_t ph = t & 1;
      const int kindP = t == 0 ? K_NONE : ((odd && t <= 2) ? K_KV : K_GU);
      const int kindC = odd ? (t < 2 ? K_KV : K_GU) : (t < 4 ? K_GU : K_Q);
      const int slotP = odd ? t - 3 : t - 1, xslotP = odd ? t + 3 : t - 1;
      const int slotC = odd ? t - 2 : t, xslotC = odd ? t + 4 : t;
      static_for<8>([&](auto kc) {
        constexpr int k = decltype(kc)::value;
        mbar_wait(BAR(B_FULL + k), ph);
        wgmma_fence();
        static_for<8>([&](auto kkc) {
          constexpr int kk = decltype(kkc)::value;
          constexpr int i = ((k & 3) * 8 + kk) * 4;
          constexpr uint32_t lo = desc_lo(stage_off(k) + kk * 1024, 8192);
          if constexpr (k < 4) wgmma_n64_rs<((k & 3) | kk) != 0, lo, kHi64>(accA, A[i], A[i + 1], A[i + 2], A[i + 3], dbase);
          else wgmma_n64_rs<((k & 3) | kk) != 0, lo, kHi64>(accB, A[i], A[i + 1], A[i + 2], A[i + 3], dbase);
        });
        wgmma_commit();
        if (k > 0) {
          wgmma_wait<1>();
          release(k - 1);
        }
        if constexpr (k < 4) {
          if (kindP == K_GU) {
            if (k == 1 || k == 2) gu_chunk(accB, k - 1, slotP, xslotP, 1);
          } else if (kindP == K_KV) {
            if (k == 1 || k == 2) kv_stage(accB, k - 1, 1);
            if (k == 3) {
              float kvacc[36];
              fence_proxy_async();
              bar_sync(1 + w, 128);
              wgmma_fence();
              static_for<4>([&](auto kkc) {
                constexpr int kk = decltype(kkc)::value;
                wgmma_n72_ss_tt<kk != 0, desc_lo(3 * 8192 + kk * 2048, 0), desc_lo(4 * 8192 + kk * 2048, 8192 - kk * 2048)>(kvacc, dbase + w * 4096);
              });
              wgmma_commit();
              wgmma_wait<0>();
              float c[8];
#pragma unroll
              for (int i = 0; i < 8; i++)
                c[i] = wq == 0 ? kvacc[i] : (wq == 1 ? kvacc[8 + i] : (wq == 2 ? kvacc[16 + i] : kvacc[24 + i]));
              const int head = (2 * p + t - 1) * 4 + wq;
              float* kvp = &g_kv[par][head][0][0];
              red_add_v2(kvp + g * 16 + 2 * tq, c[0], c[1]);
              red_add_v2(kvp + (g + 8) * 16 + 2 * tq, c[2], c[3]);
              red_add_v2(kvp + g * 16 + 8 + 2 * tq, c[4], c[5]);
              red_add_v2(kvp + (g + 8) * 16 + 8 + 2 * tq, c[6], c[7]);
              if (tq == 0) {
                red_add(&g_z[par][head][g], kvacc[32]);
                red_add(&g_z[par][head][g + 8], kvacc[34]);
              }
              signal(t - 1);
            }
          }
        } else {
          constexpr int c = k - 4;
          if (kindC == K_GU) {
            if (c < 2) gu_chunk(accA, c, slotC, xslotC, 0);
          } else if (kindC == K_KV) {
            if (c == 0 && t == 0) sts_u4(area + 5 * 8192 + t128 * 16, 0x3F803F80u, 0x3F803F80u, 0x3F803F80u, 0x3F803F80u);
            if (c < 2) kv_stage(accA, c, 0);
          } else {
            if (c == 0) mbar_wait(BAR(B_KVREADY), 0);
            uint32_t b0, b1, b2, b3;
            ldmatrix_x4_trans(kvfrag + c * 512, b0, b1, b2, b3);
            const uint32_t z0 = lds_u32(kvb + 4096 + c * 32 + tq * 4), z1 = lds_u32(kvb + 4096 + c * 32 + 16 + tq * 4);
            q_head(accA, c, 4, b0, b1, b2, b3, z0, z1);
          }
        }
      });
      wgmma_wait<0>();
      release(7);
      PROF(w, 1 + 2 * t);
    }
    if (odd) {
      gu_chunk(accB, 0, 2, 8, 1);
      gu_chunk(accB, 1, 2, 8, 1);
    } else {
      uint32_t Bf[4][6];
#pragma unroll
      for (int c = 0; c < 4; c++) {
        ldmatrix_x4_trans(kvfrag + (4 + c) * 512, Bf[c][0], Bf[c][1], Bf[c][2], Bf[c][3]);
        Bf[c][4] = lds_u32(kvb + 4096 + (4 + c) * 32 + tq * 4);
        Bf[c][5] = lds_u32(kvb + 4096 + (4 + c) * 32 + 16 + tq * 4);
      }
      bar_sync(1 + w, 128);
#pragma unroll
      for (int c = 0; c < 4; c++) q_head(accB, c, 5, Bf[c][0], Bf[c][1], Bf[c][2], Bf[c][3], Bf[c][4], Bf[c][5]);
    }
    PROF(w, 10);

    const int n_own = odd ? 3 : 6;
    auto load_a = [&](int kb) {
      if (kb < n_own) {
#pragma unroll
        for (int jj = 0; jj < 4; jj++) {
          const int i = (kb * 4 + jj) * 4;
          lds_u4(area + kb * 8192 + jj * 2048 + t128 * 16, A[i], A[i + 1], A[i + 2], A[i + 3]);
        }
      } else {
        const int xs = odd ? kb - 3 : kb;
#pragma unroll
        for (int jj = 0; jj < 4; jj++) {
          const int i = (kb * 4 + jj) * 4;
          ldg_poll_u4(&g_xbuf[m][p][xs][w][jj][t128], A[i], A[i + 1], A[i + 2], A[i + 3]);
        }
      }
    };
    auto fix_a = [&](int kb) {
      if (kb >= n_own) {
        const int xs = odd ? kb - 3 : kb;
#pragma unroll
        for (int jj = 0; jj < 4; jj++) {
          const int i = (kb * 4 + jj) * 4;
          recv_u4(&g_xbuf[m][p][xs][w][jj][t128], A[i], A[i + 1], A[i + 2], A[i + 3]);
        }
      }
    };
#pragma unroll
    for (int kb = 0; kb < 7; kb++) load_a(kb);
    PROF(w, 11);

    const int orow = m * 128 + w * 64 + wq * 16 + g;
    const int ocol = odd * 256 + p * 64 + 2 * tq;
    float acc2[2][32];
    uint32_t P[3][32];
    uint32_t xr[16];
    auto send = [&](float (&acc)[32], int bi) {
      uint4* dst = &g_pbuf[m][odd][(p + 1 + bi) & 3][bi][w][0][t128];
#pragma unroll
      for (int q = 0; q < 8; q++)
        send_u4(dst + q * 128, __float_as_uint(acc[q * 4]), __float_as_uint(acc[q * 4 + 1]), __float_as_uint(acc[q * 4 + 2]), __float_as_uint(acc[q * 4 + 3]));
      PROF(w, 12 + 2 * bi);
    };
    auto fetch = [&](int sl) {
#pragma unroll
      for (int q = 0; q < 8; q++) ldg_poll_u4(&g_pbuf[m][odd][p][sl][w][q][t128], P[sl][q * 4], P[sl][q * 4 + 1], P[sl][q * 4 + 2], P[sl][q * 4 + 3]);
    };
    static_for<36>([&](auto ic) {
      constexpr int i = decltype(ic)::value, bi = p2_bi(i), kb = p2_kb(i), j = i >> 1, st = j & 7;
      if (i == 9) { load_a(7); load_a(8); }
      if (bi == 0 && kb >= 3) fix_a(kb);
      if ((i & 1) == 0) mbar_wait(BAR(B_FULL + st), (5 + (j >> 3)) & 1);
      wgmma_fence();
      static_for<4>([&](auto kkc) {
        constexpr int kk = decltype(kkc)::value, a = (kb * 4 + kk) * 4;
        wgmma_n64_rs<(kb | kk) != 0, desc_lo(stage_off(st) + (i & 1) * 8192 + kk * 2048, 0), kHi128>(acc2[bi & 1], A[a], A[a + 1], A[a + 2], A[a + 3], dbase);
      });
      wgmma_commit();
      if (i > 0) {
        wgmma_wait<1>();
        if ((i & 1) == 0 && j - 1 <= 9) release((j - 1) & 7);
      }
      if constexpr (i == 16) send(acc2[0], 0);
      if constexpr (i == 18) send(acc2[1], 1);
      if constexpr (i == 27) send(acc2[0], 2);
      if constexpr (i == 29) fetch(0);
      if constexpr (i == 31) fetch(1);
      if constexpr (i == 32) {
#pragma unroll
        for (int q = 0; q < 8; q++) {
          xr[2 * q] = __ldg((const uint32_t*)(x + (size_t)orow * kD + ocol + q * 8));
          xr[2 * q + 1] = __ldg((const uint32_t*)(x + (size_t)(orow + 8) * kD + ocol + q * 8));
        }
      }
      if constexpr (i == 34) fetch(2);
    });
#pragma unroll
    for (int sl = 0; sl < 3; sl++)
#pragma unroll
      for (int q = 0; q < 8; q++) recv_u4(&g_pbuf[m][odd][p][sl][w][q][t128], P[sl][q * 4], P[sl][q * 4 + 1], P[sl][q * 4 + 2], P[sl][q * 4 + 3]);
    wgmma_wait<0>();
    PROF(w, 18);
#pragma unroll
    for (int q = 0; q < 8; q++) {
      float rr[4];
#pragma unroll
      for (int e = 0; e < 4; e++)
        rr[e] = acc2[1][q * 4 + e] + __uint_as_float(P[0][q * 4 + e]) + __uint_as_float(P[1][q * 4 + e]) + __uint_as_float(P[2][q * 4 + e]);
      rr[0] += __uint_as_float(xr[2 * q] << 16);
      rr[1] += __uint_as_float(xr[2 * q] & 0xffff0000u);
      rr[2] += __uint_as_float(xr[2 * q + 1] << 16);
      rr[3] += __uint_as_float(xr[2 * q + 1] & 0xffff0000u);
      *(uint32_t*)(out + (size_t)orow * kD + ocol + q * 8) = pack_bf16(rr[0], rr[1]);
      *(uint32_t*)(out + (size_t)(orow + 8) * kD + ocol + q * 8) = pack_bf16(rr[2], rr[3]);
    }
    PROF(w, 19);
    if (tid == 0) {
      const uint32_t old = atomicAdd(&g_done, 1u);
      if ((old & 127u) == 127u) *(volatile uint32_t*)&g_epoch = epoch + 1u;
    }
  }
#undef BAR
}

typedef CUresult (*EncodeFn)(CUtensorMap*, CUtensorMapDataType, cuuint32_t, void*, const cuuint64_t*, const cuuint64_t*,
                             const cuuint32_t*, const cuuint32_t*, CUtensorMapInterleave, CUtensorMapSwizzle,
                             CUtensorMapL2promotion, CUtensorMapFloatOOBfill);

void make_map(EncodeFn enc, CUtensorMap* tm, const void* ptr, int rows, int cols, bool narrow) {
  cuuint64_t gd[2] = {(cuuint64_t)cols, (cuuint64_t)rows};
  cuuint64_t gs[1] = {(cuuint64_t)cols * 2};
  cuuint32_t bd[2] = {narrow ? 32u : 64u, narrow ? 128u : 64u};
  cuuint32_t es[2] = {1, 1};
  enc(tm, CU_TENSOR_MAP_DATA_TYPE_BFLOAT16, 2, const_cast<void*>(ptr), gd, gs, bd, es, CU_TENSOR_MAP_INTERLEAVE_NONE,
      narrow ? CU_TENSOR_MAP_SWIZZLE_64B : CU_TENSOR_MAP_SWIZZLE_128B, CU_TENSOR_MAP_L2_PROMOTION_L2_256B, CU_TENSOR_MAP_FLOAT_OOB_FILL_NONE);
}

}

extern "C" void kernel_launch(void* const* d_in, const int* in_sizes, int n_in, void* d_out, int out_size) {
  static EncodeFn enc = nullptr;
  if (!enc) {
    void* fn = nullptr;
    cudaDriverEntryPointQueryResult qr;
    cudaGetDriverEntryPoint("cuTensorMapEncodeTiled", &fn, cudaEnableDefault, &qr);
    enc = (EncodeFn)fn;
    cudaFuncSetAttribute(fused_kernel, cudaFuncAttributeMaxDynamicSharedMemorySize, kSmemBytes);
  }
  CUtensorMap tm_x, tm_wqkv, tm_w1, tm_w3, tm_w2, tm_wo;
  make_map(enc, &tm_x, d_in[0], kS, kD, false);
  make_map(enc, &tm_wqkv, d_in[1], kD, 3 * kD, true);
  make_map(enc, &tm_wo, d_in[2], kD, kD, false);
  make_map(enc, &tm_w1, d_in[4], kD, kF, true);
  make_map(enc, &tm_w3, d_in[5], kD, kF, true);
  make_map(enc, &tm_w2, d_in[6], kF, kD, false);
  fused_kernel<<<128, 384, kSmemBytes>>>(tm_x, tm_wqkv, tm_w1, tm_w3, tm_w2, tm_wo, (const __nv_bfloat16*)d_in[0],
                                         (__nv_bfloat16*)d_out);
}
```

```cpp
#include <cuda_runtime.h>
#include <cuda_bf16.h>
#include <cuda.h>
#include <stdint.h>

namespace {

constexpr int kS = 2048, kD = 512, kF = 1792;
constexpr uint32_t kSpinLimit = 1u << 22;

__device__ uint4    g_xbuf[16][4][9][2][4][128];
__device__ uint4    g_pbuf[16][2][4][3][2][8][128];
__device__ float    g_kv[2][32][16][16];
__device__ float    g_z[2][32][16];
__device__ uint32_t g_kvcnt[4][32];
__device__ uint32_t g_epoch;
__device__ uint32_t g_done;
#define PROF(wg, i) do {} while (0)

__device__ __forceinline__ uint32_t smem_u32(const void* p) { return (uint32_t)__cvta_generic_to_shared(p); }
__device__ __forceinline__ void mbar_init(uint32_t bar, uint32_t cnt) {
  asm volatile("mbarrier.init.shared::cta.b64 [%0], %1;" ::"r"(bar), "r"(cnt) : "memory");
}
__device__ __forceinline__ void mbar_expect_tx(uint32_t bar, uint32_t bytes) {
  asm volatile("mbarrier.arrive.expect_tx.shared::cta.b64 _, [%0], %1;" ::"r"(bar), "r"(bytes) : "memory");
}
__device__ __forceinline__ void mbar_arrive(uint32_t bar) {
  asm volatile("mbarrier.arrive.shared::cta.b64 _, [%0];" ::"r"(bar) : "memory");
}
__device__ __forceinline__ void mbar_wait(uint32_t bar, uint32_t parity) {
  asm volatile(
      "{\n.reg .pred p;\n"
      "LAB_WAIT:\n"
      "mbarrier.try_wait.parity.shared::cta.b64 p, [%0], %1;\n"
      "@p bra DONE;\n"
      "bra LAB_WAIT;\n"
      "DONE:\n}" ::"r"(bar), "r"(parity) : "memory");
}
__device__ __forceinline__ void tma_load_2d(uint32_t dst, const CUtensorMap* tm, uint32_t bar, int c0, int c1) {
  asm volatile(
      "cp.async.bulk.tensor.2d.shared::cluster.global.mbarrier::complete_tx::bytes [%0], [%1, {%3, %4}], [%2];" ::"r"(dst),
      "l"(tm), "r"(bar), "r"(c0), "r"(c1)
      : "memory");
}
__device__ __forceinline__ void tma_load_2d_mc(uint32_t dst, const CUtensorMap* tm, uint32_t bar, int c0, int c1) {
  asm volatile(
      "cp.async.bulk.tensor.2d.shared::cluster.global.mbarrier::complete_tx::bytes.multicast::cluster [%0], [%1, {%3, %4}], [%2], %5;" ::"r"(dst),
      "l"(tm), "r"(bar), "r"(c0), "r"(c1), "h"((uint16_t)3)
      : "memory");
}
__device__ __forceinline__ void mbar_arrive_cluster(uint32_t bar, uint32_t cta) {
  asm volatile("{\n.reg .b32 ra;\nmapa.shared::cluster.u32 ra, %0, %1;\nmbarrier.arrive.shared::cluster.b64 _, [ra];\n}" ::"r"(bar), "r"(cta) : "memory");
}
__device__ __forceinline__ void prefetch_tmap(const CUtensorMap* tm) {
  asm volatile("prefetch.tensormap [%0];" ::"l"(tm) : "memory");
}
__device__ __forceinline__ void wgmma_fence() { asm volatile("wgmma.fence.sync.aligned;" ::: "memory"); }
__device__ __forceinline__ void wgmma_commit() { asm volatile("wgmma.commit_group.sync.aligned;" ::: "memory"); }
template <int N>
__device__ __forceinline__ void wgmma_wait() { asm volatile("wgmma.wait_group.sync.aligned %0;" ::"n"(N) : "memory"); }
__device__ __forceinline__ void bar_sync(int id, int n) { asm volatile("bar.sync %0, %1;" ::"r"(id), "r"(n) : "memory"); }
__device__ __forceinline__ void bar_arrive(int id, int n) { asm volatile("bar.arrive %0, %1;" ::"r"(id), "r"(n) : "memory"); }
__device__ __forceinline__ void fence_proxy_async() { asm volatile("fence.proxy.async.shared::cta;" ::: "memory"); }

__device__ __forceinline__ uint32_t ld_acquire(const uint32_t* p) {
  uint32_t v;
  asm volatile("ld.acquire.gpu.global.u32 %0, [%1];" : "=r"(v) : "l"(p) : "memory");
  return v;
}
__device__ __forceinline__ uint32_t ld_relaxed(const uint32_t* p) {
  uint32_t v;
  asm volatile("ld.relaxed.gpu.global.u32 %0, [%1];" : "=r"(v) : "l"(p));
  return v;
}
__device__ __forceinline__ void cluster_wait() { asm volatile("barrier.cluster.wait.aligned;" ::: "memory"); }
__device__ __forceinline__ void st_relaxed(uint32_t* p, uint32_t v) {
  asm volatile("st.relaxed.gpu.global.u32 [%0], %1;" ::"l"(p), "r"(v) : "memory");
}
__device__ __forceinline__ void wait_flag_eq(const uint32_t* p, uint32_t val) {
  uint32_t it = 0;
  while (ld_acquire(p) != val) {
    if (++it > kSpinLimit) break;
  }
}
__device__ __forceinline__ void wait_count_ge(const uint32_t* p, uint32_t val) {
  uint32_t it = 0;
  while ((int32_t)(ld_acquire(p) - val) < 0) {
    __nanosleep(64);
    if (++it > kSpinLimit) break;
  }
}
__device__ __forceinline__ void ldg_poll_u4(const void* p, uint32_t& a, uint32_t& b, uint32_t& c, uint32_t& d) {
  asm volatile("ld.relaxed.gpu.global.v4.u32 {%0,%1,%2,%3}, [%4];" : "=r"(a), "=r"(b), "=r"(c), "=r"(d) : "l"(p) : "memory");
}
__device__ __forceinline__ void recv_u4(void* p, uint32_t& a, uint32_t& b, uint32_t& c, uint32_t& d) {
  uint32_t it = 0;
  while (__any_sync(0xffffffffu, min(min(a, b), min(c, d)) == 0u) && ++it < kSpinLimit) ldg_poll_u4(p, a, b, c, d);
  a = ~a; b = ~b; c = ~c; d = ~d;
  asm volatile("st.global.v4.u32 [%0], {%1,%1,%1,%1};" ::"l"(p), "r"(0u) : "memory");
}
__device__ __forceinline__ void send_u4(void* p, uint32_t a, uint32_t b, uint32_t c, uint32_t d) {
  asm volatile("st.relaxed.gpu.global.v4.u32 [%0], {%1,%2,%3,%4};" ::"l"(p), "r"(~a), "r"(~b), "r"(~c), "r"(~d) : "memory");
}
__device__ __forceinline__ float4 ldg_cg_f4(const void* p) {
  float4 v;
  asm volatile("ld.global.cg.v4.f32 {%0,%1,%2,%3}, [%4];" : "=f"(v.x), "=f"(v.y), "=f"(v.z), "=f"(v.w) : "l"(p) : "memory");
  return v;
}
__device__ __forceinline__ void stg_u4(void* p, uint32_t a, uint32_t b, uint32_t c, uint32_t d) {
  asm volatile("st.global.v4.u32 [%0], {%1,%2,%3,%4};" ::"l"(p), "r"(a), "r"(b), "r"(c), "r"(d) : "memory");
}
__device__ __forceinline__ void stg_f4(void* p, float a, float b, float c, float d) {
  asm volatile("st.global.v4.f32 [%0], {%1,%2,%3,%4};" ::"l"(p), "f"(a), "f"(b), "f"(c), "f"(d) : "memory");
}
__device__ __forceinline__ void sts_u4(uint32_t addr, uint32_t a, uint32_t b, uint32_t c, uint32_t d) {
  asm volatile("st.shared.v4.u32 [%0], {%1,%2,%3,%4};" ::"r"(addr), "r"(a), "r"(b), "r"(c), "r"(d) : "memory");
}
__device__ __forceinline__ void lds_u4(uint32_t addr, uint32_t& a, uint32_t& b, uint32_t& c, uint32_t& d) {
  asm volatile("ld.shared.v4.u32 {%0,%1,%2,%3}, [%4];" : "=r"(a), "=r"(b), "=r"(c), "=r"(d) : "r"(addr) : "memory");
}
__device__ __forceinline__ uint32_t lds_u32(uint32_t addr) {
  uint32_t v;
  asm volatile("ld.shared.u32 %0, [%1];" : "=r"(v) : "r"(addr) : "memory");
  return v;
}
__device__ __forceinline__ void ldmatrix_x4(uint32_t addr, uint32_t& a, uint32_t& b, uint32_t& c, uint32_t& d) {
  asm volatile("ldmatrix.sync.aligned.m8n8.x4.shared.b16 {%0,%1,%2,%3}, [%4];" : "=r"(a), "=r"(b), "=r"(c), "=r"(d) : "r"(addr) : "memory");
}
__device__ __forceinline__ void ldmatrix_x4_trans(uint32_t addr, uint32_t& a, uint32_t& b, uint32_t& c, uint32_t& d) {
  asm volatile("ldmatrix.sync.aligned.m8n8.x4.trans.shared.b16 {%0,%1,%2,%3}, [%4];" : "=r"(a), "=r"(b), "=r"(c), "=r"(d) : "r"(addr) : "memory");
}
__device__ __forceinline__ void stmatrix_x4(uint32_t addr, uint32_t a, uint32_t b, uint32_t c, uint32_t d) {
  asm volatile("stmatrix.sync.aligned.m8n8.x4.shared.b16 [%0], {%1,%2,%3,%4};" ::"r"(addr), "r"(a), "r"(b), "r"(c), "r"(d) : "memory");
}
__device__ __forceinline__ void mma_16816(float (&c)[4], uint32_t a0, uint32_t a1, uint32_t a2, uint32_t a3, uint32_t b0, uint32_t b1) {
  asm volatile(
      "mma.sync.aligned.m16n8k16.row.col.f32.bf16.bf16.f32 {%0,%1,%2,%3}, {%4,%5,%6,%7}, {%8,%9}, {%0,%1,%2,%3};"
      : "+f"(c[0]), "+f"(c[1]), "+f"(c[2]), "+f"(c[3])
      : "r"(a0), "r"(a1), "r"(a2), "r"(a3), "r"(b0), "r"(b1));
}
__device__ __forceinline__ uint32_t pack_bf16(float lo, float hi) {
  uint32_t r;
  asm("cvt.rn.bf16x2.f32 %0, %1, %2;" : "=r"(r) : "f"(hi), "f"(lo));
  return r;
}
__device__ __forceinline__ uint32_t hsub2_bf16(uint32_t a, uint32_t b) {
  uint32_t r;
  asm("sub.rn.bf16x2 %0, %1, %2;" : "=r"(r) : "r"(a), "r"(b));
  return r;
}
__device__ __forceinline__ float ex2f(float x) {
  float r;
  asm("ex2.approx.ftz.f32 %0, %1;" : "=f"(r) : "f"(x));
  return r;
}
__device__ __forceinline__ float rcpf(float x) {
  float r;
  asm("rcp.approx.ftz.f32 %0, %1;" : "=f"(r) : "f"(x));
  return r;
}
__device__ __forceinline__ void red_add_v2(float* p, float a, float b) {
  asm volatile("red.relaxed.gpu.global.add.v2.f32 [%0], {%1,%2};" ::"l"(p), "f"(a), "f"(b) : "memory");
}
__device__ __forceinline__ void red_add(float* p, float a) {
  asm volatile("red.relaxed.gpu.global.add.f32 [%0], %1;" ::"l"(p), "f"(a) : "memory");
}
__device__ __forceinline__ float phi_f(float t) {
  float e = ex2f(t * 1.4426950408889634f);
  return (t > 0.f ? t + 1.f : e) + 1e-6f;
}

#define R8(a, o) "+f"(a[o + 0]), "+f"(a[o + 1]), "+f"(a[o + 2]), "+f"(a[o + 3]), "+f"(a[o + 4]), "+f"(a[o + 5]), "+f"(a[o + 6]), "+f"(a[o + 7])

#define W8(a, o) "=f"(a[o + 0]), "=f"(a[o + 1]), "=f"(a[o + 2]), "=f"(a[o + 3]), "=f"(a[o + 4]), "=f"(a[o + 5]), "=f"(a[o + 6]), "=f"(a[o + 7])
#define D32 "{%0,%1,%2,%3,%4,%5,%6,%7,%8,%9,%10,%11,%12,%13,%14,%15,%16,%17,%18,%19,%20,%21,%22,%23,%24,%25,%26,%27,%28,%29,%30,%31}"
#define D36 "{%0,%1,%2,%3,%4,%5,%6,%7,%8,%9,%10,%11,%12,%13,%14,%15,%16,%17,%18,%19,%20,%21,%22,%23,%24,%25,%26,%27,%28,%29,%30,%31,%32,%33,%34,%35}"

constexpr uint32_t kHi128 = (1024u >> 4) | (1u << 30);
constexpr uint32_t kHi64 = (512u >> 4) | (2u << 30);
__host__ __device__ constexpr uint32_t desc_lo(uint32_t off, uint32_t lbo) { return (off >> 4) | ((lbo >> 4) << 16); }

template <bool ACC, uint32_t LO, uint32_t HI>
__device__ __forceinline__ void wgmma_n64_rs(float (&d)[32], uint32_t a0, uint32_t a1, uint32_t a2, uint32_t a3, uint32_t base) {
  if (ACC) {
    asm volatile(
        "{\n.reg .pred p;\n.reg .b32 lo;\n.reg .b64 dd;\nsetp.eq.b32 p, 0, 0;\nadd.u32 lo, %36, %37;\nmov.b64 dd, {lo, %38};\n"
        "wgmma.mma_async.sync.aligned.m64n64k16.f32.bf16.bf16 " D32 ", {%32,%33,%34,%35}, dd, p, 1, 1, 1;\n}"
        : R8(d, 0), R8(d, 8), R8(d, 16), R8(d, 24)
        : "r"(a0), "r"(a1), "r"(a2), "r"(a3), "r"(base), "n"(LO), "n"(HI));
  } else {
    asm volatile(
        "{\n.reg .pred p;\n.reg .b32 lo;\n.reg .b64 dd;\nsetp.ne.b32 p, 0, 0;\nadd.u32 lo, %36, %37;\nmov.b64 dd, {lo, %38};\n"
        "wgmma.mma_async.sync.aligned.m64n64k16.f32.bf16.bf16 " D32 ", {%32,%33,%34,%35}, dd, p, 1, 1, 1;\n}"
        : W8(d, 0), W8(d, 8), W8(d, 16), W8(d, 24)
        : "r"(a0), "r"(a1), "r"(a2), "r"(a3), "r"(base), "n"(LO), "n"(HI));
  }
}
template <bool ACC, uint32_t LOA, uint32_t LOB>
__device__ __forceinline__ void wgmma_n72_ss_tt(float (&d)[36], uint32_t base) {
  if (ACC) {
    asm volatile(
        "{\n.reg .pred p;\n.reg .b32 lo;\n.reg .b64 da, db;\nsetp.eq.b32 p, 0, 0;\n"
        "add.u32 lo, %36, %37;\nmov.b64 da, {lo, %39};\nadd.u32 lo, %36, %38;\nmov.b64 db, {lo, %39};\n"
        "wgmma.mma_async.sync.aligned.m64n72k16.f32.bf16.bf16 " D36 ", da, db, p, 1, 1, 1, 1;\n}"
        : R8(d, 0), R8(d, 8), R8(d, 16), R8(d, 24), "+f"(d[32]), "+f"(d[33]), "+f"(d[34]), "+f"(d[35])
        : "r"(base), "n"(LOA), "n"(LOB), "n"(kHi128));
  } else {
    asm volatile(
        "{\n.reg .pred p;\n.reg .b32 lo;\n.reg .b64 da, db;\nsetp.ne.b32 p, 0, 0;\n"
        "add.u32 lo, %36, %37;\nmov.b64 da, {lo, %39};\nadd.u32 lo, %36, %38;\nmov.b64 db, {lo, %39};\n"
        "wgmma.mma_async.sync.aligned.m64n72k16.f32.bf16.bf16 " D36 ", da, db, p, 1, 1, 1, 1;\n}"
        : W8(d, 0), W8(d, 8), W8(d, 16), W8(d, 24), "=f"(d[32]), "=f"(d[33]), "=f"(d[34]), "=f"(d[35])
        : "r"(base), "n"(LOA), "n"(LOB), "n"(kHi128));
  }
}

template <int V> struct IC { static constexpr int value = V; };
template <int N, int I = 0, typename F>
__device__ __forceinline__ void static_for(F&& f) {
  if constexpr (I < N) { f(IC<I>{}); static_for<N, I + 1>(f); }
}

__host__ __device__ constexpr uint32_t stage_off(int st) {
  return st < 6 ? 131072u + (uint32_t)st * 16384u : (uint32_t)(st - 6) * 65536u + 49152u;
}

constexpr int B_FULL = 0, B_EMPTY = 8, B_XFULL = 16, B_XDONE = 32, B_KVREADY = 33, B_EV = 34, B_COUNT = 38;
constexpr uint32_t kBarOff = 229376;
constexpr int kSmemBytes = 229376 + 1024;

__host__ __device__ constexpr int p2_bi(int i) { return i < 7 ? 0 : i < 14 ? 1 : i < 16 ? 0 : i < 18 ? 1 : i / 9; }
__host__ __device__ constexpr int p2_kb(int i) { return i < 7 ? i : i < 14 ? i - 7 : i < 16 ? i - 7 : i < 18 ? i - 9 : i % 9; }

enum { K_NONE = 0, K_GU = 1, K_KV = 2, K_Q = 3 };

__global__ void __cluster_dims__(2, 1, 1) __launch_bounds__(384, 1)
fused_kernel(const __grid_constant__ CUtensorMap tm_x, const __grid_constant__ CUtensorMap tm_wqkv,
             const __grid_constant__ CUtensorMap tm_w1, const __grid_constant__ CUtensorMap tm_w3,
             const __grid_constant__ CUtensorMap tm_w2, const __grid_constant__ CUtensorMap tm_wo,
             const __nv_bfloat16* __restrict__ x, __nv_bfloat16* __restrict__ out) {
  extern __shared__ __align__(1024) uint8_t smem_raw[];
  const uint32_t sbase = __shfl_sync(0xffffffffu, smem_u32(smem_raw), 0);
  const uint32_t bars = sbase + kBarOff;
  const int tid = threadIdx.x, lane = tid & 31;
  const int warp = __shfl_sync(0xffffffffu, tid >> 5, 0);
  const int cr = blockIdx.x & 1;
  const int r = (blockIdx.x >> 1) & 7, m = ((blockIdx.x >> 4) << 1) | cr, p = r >> 1, odd = r & 1;
#define BAR(i) (bars + 8u * (uint32_t)(i))
  if (tid == 256) {
    if (sbase & 1023u) __trap();
#pragma unroll
    for (int i = 0; i < 16; i++) mbar_init(BAR(B_XFULL + i), 1);
    fence_proxy_async();
#pragma unroll
    for (int b = 0; b < 16; b++) {
      mbar_expect_tx(BAR(B_XFULL + b), 8192);
      tma_load_2d(sbase + (b >> 3) * 65536 + (b & 7) * 8192, &tm_x, BAR(B_XFULL + b), (b & 7) * 64, m * 128 + (b >> 3) * 64);
    }
#pragma unroll
    for (int i = 0; i < 8; i++) { mbar_init(BAR(B_FULL + i), 1); mbar_init(BAR(B_EMPTY + i), 4); }
#pragma unroll
    for (int i = 0; i < 4; i++) mbar_init(BAR(B_EV + i), 4);
    mbar_init(BAR(B_XDONE), 2);
    mbar_init(BAR(B_KVREADY), 1);
    asm volatile("fence.mbarrier_init.release.cluster;" ::: "memory");
    fence_proxy_async();
  } else if (tid == 288) {
    prefetch_tmap(odd ? &tm_wqkv : (cr ? &tm_w3 : &tm_w1));
  }
  __syncwarp();
  asm volatile("barrier.cluster.arrive.relaxed.aligned;" ::: "memory");
  PROF((tid >> 7), 21);
  __syncthreads();

  if (warp >= 8) {
    asm volatile("setmaxnreg.dec.sync.aligned.u32 24;");
    PROF(2, 3);
    cluster_wait();
    PROF(2, 2);
    const uint32_t epoch = warp == 8 ? 0u : ld_relaxed(&g_epoch);
    const uint32_t tag = epoch + 1u;
    const int par = epoch & 1;
    if (warp == 8) {
      if (lane == 0) {
        for (int j = 0; j < 10; j++) {
          const CUtensorMap* tm;
          int col;
          if (!odd) {
            if (j < 8) { tm = cr ? &tm_w3 : &tm_w1; col = 7 * p * 64 + j * 32; }
            else { tm = &tm_wqkv; col = 128 * p + (j - 8) * 64 + cr * 32; }
          } else {
            if (j < 4) { tm = &tm_wqkv; col = 512 + cr * 512 + 128 * p + j * 32; }
            else { tm = cr ? &tm_w3 : &tm_w1; col = (7 * p + 4) * 64 + (j - 4) * 32; }
          }
          const int t = j >> 1;
          for (int kq = 0; kq < 4; kq++) {
            const int k = (j & 1) * 4 + kq;
            mbar_wait(BAR(B_EMPTY + k), k < 6 ? ((t & 1) ^ 1) : (t & 1));
            mbar_expect_tx(BAR(B_FULL + k), 16384);
            tma_load_2d_mc(sbase + stage_off(k) + cr * 8192, tm, BAR(B_FULL + k), col, kq * 128);
          }
        }
        for (int j = 0; j < 18; j++) {
          const int st = j & 7, n = 5 + (j >> 3);
          const int i = 2 * j + cr;
          const int bi = p2_bi(i), kb = p2_kb(i);
          const int col = odd * 256 + ((p + 1 + bi) & 3) * 64;
          const CUtensorMap* tmk;
          int row;
          if (!odd) {
            if (kb < 4) { tmk = &tm_w2; row = (7 * p + kb) * 64; }
            else if (kb < 6) { tmk = &tm_wo; row = (2 * p + kb - 4) * 64; }
            else { tmk = &tm_w2; row = (7 * p + 4 + kb - 6) * 64; }
          } else {
            if (kb < 3) { tmk = &tm_w2; row = (7 * p + 4 + kb) * 64; }
            else if (kb < 7) { tmk = &tm_w2; row = (7 * p + kb - 3) * 64; }
            else { tmk = &tm_wo; row = (2 * p + kb - 7) * 64; }
          }
          mbar_wait(BAR(B_EMPTY + st), st < 6 ? ((n & 1) ^ 1) : (n & 1));
          mbar_expect_tx(BAR(B_FULL + st), 16384);
          tma_load_2d_mc(sbase + stage_off(st) + cr * 8192, tmk, BAR(B_FULL + st), col, row);
        }
      }
    } else if (warp <= 10) {
      if (lane == 0 && odd) {
        const int w = warp - 9;
        for (int e = 0; e < 2; e++) {
          mbar_wait(BAR(B_EV + w * 2 + e), 0);
          __threadfence();
          atomicAdd(&g_kvcnt[p][0], 1u);
        }
      }
    } else {
      if (!odd) {
        {
          const int ce = m * 4 + p;
          float* kvn = &g_kv[par ^ 1][0][0][0];
          for (int i = lane; i < 128; i += 32) kvn[ce * 128 + i] = 0.f;
          if (lane < 8) (&g_z[par ^ 1][0][0])[ce * 8 + lane] = 0.f;
        }
        mbar_wait(BAR(B_XDONE), 0);
        wait_count_ge(&g_kvcnt[p][0], 64u * tag);
        const float* kvp = &g_kv[par][8 * p][0][0];
        const uint32_t dst0 = sbase + 5 * 8192, dst1 = dst0 + 65536;
#pragma unroll 4
        for (int i = 0; i < 16; i++) {
          float4 v = ldg_cg_f4(kvp + (i * 32 + lane) * 4);
          uint32_t lo = pack_bf16(v.x, v.y), hi = pack_bf16(v.z, v.w);
          uint32_t off = (uint32_t)(i * 32 + lane) * 8u;
          asm volatile("st.shared.v2.u32 [%0], {%1,%2};" ::"r"(dst0 + off), "r"(lo), "r"(hi) : "memory");
          asm volatile("st.shared.v2.u32 [%0], {%1,%2};" ::"r"(dst1 + off), "r"(lo), "r"(hi) : "memory");
        }
        {
          float4 v = ldg_cg_f4(&g_z[par][8 * p][0] + lane * 4);
          uint32_t lo = pack_bf16(v.x, v.y), hi = pack_bf16(v.z, v.w);
          uint32_t off = 4096u + (uint32_t)lane * 8u;
          asm volatile("st.shared.v2.u32 [%0], {%1,%2};" ::"r"(dst0 + off), "r"(lo), "r"(hi) : "memory");
          asm volatile("st.shared.v2.u32 [%0], {%1,%2};" ::"r"(dst1 + off), "r"(lo), "r"(hi) : "memory");
        }
        __syncwarp();
        if (lane == 0) mbar_arrive(BAR(B_KVREADY));
      }
    }
  } else {
    asm volatile("setmaxnreg.inc.sync.aligned.u32 240;");
    const int w = warp >> 2, wq = warp & 3, t128 = tid & 127;
    const int g = lane >> 2, tq = lane & 3;
    const uint32_t area = sbase + (uint32_t)w * 65536u;
    const bool elect = (t128 == 0);
    PROF(w, 22);
    const uint32_t dbase = (sbase & 0x3FFFFu) >> 4;
    uint32_t A[144];
    float rs0, rs1;
    auto release = [&](int st) {
      if (elect) { mbar_arrive_cluster(BAR(B_EMPTY + st), 0); mbar_arrive_cluster(BAR(B_EMPTY + st), 1); }
    };

    {
      const int row = wq * 16 + (lane & 7) + ((lane >> 3) & 1) * 8;
      const uint32_t rbase = area + row * 128;
      float s0[2][4] = {}, q0[2][4] = {}, q1[2][4] = {};
      const uint32_t ones = 0x3F803F80u;
#pragma unroll
      for (int b = 0; b < 8; b++) {
        mbar_wait(BAR(B_XFULL + w * 8 + b), 0);
        if (b == 0) PROF(w, 23);
        if (b == 7) PROF(w, 24);
#pragma unroll
        for (int kk = 0; kk < 4; kk++) {
          const int i = (b * 4 + kk) * 4;
          ldmatrix_x4(rbase + b * 8192 + (((kk * 2 + (lane >> 4)) ^ (row & 7)) << 4), A[i], A[i + 1], A[i + 2], A[i + 3]);
        }
#pragma unroll
        for (int kk = 0; kk < 4; kk++) {
          const int i = (b * 4 + kk) * 4;
          mma_16816(s0[kk & 1], A[i], A[i + 1], A[i + 2], A[i + 3], ones, ones);
          mma_16816(q0[kk & 1], A[i], A[i + 1], A[i + 2], A[i + 3], A[i], A[i + 2]);
          mma_16816(q1[kk & 1], A[i], A[i + 1], A[i + 2], A[i + 3], A[i + 1], A[i + 3]);
        }
      }
      const float mean0 = (s0[0][0] + s0[1][0]) * (1.f / 512.f), mean1 = (s0[0][2] + s0[1][2]) * (1.f / 512.f);
      const uint32_t m0 = pack_bf16(mean0, mean0), m1 = pack_bf16(mean1, mean1);
#pragma unroll
      for (int i = 0; i < 128; i += 2) {
        A[i] = hsub2_bf16(A[i], m0);
        A[i + 1] = hsub2_bf16(A[i + 1], m1);
      }
      float v0 = (g & 1) ? q0[0][1] + q0[1][1] : q0[0][0] + q0[1][0];
      float v1 = (g & 1) ? q1[0][3] + q1[1][3] : q1[0][2] + q1[1][2];
      const int src = 4 * g + (g >> 1);
      v0 = __shfl_sync(0xffffffffu, v0, src);
      v1 = __shfl_sync(0xffffffffu, v1, src);
      v0 = fmaxf(v0 * (1.f / 512.f) - mean0 * mean0, 0.f);
      v1 = fmaxf(v1 * (1.f / 512.f) - mean1 * mean1, 0.f);
      rs0 = rsqrtf(v0 + 1e-5f);
      rs1 = rsqrtf(v1 + 1e-5f);
      bar_sync(1 + w, 128);
      cluster_wait();
      PROF(w, 0);
      release(6); release(7);
      if (elect) mbar_arrive(BAR(B_XDONE));
    }

    auto gu_chunk = [&](float (&acc)[32], int f, int slot, int xslot, int hb) {
      const float c0 = rs0 * -1.4426950408889634f, c1 = rs1 * -1.4426950408889634f;
      const float q0 = rs0 * rs0, q1 = rs1 * rs1;
      uint32_t h[4];
#pragma unroll
      for (int i = 0; i < 4; i++) {
        const float ga = acc[f * 8 + 2 * i], gb = acc[f * 8 + 2 * i + 1];
        const float ua = acc[16 + f * 8 + 2 * i], ub = acc[16 + f * 8 + 2 * i + 1];
        const float c = (i & 1) ? c1 : c0, q = (i & 1) ? q1 : q0;
        const float da = 1.f + ex2f(fminf(ga * c, 60.f)), db = 1.f + ex2f(fminf(gb * c, 60.f));
        const float rq = rcpf(da * db) * q;
        h[i] = pack_bf16(ga * ua * (db * rq), gb * ub * (da * rq));
      }
      const int jj = hb * 2 + f;
      sts_u4(area + slot * 8192 + jj * 2048 + t128 * 16, h[0], h[1], h[2], h[3]);
      send_u4(&g_xbuf[m][p][xslot][w][jj][t128], h[0], h[1], h[2], h[3]);
    };
    auto kv_stage = [&](float (&acc)[32], int c, int hb) {
      const int srow = wq * 16 + (lane & 7) + ((lane >> 3) & 1) * 8;
      const uint32_t base = area + (3 + c) * 8192 + srow * 128;
#pragma unroll
      for (int jj = 0; jj < 2; jj++) {
        const int a = c * 16 + jj * 8;
        uint32_t r0, r1, r2, r3;
        if (c == 0) {
          r0 = pack_bf16(phi_f(acc[a] * rs0), phi_f(acc[a + 1] * rs0));
          r1 = pack_bf16(phi_f(acc[a + 2] * rs1), phi_f(acc[a + 3] * rs1));
          r2 = pack_bf16(phi_f(acc[a + 4] * rs0), phi_f(acc[a + 5] * rs0));
          r3 = pack_bf16(phi_f(acc[a + 6] * rs1), phi_f(acc[a + 7] * rs1));
        } else {
          r0 = pack_bf16(acc[a] * rs0, acc[a + 1] * rs0);
          r1 = pack_bf16(acc[a + 2] * rs1, acc[a + 3] * rs1);
          r2 = pack_bf16(acc[a + 4] * rs0, acc[a + 5] * rs0);
          r3 = pack_bf16(acc[a + 6] * rs1, acc[a + 7] * rs1);
        }
        stmatrix_x4(base + (((hb * 4 + jj * 2 + (lane >> 4)) ^ (srow & 7)) << 4), r0, r1, r2, r3);
      }
    };
    auto q_head = [&](float (&acc)[32], int c, int slot, uint32_t b0, uint32_t b1, uint32_t b2, uint32_t b3, uint32_t z0, uint32_t z1) {
      const int a = c * 8;
      const uint32_t a0 = pack_bf16(phi_f(acc[a] * rs0), phi_f(acc[a + 1] * rs0));
      const uint32_t a1 = pack_bf16(phi_f(acc[a + 2] * rs1), phi_f(acc[a + 3] * rs1));
      const uint32_t a2 = pack_bf16(phi_f(acc[a + 4] * rs0), phi_f(acc[a + 5] * rs0));
      const uint32_t a3 = pack_bf16(phi_f(acc[a + 6] * rs1), phi_f(acc[a + 7] * rs1));
      float n0[4] = {0.f, 0.f, 0.f, 0.f}, n1[4] = {0.f, 0.f, 0.f, 0.f}, dn[4] = {0.f, 0.f, 0.f, 0.f};
      mma_16816(n0, a0, a1, a2, a3, b0, b1);
      mma_16816(n1, a0, a1, a2, a3, b2, b3);
      mma_16816(dn, a0, a1, a2, a3, z0, z1);
      const float i0 = __fdividef(1.f, dn[0] + 1e-6f), i1 = __fdividef(1.f, dn[2] + 1e-6f);
      const uint32_t o0 = pack_bf16(n0[0] * i0, n0[1] * i0), o1 = pack_bf16(n0[2] * i1, n0[3] * i1);
      const uint32_t o2 = pack_bf16(n1[0] * i0, n1[1] * i0), o3 = pack_bf16(n1[2] * i1, n1[3] * i1);
      sts_u4(area + slot * 8192 + c * 2048 + t128 * 16, o0, o1, o2, o3);
      send_u4(&g_xbuf[m][p][slot][w][c][t128], o0, o1, o2, o3);
    };
    const uint32_t kvb = area + 5 * 8192;
    const uint32_t kvfrag = kvb + ((lane & 7) + ((lane >> 3) & 1) * 8) * 32 + (lane >> 4) * 16;
    auto signal = [&](int e) {
      __syncwarp();
      if (lane == 0) mbar_arrive(BAR(B_EV + w * 2 + e));
    };

    float accB[32];
#pragma unroll 1
    for (int t = 0; t < 5; t++) {
      float accA[32];
      const uint32_t ph = t & 1;
      const int kindP = t == 0 ? K_NONE : ((odd && t <= 2) ? K_KV : K_GU);
      const int kindC = odd ? (t < 2 ? K_KV : K_GU) : (t < 4 ? K_GU : K_Q);
      const int slotP = odd ? t - 3 : t - 1, xslotP = odd ? t + 3 : t - 1;
      const int slotC = odd ? t - 2 : t, xslotC = odd ? t + 4 : t;
      static_for<8>([&](auto kc) {
        constexpr int k = decltype(kc)::value;
        mbar_wait(BAR(B_FULL + k), ph);
        wgmma_fence();
        static_for<8>([&](auto kkc) {
          constexpr int kk = decltype(kkc)::value;
          constexpr int i = ((k & 3) * 8 + kk) * 4;
          constexpr uint32_t lo = desc_lo(stage_off(k) + kk * 1024, 8192);
          if constexpr (k < 4) wgmma_n64_rs<((k & 3) | kk) != 0, lo, kHi64>(accA, A[i], A[i + 1], A[i + 2], A[i + 3], dbase);
          else wgmma_n64_rs<((k & 3) | kk) != 0, lo, kHi64>(accB, A[i], A[i + 1], A[i + 2], A[i + 3], dbase);
        });
        wgmma_commit();
        if (k > 0) {
          wgmma_wait<1>();
          release(k - 1);
        }
        if constexpr (k < 4) {
          if (kindP == K_GU) {
            if (k == 1 || k == 2) gu_chunk(accB, k - 1, slotP, xslotP, 1);
          } else if (kindP == K_KV) {
            if (k == 1 || k == 2) kv_stage(accB, k - 1, 1);
            if (k == 3) {
              float kvacc[36];
              const int par = ld_relaxed(&g_epoch) & 1;
              fence_proxy_async();
              bar_sync(1 + w, 128);
              wgmma_fence();
              static_for<4>([&](auto kkc) {
                constexpr int kk = decltype(kkc)::value;
                wgmma_n72_ss_tt<kk != 0, desc_lo(3 * 8192 + kk * 2048, 0), desc_lo(4 * 8192 + kk * 2048, 8192 - kk * 2048)>(kvacc, dbase + w * 4096);
              });
              wgmma_commit();
              wgmma_wait<0>();
              float c[8];
#pragma unroll
              for (int i = 0; i < 8; i++)
                c[i] = wq == 0 ? kvacc[i] : (wq == 1 ? kvacc[8 + i] : (wq == 2 ? kvacc[16 + i] : kvacc[24 + i]));
              const int head = (2 * p + t - 1) * 4 + wq;
              float* kvp = &g_kv[par][head][0][0];
              red_add_v2(kvp + g * 16 + 2 * tq, c[0], c[1]);
              red_add_v2(kvp + (g + 8) * 16 + 2 * tq, c[2], c[3]);
              red_add_v2(kvp + g * 16 + 8 + 2 * tq, c[4], c[5]);
              red_add_v2(kvp + (g + 8) * 16 + 8 + 2 * tq, c[6], c[7]);
              if (tq == 0) {
                red_add(&g_z[par][head][g], kvacc[32]);
                red_add(&g_z[par][head][g + 8], kvacc[34]);
              }
              signal(t - 1);
            }
          }
        } else {
          constexpr int c = k - 4;
          if (kindC == K_GU) {
            if (c < 2) gu_chunk(accA, c, slotC, xslotC, 0);
          } else if (kindC == K_KV) {
            if (c == 0 && t == 0) sts_u4(area + 5 * 8192 + t128 * 16, 0x3F803F80u, 0x3F803F80u, 0x3F803F80u, 0x3F803F80u);
            if (c < 2) kv_stage(accA, c, 0);
          } else {
            if (c == 0) mbar_wait(BAR(B_KVREADY), 0);
            uint32_t b0, b1, b2, b3;
            ldmatrix_x4_trans(kvfrag + c * 512, b0, b1, b2, b3);
            const uint32_t z0 = lds_u32(kvb + 4096 + c * 32 + tq * 4), z1 = lds_u32(kvb + 4096 + c * 32 + 16 + tq * 4);
            q_head(accA, c, 4, b0, b1, b2, b3, z0, z1);
          }
        }
      });
      wgmma_wait<0>();
      release(7);
      PROF(w, 1 + 2 * t);
    }
    if (odd) {
      gu_chunk(accB, 0, 2, 8, 1);
      gu_chunk(accB, 1, 2, 8, 1);
    } else {
      uint32_t Bf[4][6];
#pragma unroll
      for (int c = 0; c < 4; c++) {
        ldmatrix_x4_trans(kvfrag + (4 + c) * 512, Bf[c][0], Bf[c][1], Bf[c][2], Bf[c][3]);
        Bf[c][4] = lds_u32(kvb + 4096 + (4 + c) * 32 + tq * 4);
        Bf[c][5] = lds_u32(kvb + 4096 + (4 + c) * 32 + 16 + tq * 4);
      }
      bar_sync(1 + w, 128);
#pragma unroll
      for (int c = 0; c < 4; c++) q_head(accB, c, 5, Bf[c][0], Bf[c][1], Bf[c][2], Bf[c][3], Bf[c][4], Bf[c][5]);
    }
    PROF(w, 10);

    const int n_own = odd ? 3 : 6;
    auto load_a = [&](int kb) {
      if (kb < n_own) {
#pragma unroll
        for (int jj = 0; jj < 4; jj++) {
          const int i = (kb * 4 + jj) * 4;
          lds_u4(area + kb * 8192 + jj * 2048 + t128 * 16, A[i], A[i + 1], A[i + 2], A[i + 3]);
        }
      } else {
        const int xs = odd ? kb - 3 : kb;
#pragma unroll
        for (int jj = 0; jj < 4; jj++) {
          const int i = (kb * 4 + jj) * 4;
          ldg_poll_u4(&g_xbuf[m][p][xs][w][jj][t128], A[i], A[i + 1], A[i + 2], A[i + 3]);
        }
      }
    };
    auto fix_a = [&](int kb) {
      if (kb >= n_own) {
        const int xs = odd ? kb - 3 : kb;
#pragma unroll
        for (int jj = 0; jj < 4; jj++) {
          const int i = (kb * 4 + jj) * 4;
          recv_u4(&g_xbuf[m][p][xs][w][jj][t128], A[i], A[i + 1], A[i + 2], A[i + 3]);
        }
      }
    };
#pragma unroll
    for (int kb = 0; kb < 7; kb++) load_a(kb);
    PROF(w, 11);

    const int orow = m * 128 + w * 64 + wq * 16 + g;
    const int ocol = odd * 256 + p * 64 + 2 * tq;
    float acc2[2][32];
    uint32_t P[3][32];
    uint32_t xr[16];
    auto send = [&](float (&acc)[32], int bi) {
      uint4* dst = &g_pbuf[m][odd][(p + 1 + bi) & 3][bi][w][0][t128];
#pragma unroll
      for (int q = 0; q < 8; q++)
        send_u4(dst + q * 128, __float_as_uint(acc[q * 4]), __float_as_uint(acc[q * 4 + 1]), __float_as_uint(acc[q * 4 + 2]), __float_as_uint(acc[q * 4 + 3]));
      PROF(w, 12 + 2 * bi);
    };
    auto fetch = [&](int sl) {
#pragma unroll
      for (int q = 0; q < 8; q++) ldg_poll_u4(&g_pbuf[m][odd][p][sl][w][q][t128], P[sl][q * 4], P[sl][q * 4 + 1], P[sl][q * 4 + 2], P[sl][q * 4 + 3]);
    };
    static_for<36>([&](auto ic) {
      constexpr int i = decltype(ic)::value, bi = p2_bi(i), kb = p2_kb(i), j = i >> 1, st = j & 7;
      if (i == 9) { load_a(7); load_a(8); }
      if (bi == 0 && kb >= 3) fix_a(kb);
      if ((i & 1) == 0) mbar_wait(BAR(B_FULL + st), (5 + (j >> 3)) & 1);
      wgmma_fence();
      static_for<4>([&](auto kkc) {
        constexpr int kk = decltype(kkc)::value, a = (kb * 4 + kk) * 4;
        wgmma_n64_rs<(kb | kk) != 0, desc_lo(stage_off(st) + (i & 1) * 8192 + kk * 2048, 0), kHi128>(acc2[bi & 1], A[a], A[a + 1], A[a + 2], A[a + 3], dbase);
      });
      wgmma_commit();
      if (i > 0) {
        wgmma_wait<1>();
        if ((i & 1) == 0 && j - 1 <= 9) release((j - 1) & 7);
      }
      if constexpr (i == 16) send(acc2[0], 0);
      if constexpr (i == 18) send(acc2[1], 1);
      if constexpr (i == 27) send(acc2[0], 2);
      if constexpr (i == 29) fetch(0);
      if constexpr (i == 31) fetch(1);
      if constexpr (i == 32) {
#pragma unroll
        for (int q = 0; q < 8; q++) {
          xr[2 * q] = __ldg((const uint32_t*)(x + (size_t)orow * kD + ocol + q * 8));
          xr[2 * q + 1] = __ldg((const uint32_t*)(x + (size_t)(orow + 8) * kD + ocol + q * 8));
        }
      }
      if constexpr (i == 34) fetch(2);
    });
#pragma unroll
    for (int sl = 0; sl < 3; sl++)
#pragma unroll
      for (int q = 0; q < 8; q++) recv_u4(&g_pbuf[m][odd][p][sl][w][q][t128], P[sl][q * 4], P[sl][q * 4 + 1], P[sl][q * 4 + 2], P[sl][q * 4 + 3]);
    wgmma_wait<0>();
    PROF(w, 18);
#pragma unroll
    for (int q = 0; q < 8; q++) {
      float rr[4];
#pragma unroll
      for (int e = 0; e < 4; e++)
        rr[e] = acc2[1][q * 4 + e] + __uint_as_float(P[0][q * 4 + e]) + __uint_as_float(P[1][q * 4 + e]) + __uint_as_float(P[2][q * 4 + e]);
      rr[0] += __uint_as_float(xr[2 * q] << 16);
      rr[1] += __uint_as_float(xr[2 * q] & 0xffff0000u);
      rr[2] += __uint_as_float(xr[2 * q + 1] << 16);
      rr[3] += __uint_as_float(xr[2 * q + 1] & 0xffff0000u);
      *(uint32_t*)(out + (size_t)orow * kD + ocol + q * 8) = pack_bf16(rr[0], rr[1]);
      *(uint32_t*)(out + (size_t)(orow + 8) * kD + ocol + q * 8) = pack_bf16(rr[2], rr[3]);
    }
    PROF(w, 19);
    if (tid == 0) {
      const uint32_t old = atomicAdd(&g_done, 1u);
      if ((old & 127u) == 127u) st_relaxed(&g_epoch, ld_relaxed(&g_epoch) + 1u);
    }
  }
#undef BAR
}

typedef CUresult (*EncodeFn)(CUtensorMap*, CUtensorMapDataType, cuuint32_t, void*, const cuuint64_t*, const cuuint64_t*,
                             const cuuint32_t*, const cuuint32_t*, CUtensorMapInterleave, CUtensorMapSwizzle,
                             CUtensorMapL2promotion, CUtensorMapFloatOOBfill);

void make_map(EncodeFn enc, CUtensorMap* tm, const void* ptr, int rows, int cols, bool narrow) {
  cuuint64_t gd[2] = {(cuuint64_t)cols, (cuuint64_t)rows};
  cuuint64_t gs[1] = {(cuuint64_t)cols * 2};
  cuuint32_t bd[2] = {narrow ? 32u : 64u, narrow ? 128u : 64u};
  cuuint32_t es[2] = {1, 1};
  enc(tm, CU_TENSOR_MAP_DATA_TYPE_BFLOAT16, 2, const_cast<void*>(ptr), gd, gs, bd, es, CU_TENSOR_MAP_INTERLEAVE_NONE,
      narrow ? CU_TENSOR_MAP_SWIZZLE_64B : CU_TENSOR_MAP_SWIZZLE_128B, CU_TENSOR_MAP_L2_PROMOTION_L2_256B, CU_TENSOR_MAP_FLOAT_OOB_FILL_NONE);
}

}

extern "C" void kernel_launch(void* const* d_in, const int* in_sizes, int n_in, void* d_out, int out_size) {
  static EncodeFn enc = nullptr;
  if (!enc) {
    void* fn = nullptr;
    cudaDriverEntryPointQueryResult qr;
    cudaGetDriverEntryPoint("cuTensorMapEncodeTiled", &fn, cudaEnableDefault, &qr);
    enc = (EncodeFn)fn;
    cudaFuncSetAttribute(fused_kernel, cudaFuncAttributeMaxDynamicSharedMemorySize, kSmemBytes);
  }
  CUtensorMap tm_x, tm_wqkv, tm_w1, tm_w3, tm_w2, tm_wo;
  make_map(enc, &tm_x, d_in[0], kS, kD, false);
  make_map(enc, &tm_wqkv, d_in[1], kD, 3 * kD, true);
  make_map(enc, &tm_wo, d_in[2], kD, kD, false);
  make_map(enc, &tm_w1, d_in[4], kD, kF, true);
  make_map(enc, &tm_w3, d_in[5], kD, kF, true);
  make_map(enc, &tm_w2, d_in[6], kF, kD, false);
  fused_kernel<<<128, 384, kSmemBytes>>>(tm_x, tm_wqkv, tm_w1, tm_w3, tm_w2, tm_wo, (const __nv_bfloat16*)d_in[0],
                                         (__nv_bfloat16*)d_out);
}
```

```cpp
#include <cuda_runtime.h>
#include <cuda_bf16.h>
#include <cuda.h>
#include <stdint.h>

namespace {

constexpr int kS = 2048, kD = 512, kF = 1792;
constexpr uint32_t kSpinLimit = 1u << 22;

__device__ uint4    g_xbuf[16][4][9][2][4][128];
__device__ uint4    g_pbuf[16][2][4][3][2][8][128];
__device__ float    g_kv[2][32][16][16];
__device__ float    g_z[2][32][16];
__device__ uint32_t g_kvcnt[4][32];
__device__ uint32_t g_epoch;
__device__ uint32_t g_done;
#define PROF(wg, i) do {} while (0)

__device__ __forceinline__ uint32_t smem_u32(const void* p) { return (uint32_t)__cvta_generic_to_shared(p); }
__device__ __forceinline__ void mbar_init(uint32_t bar, uint32_t cnt) {
  asm volatile("mbarrier.init.shared::cta.b64 [%0], %1;" ::"r"(bar), "r"(cnt) : "memory");
}
__device__ __forceinline__ void mbar_expect_tx(uint32_t bar, uint32_t bytes) {
  asm volatile("mbarrier.arrive.expect_tx.shared::cta.b64 _, [%0], %1;" ::"r"(bar), "r"(bytes) : "memory");
}
__device__ __forceinline__ void mbar_arrive(uint32_t bar) {
  asm volatile("mbarrier.arrive.shared::cta.b64 _, [%0];" ::"r"(bar) : "memory");
}
__device__ __forceinline__ void mbar_wait(uint32_t bar, uint32_t parity) {
  asm volatile(
      "{\n.reg .pred p;\n"
      "LAB_WAIT:\n"
      "mbarrier.try_wait.parity.shared::cta.b64 p, [%0], %1;\n"
      "@p bra DONE;\n"
      "bra LAB_WAIT;\n"
      "DONE:\n}" ::"r"(bar), "r"(parity) : "memory");
}
__device__ __forceinline__ void tma_load_2d(uint32_t dst, const CUtensorMap* tm, uint32_t bar, int c0, int c1) {
  asm volatile(
      "cp.async.bulk.tensor.2d.shared::cluster.global.mbarrier::complete_tx::bytes [%0], [%1, {%3, %4}], [%2];" ::"r"(dst),
      "l"(tm), "r"(bar), "r"(c0), "r"(c1)
      : "memory");
}
__device__ __forceinline__ void tma_load_2d_mc(uint32_t dst, const CUtensorMap* tm, uint32_t bar, int c0, int c1) {
  asm volatile(
      "cp.async.bulk.tensor.2d.shared::cluster.global.mbarrier::complete_tx::bytes.multicast::cluster [%0], [%1, {%3, %4}], [%2], %5;" ::"r"(dst),
      "l"(tm), "r"(bar), "r"(c0), "r"(c1), "h"((uint16_t)3)
      : "memory");
}
__device__ __forceinline__ void mbar_arrive_cluster(uint32_t bar, uint32_t cta) {
  asm volatile("{\n.reg .b32 ra;\nmapa.shared::cluster.u32 ra, %0, %1;\nmbarrier.arrive.shared::cluster.b64 _, [ra];\n}" ::"r"(bar), "r"(cta) : "memory");
}
__device__ __forceinline__ void prefetch_tmap(const CUtensorMap* tm) {
  asm volatile("prefetch.tensormap [%0];" ::"l"(tm) : "memory");
}
__device__ __forceinline__ void wgmma_fence() { asm volatile("wgmma.fence.sync.aligned;" ::: "memory"); }
__device__ __forceinline__ void wgmma_commit() { asm volatile("wgmma.commit_group.sync.aligned;" ::: "memory"); }
template <int N>
__device__ __forceinline__ void wgmma_wait() { asm volatile("wgmma.wait_group.sync.aligned %0;" ::"n"(N) : "memory"); }
__device__ __forceinline__ void bar_sync(int id, int n) { asm volatile("bar.sync %0, %1;" ::"r"(id), "r"(n) : "memory"); }
__device__ __forceinline__ void bar_arrive(int id, int n) { asm volatile("bar.arrive %0, %1;" ::"r"(id), "r"(n) : "memory"); }
__device__ __forceinline__ void fence_proxy_async() { asm volatile("fence.proxy.async.shared::cta;" ::: "memory"); }

__device__ __forceinline__ uint32_t ld_acquire(const uint32_t* p) {
  uint32_t v;
  asm volatile("ld.acquire.gpu.global.u32 %0, [%1];" : "=r"(v) : "l"(p) : "memory");
  return v;
}
__device__ __forceinline__ uint32_t ld_relaxed(const uint32_t* p) {
  uint32_t v;
  asm volatile("ld.relaxed.gpu.global.u32 %0, [%1];" : "=r"(v) : "l"(p));
  return v;
}
__device__ __forceinline__ void cluster_wait() { asm volatile("barrier.cluster.wait.aligned;" ::: "memory"); }
__device__ __forceinline__ void st_relaxed(uint32_t* p, uint32_t v) {
  asm volatile("st.relaxed.gpu.global.u32 [%0], %1;" ::"l"(p), "r"(v) : "memory");
}
__device__ __forceinline__ void wait_flag_eq(const uint32_t* p, uint32_t val) {
  uint32_t it = 0;
  while (ld_acquire(p) != val) {
    if (++it > kSpinLimit) break;
  }
}
__device__ __forceinline__ void wait_count_ge(const uint32_t* p, uint32_t val) {
  uint32_t it = 0;
  while ((int32_t)(ld_acquire(p) - val) < 0) {
    __nanosleep(64);
    if (++it > kSpinLimit) break;
  }
}
__device__ __forceinline__ void ldg_poll_u4(const void* p, uint32_t& a, uint32_t& b, uint32_t& c, uint32_t& d) {
  asm volatile("ld.relaxed.gpu.global.v4.u32 {%0,%1,%2,%3}, [%4];" : "=r"(a), "=r"(b), "=r"(c), "=r"(d) : "l"(p) : "memory");
}
template <int N>
__device__ __forceinline__ void recv_group(uint4* p, uint32_t* r) {
  uint32_t it = 0;
  while (true) {
    uint32_t mn = 0xffffffffu;
#pragma unroll
    for (int i = 0; i < 4 * N; i++) mn = min(mn, r[i]);
    if (!__any_sync(0xffffffffu, mn == 0u) || ++it > kSpinLimit) break;
#pragma unroll
    for (int q = 0; q < N; q++) ldg_poll_u4(p + q * 128, r[q * 4], r[q * 4 + 1], r[q * 4 + 2], r[q * 4 + 3]);
  }
#pragma unroll
  for (int i = 0; i < 4 * N; i++) r[i] = ~r[i];
#pragma unroll
  for (int q = 0; q < N; q++) asm volatile("st.global.v4.u32 [%0], {%1,%1,%1,%1};" ::"l"(p + q * 128), "r"(0u) : "memory");
}
__device__ __forceinline__ void send_u4(void* p, uint32_t a, uint32_t b, uint32_t c, uint32_t d) {
  asm volatile("st.global.v4.u32 [%0], {%1,%2,%3,%4};" ::"l"(p), "r"(~a), "r"(~b), "r"(~c), "r"(~d) : "memory");
}
__device__ __forceinline__ float4 ldg_cg_f4(const void* p) {
  float4 v;
  asm volatile("ld.global.cg.v4.f32 {%0,%1,%2,%3}, [%4];" : "=f"(v.x), "=f"(v.y), "=f"(v.z), "=f"(v.w) : "l"(p) : "memory");
  return v;
}
__device__ __forceinline__ void stg_u4(void* p, uint32_t a, uint32_t b, uint32_t c, uint32_t d) {
  asm volatile("st.global.v4.u32 [%0], {%1,%2,%3,%4};" ::"l"(p), "r"(a), "r"(b), "r"(c), "r"(d) : "memory");
}
__device__ __forceinline__ void stg_f4(void* p, float a, float b, float c, float d) {
  asm volatile("st.global.v4.f32 [%0], {%1,%2,%3,%4};" ::"l"(p), "f"(a), "f"(b), "f"(c), "f"(d) : "memory");
}
__device__ __forceinline__ void sts_u4(uint32_t addr, uint32_t a, uint32_t b, uint32_t c, uint32_t d) {
  asm volatile("st.shared.v4.u32 [%0], {%1,%2,%3,%4};" ::"r"(addr), "r"(a), "r"(b), "r"(c), "r"(d) : "memory");
}
__device__ __forceinline__ void lds_u4(uint32_t addr, uint32_t& a, uint32_t& b, uint32_t& c, uint32_t& d) {
  asm volatile("ld.shared.v4.u32 {%0,%1,%2,%3}, [%4];" : "=r"(a), "=r"(b), "=r"(c), "=r"(d) : "r"(addr) : "memory");
}
__device__ __forceinline__ uint32_t lds_u32(uint32_t addr) {
  uint32_t v;
  asm volatile("ld.shared.u32 %0, [%1];" : "=r"(v) : "r"(addr) : "memory");
  return v;
}
__device__ __forceinline__ void ldmatrix_x4(uint32_t addr, uint32_t& a, uint32_t& b, uint32_t& c, uint32_t& d) {
  asm volatile("ldmatrix.sync.aligned.m8n8.x4.shared.b16 {%0,%1,%2,%3}, [%4];" : "=r"(a), "=r"(b), "=r"(c), "=r"(d) : "r"(addr) : "memory");
}
__device__ __forceinline__ void ldmatrix_x4_trans(uint32_t addr, uint32_t& a, uint32_t& b, uint32_t& c, uint32_t& d) {
  asm volatile("ldmatrix.sync.aligned.m8n8.x4.trans.shared.b16 {%0,%1,%2,%3}, [%4];" : "=r"(a), "=r"(b), "=r"(c), "=r"(d) : "r"(addr) : "memory");
}
__device__ __forceinline__ void stmatrix_x4(uint32_t addr, uint32_t a, uint32_t b, uint32_t c, uint32_t d) {
  asm volatile("stmatrix.sync.aligned.m8n8.x4.shared.b16 [%0], {%1,%2,%3,%4};" ::"r"(addr), "r"(a), "r"(b), "r"(c), "r"(d) : "memory");
}
__device__ __forceinline__ void mma_16816(float (&c)[4], uint32_t a0, uint32_t a1, uint32_t a2, uint32_t a3, uint32_t b0, uint32_t b1) {
  asm volatile(
      "mma.sync.aligned.m16n8k16.row.col.f32.bf16.bf16.f32 {%0,%1,%2,%3}, {%4,%5,%6,%7}, {%8,%9}, {%0,%1,%2,%3};"
      : "+f"(c[0]), "+f"(c[1]), "+f"(c[2]), "+f"(c[3])
      : "r"(a0), "r"(a1), "r"(a2), "r"(a3), "r"(b0), "r"(b1));
}
__device__ __forceinline__ uint32_t pack_bf16(float lo, float hi) {
  uint32_t r;
  asm("cvt.rn.bf16x2.f32 %0, %1, %2;" : "=r"(r) : "f"(hi), "f"(lo));
  return r;
}
__device__ __forceinline__ uint32_t hsub2_bf16(uint32_t a, uint32_t b) {
  uint32_t r;
  asm("sub.rn.bf16x2 %0, %1, %2;" : "=r"(r) : "r"(a), "r"(b));
  return r;
}
__device__ __forceinline__ float ex2f(float x) {
  float r;
  asm("ex2.approx.ftz.f32 %0, %1;" : "=f"(r) : "f"(x));
  return r;
}
__device__ __forceinline__ float rcpf(float x) {
  float r;
  asm("rcp.approx.ftz.f32 %0, %1;" : "=f"(r) : "f"(x));
  return r;
}
__device__ __forceinline__ void red_add_v2(float* p, float a, float b) {
  asm volatile("red.relaxed.gpu.global.add.v2.f32 [%0], {%1,%2};" ::"l"(p), "f"(a), "f"(b) : "memory");
}
__device__ __forceinline__ void red_add(float* p, float a) {
  asm volatile("red.relaxed.gpu.global.add.f32 [%0], %1;" ::"l"(p), "f"(a) : "memory");
}
__device__ __forceinline__ float phi_f(float t) {
  float e = ex2f(t * 1.4426950408889634f);
  return (t > 0.f ? t + 1.f : e) + 1e-6f;
}

#define R8(a, o) "+f"(a[o + 0]), "+f"(a[o + 1]), "+f"(a[o + 2]), "+f"(a[o + 3]), "+f"(a[o + 4]), "+f"(a[o + 5]), "+f"(a[o + 6]), "+f"(a[o + 7])

#define W8(a, o) "=f"(a[o + 0]), "=f"(a[o + 1]), "=f"(a[o + 2]), "=f"(a[o + 3]), "=f"(a[o + 4]), "=f"(a[o + 5]), "=f"(a[o + 6]), "=f"(a[o + 7])
#define D32 "{%0,%1,%2,%3,%4,%5,%6,%7,%8,%9,%10,%11,%12,%13,%14,%15,%16,%17,%18,%19,%20,%21,%22,%23,%24,%25,%26,%27,%28,%29,%30,%31}"
#define D36 "{%0,%1,%2,%3,%4,%5,%6,%7,%8,%9,%10,%11,%12,%13,%14,%15,%16,%17,%18,%19,%20,%21,%22,%23,%24,%25,%26,%27,%28,%29,%30,%31,%32,%33,%34,%35}"

constexpr uint32_t kHi128 = (1024u >> 4) | (1u << 30);
constexpr uint32_t kHi64 = (512u >> 4) | (2u << 30);
__host__ __device__ constexpr uint32_t desc_lo(uint32_t off, uint32_t lbo) { return (off >> 4) | ((lbo >> 4) << 16); }

template <bool ACC, uint32_t LO, uint32_t HI>
__device__ __forceinline__ void wgmma_n64_rs(float (&d)[32], uint32_t a0, uint32_t a1, uint32_t a2, uint32_t a3, uint32_t base) {
  if (ACC) {
    asm volatile(
        "{\n.reg .pred p;\n.reg .b32 lo;\n.reg .b64 dd;\nsetp.eq.b32 p, 0, 0;\nadd.u32 lo, %36, %37;\nmov.b64 dd, {lo, %38};\n"
        "wgmma.mma_async.sync.aligned.m64n64k16.f32.bf16.bf16 " D32 ", {%32,%33,%34,%35}, dd, p, 1, 1, 1;\n}"
        : R8(d, 0), R8(d, 8), R8(d, 16), R8(d, 24)
        : "r"(a0), "r"(a1), "r"(a2), "r"(a3), "r"(base), "n"(LO), "n"(HI));
  } else {
    asm volatile(
        "{\n.reg .pred p;\n.reg .b32 lo;\n.reg .b64 dd;\nsetp.ne.b32 p, 0, 0;\nadd.u32 lo, %36, %37;\nmov.b64 dd, {lo, %38};\n"
        "wgmma.mma_async.sync.aligned.m64n64k16.f32.bf16.bf16 " D32 ", {%32,%33,%34,%35}, dd, p, 1, 1, 1;\n}"
        : W8(d, 0), W8(d, 8), W8(d, 16), W8(d, 24)
        : "r"(a0), "r"(a1), "r"(a2), "r"(a3), "r"(base), "n"(LO), "n"(HI));
  }
}
template <bool ACC, uint32_t LOA, uint32_t LOB>
__device__ __forceinline__ void wgmma_n72_ss_tt(float (&d)[36], uint32_t base) {
  if (ACC) {
    asm volatile(
        "{\n.reg .pred p;\n.reg .b32 lo;\n.reg .b64 da, db;\nsetp.eq.b32 p, 0, 0;\n"
        "add.u32 lo, %36, %37;\nmov.b64 da, {lo, %39};\nadd.u32 lo, %36, %38;\nmov.b64 db, {lo, %39};\n"
        "wgmma.mma_async.sync.aligned.m64n72k16.f32.bf16.bf16 " D36 ", da, db, p, 1, 1, 1, 1;\n}"
        : R8(d, 0), R8(d, 8), R8(d, 16), R8(d, 24), "+f"(d[32]), "+f"(d[33]), "+f"(d[34]), "+f"(d[35])
        : "r"(base), "n"(LOA), "n"(LOB), "n"(kHi128));
  } else {
    asm volatile(
        "{\n.reg .pred p;\n.reg .b32 lo;\n.reg .b64 da, db;\nsetp.ne.b32 p, 0, 0;\n"
        "add.u32 lo, %36, %37;\nmov.b64 da, {lo, %39};\nadd.u32 lo, %36, %38;\nmov.b64 db, {lo, %39};\n"
        "wgmma.mma_async.sync.aligned.m64n72k16.f32.bf16.bf16 " D36 ", da, db, p, 1, 1, 1, 1;\n}"
        : W8(d, 0), W8(d, 8), W8(d, 16), W8(d, 24), "=f"(d[32]), "=f"(d[33]), "=f"(d[34]), "=f"(d[35])
        : "r"(base), "n"(LOA), "n"(LOB), "n"(kHi128));
  }
}

template <int V> struct IC { static constexpr int value = V; };
template <int N, int I = 0, typename F>
__device__ __forceinline__ void static_for(F&& f) {
  if constexpr (I < N) { f(IC<I>{}); static_for<N, I + 1>(f); }
}

__host__ __device__ constexpr uint32_t stage_off(int st) {
  return st < 6 ? 131072u + (uint32_t)st * 16384u : (uint32_t)(st - 6) * 65536u + 49152u;
}

constexpr int B_FULL = 0, B_EMPTY = 8, B_XFULL = 16, B_XDONE = 32, B_KVREADY = 33, B_EV = 34, B_COUNT = 38;
constexpr uint32_t kBarOff = 229376;
constexpr int kSmemBytes = 229376 + 1024;

__host__ __device__ constexpr int p2_bi(int i) { return i < 7 ? 0 : i < 14 ? 1 : i < 16 ? 0 : i < 18 ? 1 : i / 9; }
__host__ __device__ constexpr int p2_kb(int i) { return i < 7 ? i : i < 14 ? i - 7 : i < 16 ? i - 7 : i < 18 ? i - 9 : i % 9; }

enum { K_NONE = 0, K_GU = 1, K_KV = 2, K_Q = 3 };

__global__ void __cluster_dims__(2, 1, 1) __launch_bounds__(384, 1)
fused_kernel(const __grid_constant__ CUtensorMap tm_x, const __grid_constant__ CUtensorMap tm_wqkv,
             const __grid_constant__ CUtensorMap tm_w1, const __grid_constant__ CUtensorMap tm_w3,
             const __grid_constant__ CUtensorMap tm_w2, const __grid_constant__ CUtensorMap tm_wo,
             const __nv_bfloat16* __restrict__ x, __nv_bfloat16* __restrict__ out) {
  extern __shared__ __align__(1024) uint8_t smem_raw[];
  const uint32_t sbase = __shfl_sync(0xffffffffu, smem_u32(smem_raw), 0);
  const uint32_t bars = sbase + kBarOff;
  const int tid = threadIdx.x, lane = tid & 31;
  const int warp = __shfl_sync(0xffffffffu, tid >> 5, 0);
  const int cr = blockIdx.x & 1;
  const int r = (blockIdx.x >> 1) & 7, m = ((blockIdx.x >> 4) << 1) | cr, p = r >> 1, odd = r & 1;
#define BAR(i) (bars + 8u * (uint32_t)(i))
  if (tid == 256) {
    if (sbase & 1023u) __trap();
#pragma unroll
    for (int i = 0; i < 16; i++) mbar_init(BAR(B_XFULL + i), 1);
    fence_proxy_async();
#pragma unroll
    for (int b = 0; b < 16; b++) {
      mbar_expect_tx(BAR(B_XFULL + b), 8192);
      tma_load_2d(sbase + (b >> 3) * 65536 + (b & 7) * 8192, &tm_x, BAR(B_XFULL + b), (b & 7) * 64, m * 128 + (b >> 3) * 64);
    }
#pragma unroll
    for (int i = 0; i < 8; i++) { mbar_init(BAR(B_FULL + i), 1); mbar_init(BAR(B_EMPTY + i), 4); }
#pragma unroll
    for (int i = 0; i < 4; i++) mbar_init(BAR(B_EV + i), 4);
    mbar_init(BAR(B_XDONE), 2);
    mbar_init(BAR(B_KVREADY), 1);
    asm volatile("fence.mbarrier_init.release.cluster;" ::: "memory");
    fence_proxy_async();
  } else if (tid == 288) {
    prefetch_tmap(odd ? &tm_wqkv : (cr ? &tm_w3 : &tm_w1));
  }
  __syncwarp();
  asm volatile("barrier.cluster.arrive.relaxed.aligned;" ::: "memory");
  PROF((tid >> 7), 21);
  __syncthreads();

  if (warp >= 8) {
    asm volatile("setmaxnreg.dec.sync.aligned.u32 24;");
    PROF(2, 3);
    cluster_wait();
    PROF(2, 2);
    const uint32_t epoch = warp == 8 ? 0u : ld_relaxed(&g_epoch);
    const uint32_t tag = epoch + 1u;
    const int par = epoch & 1;
    if (warp == 8) {
      if (lane == 0) {
        for (int j = 0; j < 10; j++) {
          const CUtensorMap* tm;
          int col;
          if (!odd) {
            if (j < 8) { tm = cr ? &tm_w3 : &tm_w1; col = 7 * p * 64 + j * 32; }
            else { tm = &tm_wqkv; col = 128 * p + (j - 8) * 64 + cr * 32; }
          } else {
            if (j < 4) { tm = &tm_wqkv; col = 512 + cr * 512 + 128 * p + j * 32; }
            else { tm = cr ? &tm_w3 : &tm_w1; col = (7 * p + 4) * 64 + (j - 4) * 32; }
          }
          const int t = j >> 1;
          for (int kq = 0; kq < 4; kq++) {
            const int k = (j & 1) * 4 + kq;
            mbar_wait(BAR(B_EMPTY + k), k < 6 ? ((t & 1) ^ 1) : (t & 1));
            mbar_expect_tx(BAR(B_FULL + k), 16384);
            tma_load_2d_mc(sbase + stage_off(k) + cr * 8192, tm, BAR(B_FULL + k), col, kq * 128);
          }
        }
        for (int j = 0; j < 18; j++) {
          const int st = j & 7, n = 5 + (j >> 3);
          const int i = 2 * j + cr;
          const int bi = p2_bi(i), kb = p2_kb(i);
          const int col = odd * 256 + ((p + 1 + bi) & 3) * 64;
          const CUtensorMap* tmk;
          int row;
          if (!odd) {
            if (kb < 4) { tmk = &tm_w2; row = (7 * p + kb) * 64; }
            else if (kb < 6) { tmk = &tm_wo; row = (2 * p + kb - 4) * 64; }
            else { tmk = &tm_w2; row = (7 * p + 4 + kb - 6) * 64; }
          } else {
            if (kb < 3) { tmk = &tm_w2; row = (7 * p + 4 + kb) * 64; }
            else if (kb < 7) { tmk = &tm_w2; row = (7 * p + kb - 3) * 64; }
            else { tmk = &tm_wo; row = (2 * p + kb - 7) * 64; }
          }
          mbar_wait(BAR(B_EMPTY + st), st < 6 ? ((n & 1) ^ 1) : (n & 1));
          mbar_expect_tx(BAR(B_FULL + st), 16384);
          tma_load_2d_mc(sbase + stage_off(st) + cr * 8192, tmk, BAR(B_FULL + st), col, row);
        }
      }
    } else if (warp <= 10) {
      if (lane == 0 && odd) {
        const int w = warp - 9;
        for (int e = 0; e < 2; e++) {
          mbar_wait(BAR(B_EV + w * 2 + e), 0);
          __threadfence();
          atomicAdd(&g_kvcnt[p][0], 1u);
        }
      }
    } else {
      if (!odd) {
        {
          const int ce = m * 4 + p;
          float* kvn = &g_kv[par ^ 1][0][0][0];
          for (int i = lane; i < 128; i += 32) kvn[ce * 128 + i] = 0.f;
          if (lane < 8) (&g_z[par ^ 1][0][0])[ce * 8 + lane] = 0.f;
        }
        mbar_wait(BAR(B_XDONE), 0);
        wait_count_ge(&g_kvcnt[p][0], 64u * tag);
        const float* kvp = &g_kv[par][8 * p][0][0];
        const uint32_t dst0 = sbase + 5 * 8192, dst1 = dst0 + 65536;
#pragma unroll 4
        for (int i = 0; i < 16; i++) {
          float4 v = ldg_cg_f4(kvp + (i * 32 + lane) * 4);
          uint32_t lo = pack_bf16(v.x, v.y), hi = pack_bf16(v.z, v.w);
          uint32_t off = (uint32_t)(i * 32 + lane) * 8u;
          asm volatile("st.shared.v2.u32 [%0], {%1,%2};" ::"r"(dst0 + off), "r"(lo), "r"(hi) : "memory");
          asm volatile("st.shared.v2.u32 [%0], {%1,%2};" ::"r"(dst1 + off), "r"(lo), "r"(hi) : "memory");
        }
        {
          float4 v = ldg_cg_f4(&g_z[par][8 * p][0] + lane * 4);
          uint32_t lo = pack_bf16(v.x, v.y), hi = pack_bf16(v.z, v.w);
          uint32_t off = 4096u + (uint32_t)lane * 8u;
          asm volatile("st.shared.v2.u32 [%0], {%1,%2};" ::"r"(dst0 + off), "r"(lo), "r"(hi) : "memory");
          asm volatile("st.shared.v2.u32 [%0], {%1,%2};" ::"r"(dst1 + off), "r"(lo), "r"(hi) : "memory");
        }
        __syncwarp();
        if (lane == 0) mbar_arrive(BAR(B_KVREADY));
      }
    }
  } else {
    asm volatile("setmaxnreg.inc.sync.aligned.u32 240;");
    const int w = warp >> 2, wq = warp & 3, t128 = tid & 127;
    const int g = lane >> 2, tq = lane & 3;
    const uint32_t area = sbase + (uint32_t)w * 65536u;
    const bool elect = (t128 == 0);
    PROF(w, 22);
    const uint32_t dbase = (sbase & 0x3FFFFu) >> 4;
    uint32_t A[144];
    float rs0, rs1;
    auto release = [&](int st) {
      if (elect) { mbar_arrive_cluster(BAR(B_EMPTY + st), 0); mbar_arrive_cluster(BAR(B_EMPTY + st), 1); }
    };

    {
      const int row = wq * 16 + (lane & 7) + ((lane >> 3) & 1) * 8;
      const uint32_t rbase = area + row * 128;
      float s0[2][4] = {}, q0[2][4] = {}, q1[2][4] = {};
      const uint32_t ones = 0x3F803F80u;
#pragma unroll
      for (int b = 0; b < 8; b++) {
        mbar_wait(BAR(B_XFULL + w * 8 + b), 0);
        if (b == 0) PROF(w, 23);
        if (b == 7) PROF(w, 24);
#pragma unroll
        for (int kk = 0; kk < 4; kk++) {
          const int i = (b * 4 + kk) * 4;
          ldmatrix_x4(rbase + b * 8192 + (((kk * 2 + (lane >> 4)) ^ (row & 7)) << 4), A[i], A[i + 1], A[i + 2], A[i + 3]);
        }
#pragma unroll
        for (int kk = 0; kk < 4; kk++) {
          const int i = (b * 4 + kk) * 4;
          mma_16816(s0[kk & 1], A[i], A[i + 1], A[i + 2], A[i + 3], ones, ones);
          mma_16816(q0[kk & 1], A[i], A[i + 1], A[i + 2], A[i + 3], A[i], A[i + 2]);
          mma_16816(q1[kk & 1], A[i], A[i + 1], A[i + 2], A[i + 3], A[i + 1], A[i + 3]);
        }
      }
      const float mean0 = (s0[0][0] + s0[1][0]) * (1.f / 512.f), mean1 = (s0[0][2] + s0[1][2]) * (1.f / 512.f);
      const uint32_t m0 = pack_bf16(mean0, mean0), m1 = pack_bf16(mean1, mean1);
#pragma unroll
      for (int i = 0; i < 128; i += 2) {
        A[i] = hsub2_bf16(A[i], m0);
        A[i + 1] = hsub2_bf16(A[i + 1], m1);
      }
      float v0 = (g & 1) ? q0[0][1] + q0[1][1] : q0[0][0] + q0[1][0];
      float v1 = (g & 1) ? q1[0][3] + q1[1][3] : q1[0][2] + q1[1][2];
      const int src = 4 * g + (g >> 1);
      v0 = __shfl_sync(0xffffffffu, v0, src);
      v1 = __shfl_sync(0xffffffffu, v1, src);
      v0 = fmaxf(v0 * (1.f / 512.f) - mean0 * mean0, 0.f);
      v1 = fmaxf(v1 * (1.f / 512.f) - mean1 * mean1, 0.f);
      rs0 = rsqrtf(v0 + 1e-5f);
      rs1 = rsqrtf(v1 + 1e-5f);
      bar_sync(1 + w, 128);
      cluster_wait();
      PROF(w, 0);
      release(6); release(7);
      if (elect) mbar_arrive(BAR(B_XDONE));
    }

    auto gu_chunk = [&](float (&acc)[32], int f, int slot, int xslot, int hb) {
      const float c0 = rs0 * -1.4426950408889634f, c1 = rs1 * -1.4426950408889634f;
      const float q0 = rs0 * rs0, q1 = rs1 * rs1;
      uint32_t h[4];
#pragma unroll
      for (int i = 0; i < 4; i++) {
        const float ga = acc[f * 8 + 2 * i], gb = acc[f * 8 + 2 * i + 1];
        const float ua = acc[16 + f * 8 + 2 * i], ub = acc[16 + f * 8 + 2 * i + 1];
        const float c = (i & 1) ? c1 : c0, q = (i & 1) ? q1 : q0;
        const float da = 1.f + ex2f(fminf(ga * c, 60.f)), db = 1.f + ex2f(fminf(gb * c, 60.f));
        const float rq = rcpf(da * db) * q;
        h[i] = pack_bf16(ga * ua * (db * rq), gb * ub * (da * rq));
      }
      const int jj = hb * 2 + f;
      sts_u4(area + slot * 8192 + jj * 2048 + t128 * 16, h[0], h[1], h[2], h[3]);
      send_u4(&g_xbuf[m][p][xslot][w][jj][t128], h[0], h[1], h[2], h[3]);
    };
    auto kv_stage = [&](float (&acc)[32], int c, int hb) {
      const int srow = wq * 16 + (lane & 7) + ((lane >> 3) & 1) * 8;
      const uint32_t base = area + (3 + c) * 8192 + srow * 128;
#pragma unroll
      for (int jj = 0; jj < 2; jj++) {
        const int a = c * 16 + jj * 8;
        uint32_t r0, r1, r2, r3;
        if (c == 0) {
          r0 = pack_bf16(phi_f(acc[a] * rs0), phi_f(acc[a + 1] * rs0));
          r1 = pack_bf16(phi_f(acc[a + 2] * rs1), phi_f(acc[a + 3] * rs1));
          r2 = pack_bf16(phi_f(acc[a + 4] * rs0), phi_f(acc[a + 5] * rs0));
          r3 = pack_bf16(phi_f(acc[a + 6] * rs1), phi_f(acc[a + 7] * rs1));
        } else {
          r0 = pack_bf16(acc[a] * rs0, acc[a + 1] * rs0);
          r1 = pack_bf16(acc[a + 2] * rs1, acc[a + 3] * rs1);
          r2 = pack_bf16(acc[a + 4] * rs0, acc[a + 5] * rs0);
          r3 = pack_bf16(acc[a + 6] * rs1, acc[a + 7] * rs1);
        }
        stmatrix_x4(base + (((hb * 4 + jj * 2 + (lane >> 4)) ^ (srow & 7)) << 4), r0, r1, r2, r3);
      }
    };
    auto q_head = [&](float (&acc)[32], int c, int slot, uint32_t b0, uint32_t b1, uint32_t b2, uint32_t b3, uint32_t z0, uint32_t z1) {
      const int a = c * 8;
      const uint32_t a0 = pack_bf16(phi_f(acc[a] * rs0), phi_f(acc[a + 1] * rs0));
      const uint32_t a1 = pack_bf16(phi_f(acc[a + 2] * rs1), phi_f(acc[a + 3] * rs1));
      const uint32_t a2 = pack_bf16(phi_f(acc[a + 4] * rs0), phi_f(acc[a + 5] * rs0));
      const uint32_t a3 = pack_bf16(phi_f(acc[a + 6] * rs1), phi_f(acc[a + 7] * rs1));
      float n0[4] = {0.f, 0.f, 0.f, 0.f}, n1[4] = {0.f, 0.f, 0.f, 0.f}, dn[4] = {0.f, 0.f, 0.f, 0.f};
      mma_16816(n0, a0, a1, a2, a3, b0, b1);
      mma_16816(n1, a0, a1, a2, a3, b2, b3);
      mma_16816(dn, a0, a1, a2, a3, z0, z1);
      const float i0 = __fdividef(1.f, dn[0] + 1e-6f), i1 = __fdividef(1.f, dn[2] + 1e-6f);
      const uint32_t o0 = pack_bf16(n0[0] * i0, n0[1] * i0), o1 = pack_bf16(n0[2] * i1, n0[3] * i1);
      const uint32_t o2 = pack_bf16(n1[0] * i0, n1[1] * i0), o3 = pack_bf16(n1[2] * i1, n1[3] * i1);
      sts_u4(area + slot * 8192 + c * 2048 + t128 * 16, o0, o1, o2, o3);
      send_u4(&g_xbuf[m][p][slot][w][c][t128], o0, o1, o2, o3);
    };
    const uint32_t kvb = area + 5 * 8192;
    const uint32_t kvfrag = kvb + ((lane & 7) + ((lane >> 3) & 1) * 8) * 32 + (lane >> 4) * 16;
    auto signal = [&](int e) {
      __syncwarp();
      if (lane == 0) mbar_arrive(BAR(B_EV + w * 2 + e));
    };

    float accB[32];
#pragma unroll 1
    for (int t = 0; t < 5; t++) {
      float accA[32];
      const uint32_t ph = t & 1;
      const int kindP = t == 0 ? K_NONE : ((odd && t <= 2) ? K_KV : K_GU);
      const int kindC = odd ? (t < 2 ? K_KV : K_GU) : (t < 4 ? K_GU : K_Q);
      const int slotP = odd ? t - 3 : t - 1, xslotP = odd ? t + 3 : t - 1;
      const int slotC = odd ? t - 2 : t, xslotC = odd ? t + 4 : t;
      static_for<8>([&](auto kc) {
        constexpr int k = decltype(kc)::value;
        mbar_wait(BAR(B_FULL + k), ph);
        wgmma_fence();
        static_for<8>([&](auto kkc) {
          constexpr int kk = decltype(kkc)::value;
          constexpr int i = ((k & 3) * 8 + kk) * 4;
          constexpr uint32_t lo = desc_lo(stage_off(k) + kk * 1024, 8192);
          if constexpr (k < 4) wgmma_n64_rs<((k & 3) | kk) != 0, lo, kHi64>(accA, A[i], A[i + 1], A[i + 2], A[i + 3], dbase);
          else wgmma_n64_rs<((k & 3) | kk) != 0, lo, kHi64>(accB, A[i], A[i + 1], A[i + 2], A[i + 3], dbase);
        });
        wgmma_commit();
        if (k > 0) {
          wgmma_wait<1>();
          release(k - 1);
        }
        if constexpr (k < 4) {
          if (kindP == K_GU) {
            if (k == 1 || k == 2) gu_chunk(accB, k - 1, slotP, xslotP, 1);
          } else if (kindP == K_KV) {
            if (k == 1 || k == 2) kv_stage(accB, k - 1, 1);
            if (k == 3) {
              float kvacc[36];
              const int par = ld_relaxed(&g_epoch) & 1;
              fence_proxy_async();
              bar_sync(1 + w, 128);
              wgmma_fence();
              static_for<4>([&](auto kkc) {
                constexpr int kk = decltype(kkc)::value;
                wgmma_n72_ss_tt<kk != 0, desc_lo(3 * 8192 + kk * 2048, 0), desc_lo(4 * 8192 + kk * 2048, 8192 - kk * 2048)>(kvacc, dbase + w * 4096);
              });
              wgmma_commit();
              wgmma_wait<0>();
              float c[8];
#pragma unroll
              for (int i = 0; i < 8; i++)
                c[i] = wq == 0 ? kvacc[i] : (wq == 1 ? kvacc[8 + i] : (wq == 2 ? kvacc[16 + i] : kvacc[24 + i]));
              const int head = (2 * p + t - 1) * 4 + wq;
              float* kvp = &g_kv[par][head][0][0];
              red_add_v2(kvp + g * 16 + 2 * tq, c[0], c[1]);
              red_add_v2(kvp + (g + 8) * 16 + 2 * tq, c[2], c[3]);
              red_add_v2(kvp + g * 16 + 8 + 2 * tq, c[4], c[5]);
              red_add_v2(kvp + (g + 8) * 16 + 8 + 2 * tq, c[6], c[7]);
              if (tq == 0) {
                red_add(&g_z[par][head][g], kvacc[32]);
                red_add(&g_z[par][head][g + 8], kvacc[34]);
              }
              signal(t - 1);
            }
          }
        } else {
          constexpr int c = k - 4;
          if (kindC == K_GU) {
            if (c < 2) gu_chunk(accA, c, slotC, xslotC, 0);
          } else if (kindC == K_KV) {
            if (c == 0 && t == 0) sts_u4(area + 5 * 8192 + t128 * 16, 0x3F803F80u, 0x3F803F80u, 0x3F803F80u, 0x3F803F80u);
            if (c < 2) kv_stage(accA, c, 0);
          } else {
            if (c == 0) mbar_wait(BAR(B_KVREADY), 0);
            uint32_t b0, b1, b2, b3;
            ldmatrix_x4_trans(kvfrag + c * 512, b0, b1, b2, b3);
            const uint32_t z0 = lds_u32(kvb + 4096 + c * 32 + tq * 4), z1 = lds_u32(kvb + 4096 + c * 32 + 16 + tq * 4);
            q_head(accA, c, 4, b0, b1, b2, b3, z0, z1);
          }
        }
      });
      wgmma_wait<0>();
      release(7);
      PROF(w, 1 + 2 * t);
    }
    if (odd) {
      gu_chunk(accB, 0, 2, 8, 1);
      gu_chunk(accB, 1, 2, 8, 1);
    } else {
      uint32_t Bf[4][6];
#pragma unroll
      for (int c = 0; c < 4; c++) {
        ldmatrix_x4_trans(kvfrag + (4 + c) * 512, Bf[c][0], Bf[c][1], Bf[c][2], Bf[c][3]);
        Bf[c][4] = lds_u32(kvb + 4096 + (4 + c) * 32 + tq * 4);
        Bf[c][5] = lds_u32(kvb + 4096 + (4 + c) * 32 + 16 + tq * 4);
      }
      bar_sync(1 + w, 128);
#pragma unroll
      for (int c = 0; c < 4; c++) q_head(accB, c, 5, Bf[c][0], Bf[c][1], Bf[c][2], Bf[c][3], Bf[c][4], Bf[c][5]);
    }
    PROF(w, 10);

    const int n_own = odd ? 3 : 6;
    auto load_a = [&](int kb) {
      if (kb < n_own) {
#pragma unroll
        for (int jj = 0; jj < 4; jj++) {
          const int i = (kb * 4 + jj) * 4;
          lds_u4(area + kb * 8192 + jj * 2048 + t128 * 16, A[i], A[i + 1], A[i + 2], A[i + 3]);
        }
      } else {
        const int xs = odd ? kb - 3 : kb;
#pragma unroll
        for (int jj = 0; jj < 4; jj++) {
          const int i = (kb * 4 + jj) * 4;
          ldg_poll_u4(&g_xbuf[m][p][xs][w][jj][t128], A[i], A[i + 1], A[i + 2], A[i + 3]);
        }
      }
    };
    auto fix_a = [&](int kb) {
      if (kb >= n_own) {
        const int xs = odd ? kb - 3 : kb;
        recv_group<4>(&g_xbuf[m][p][xs][w][0][t128], &A[kb * 16]);
      }
    };
#pragma unroll
    for (int kb = 0; kb < 7; kb++) load_a(kb);
    PROF(w, 11);

    const int orow = m * 128 + w * 64 + wq * 16 + g;
    const int ocol = odd * 256 + p * 64 + 2 * tq;
    float acc2[2][32];
    uint32_t P[3][32];
    uint32_t xr[16];
    auto send = [&](float (&acc)[32], int bi) {
      uint4* dst = &g_pbuf[m][odd][(p + 1 + bi) & 3][bi][w][0][t128];
#pragma unroll
      for (int q = 0; q < 8; q++)
        send_u4(dst + q * 128, __float_as_uint(acc[q * 4]), __float_as_uint(acc[q * 4 + 1]), __float_as_uint(acc[q * 4 + 2]), __float_as_uint(acc[q * 4 + 3]));
      PROF(w, 12 + 2 * bi);
    };
    auto fetch = [&](int sl) {
#pragma unroll
      for (int q = 0; q < 8; q++) ldg_poll_u4(&g_pbuf[m][odd][p][sl][w][q][t128], P[sl][q * 4], P[sl][q * 4 + 1], P[sl][q * 4 + 2], P[sl][q * 4 + 3]);
    };
    static_for<36>([&](auto ic) {
      constexpr int i = decltype(ic)::value, bi = p2_bi(i), kb = p2_kb(i), j = i >> 1, st = j & 7;
      if (i == 9) { load_a(7); load_a(8); }
      if (bi == 0 && kb >= 3) fix_a(kb);
      if ((i & 1) == 0) mbar_wait(BAR(B_FULL + st), (5 + (j >> 3)) & 1);
      wgmma_fence();
      static_for<4>([&](auto kkc) {
        constexpr int kk = decltype(kkc)::value, a = (kb * 4 + kk) * 4;
        wgmma_n64_rs<(kb | kk) != 0, desc_lo(stage_off(st) + (i & 1) * 8192 + kk * 2048, 0), kHi128>(acc2[bi & 1], A[a], A[a + 1], A[a + 2], A[a + 3], dbase);
      });
      wgmma_commit();
      if (i > 0) {
        wgmma_wait<1>();
        if ((i & 1) == 0 && j - 1 <= 9) release((j - 1) & 7);
      }
      if constexpr (i == 16) send(acc2[0], 0);
      if constexpr (i == 18) send(acc2[1], 1);
      if constexpr (i == 27) send(acc2[0], 2);
      if constexpr (i == 29) fetch(0);
      if constexpr (i == 31) fetch(1);
      if constexpr (i == 32) {
#pragma unroll
        for (int q = 0; q < 8; q++) {
          xr[2 * q] = __ldg((const uint32_t*)(x + (size_t)orow * kD + ocol + q * 8));
          xr[2 * q + 1] = __ldg((const uint32_t*)(x + (size_t)(orow + 8) * kD + ocol + q * 8));
        }
      }
      if constexpr (i == 34) fetch(2);
    });
#pragma unroll
    for (int sl = 0; sl < 3; sl++) recv_group<8>(&g_pbuf[m][odd][p][sl][w][0][t128], &P[sl][0]);
    wgmma_wait<0>();
    PROF(w, 18);
#pragma unroll
    for (int q = 0; q < 8; q++) {
      float rr[4];
#pragma unroll
      for (int e = 0; e < 4; e++)
        rr[e] = acc2[1][q * 4 + e] + __uint_as_float(P[0][q * 4 + e]) + __uint_as_float(P[1][q * 4 + e]) + __uint_as_float(P[2][q * 4 + e]);
      rr[0] += __uint_as_float(xr[2 * q] << 16);
      rr[1] += __uint_as_float(xr[2 * q] & 0xffff0000u);
      rr[2] += __uint_as_float(xr[2 * q + 1] << 16);
      rr[3] += __uint_as_float(xr[2 * q + 1] & 0xffff0000u);
      *(uint32_t*)(out + (size_t)orow * kD + ocol + q * 8) = pack_bf16(rr[0], rr[1]);
      *(uint32_t*)(out + (size_t)(orow + 8) * kD + ocol + q * 8) = pack_bf16(rr[2], rr[3]);
    }
    PROF(w, 19);
    if (tid == 0) {
      const uint32_t old = atomicAdd(&g_done, 1u);
      if ((old & 127u) == 127u) st_relaxed(&g_epoch, ld_relaxed(&g_epoch) + 1u);
    }
  }
#undef BAR
}

typedef CUresult (*EncodeFn)(CUtensorMap*, CUtensorMapDataType, cuuint32_t, void*, const cuuint64_t*, const cuuint64_t*,
                             const cuuint32_t*, const cuuint32_t*, CUtensorMapInterleave, CUtensorMapSwizzle,
                             CUtensorMapL2promotion, CUtensorMapFloatOOBfill);

void make_map(EncodeFn enc, CUtensorMap* tm, const void* ptr, int rows, int cols, bool narrow) {
  cuuint64_t gd[2] = {(cuuint64_t)cols, (cuuint64_t)rows};
  cuuint64_t gs[1] = {(cuuint64_t)cols * 2};
  cuuint32_t bd[2] = {narrow ? 32u : 64u, narrow ? 128u : 64u};
  cuuint32_t es[2] = {1, 1};
  enc(tm, CU_TENSOR_MAP_DATA_TYPE_BFLOAT16, 2, const_cast<void*>(ptr), gd, gs, bd, es, CU_TENSOR_MAP_INTERLEAVE_NONE,
      narrow ? CU_TENSOR_MAP_SWIZZLE_64B : CU_TENSOR_MAP_SWIZZLE_128B, CU_TENSOR_MAP_L2_PROMOTION_L2_256B, CU_TENSOR_MAP_FLOAT_OOB_FILL_NONE);
}

}

extern "C" void kernel_launch(void* const* d_in, const int* in_sizes, int n_in, void* d_out, int out_size) {
  static EncodeFn enc = nullptr;
  if (!enc) {
    void* fn = nullptr;
    cudaDriverEntryPointQueryResult qr;
    cudaGetDriverEntryPoint("cuTensorMapEncodeTiled", &fn, cudaEnableDefault, &qr);
    enc = (EncodeFn)fn;
    cudaFuncSetAttribute(fused_kernel, cudaFuncAttributeMaxDynamicSharedMemorySize, kSmemBytes);
  }
  CUtensorMap tm_x, tm_wqkv, tm_w1, tm_w3, tm_w2, tm_wo;
  make_map(enc, &tm_x, d_in[0], kS, kD, false);
  make_map(enc, &tm_wqkv, d_in[1], kD, 3 * kD, true);
  make_map(enc, &tm_wo, d_in[2], kD, kD, false);
  make_map(enc, &tm_w1, d_in[4], kD, kF, true);
  make_map(enc, &tm_w3, d_in[5], kD, kF, true);
  make_map(enc, &tm_w2, d_in[6], kF, kD, false);
  fused_kernel<<<128, 384, kSmemBytes>>>(tm_x, tm_wqkv, tm_w1, tm_w3, tm_w2, tm_wo, (const __nv_bfloat16*)d_in[0],
                                         (__nv_bfloat16*)d_out);
}
```

```cpp
#include <cuda_runtime.h>
#include <cuda_bf16.h>
#include <cuda.h>
#include <stdint.h>

namespace {

constexpr int kS = 2048, kD = 512, kF = 1792;
constexpr uint32_t kSpinLimit = 1u << 22;

__device__ uint4    g_xbuf[16][4][9][2][4][128];
__device__ uint4    g_pbuf[16][2][4][3][2][8][128];
__device__ float    g_kv[2][32][16][16];
__device__ float    g_z[2][32][16];
__device__ uint32_t g_kvcnt[4][32];
__device__ uint32_t g_epoch;
__device__ uint32_t g_done;
#define PROF(wg, i) do {} while (0)

__device__ __forceinline__ uint32_t smem_u32(const void* p) { return (uint32_t)__cvta_generic_to_shared(p); }
__device__ __forceinline__ void mbar_init(uint32_t bar, uint32_t cnt) {
  asm volatile("mbarrier.init.shared::cta.b64 [%0], %1;" ::"r"(bar), "r"(cnt) : "memory");
}
__device__ __forceinline__ void mbar_expect_tx(uint32_t bar, uint32_t bytes) {
  asm volatile("mbarrier.arrive.expect_tx.shared::cta.b64 _, [%0], %1;" ::"r"(bar), "r"(bytes) : "memory");
}
__device__ __forceinline__ void mbar_arrive(uint32_t bar) {
  asm volatile("mbarrier.arrive.shared::cta.b64 _, [%0];" ::"r"(bar) : "memory");
}
__device__ __forceinline__ void mbar_wait(uint32_t bar, uint32_t parity) {
  asm volatile(
      "{\n.reg .pred p;\n"
      "LAB_WAIT:\n"
      "mbarrier.try_wait.parity.shared::cta.b64 p, [%0], %1;\n"
      "@p bra DONE;\n"
      "bra LAB_WAIT;\n"
      "DONE:\n}" ::"r"(bar), "r"(parity) : "memory");
}
__device__ __forceinline__ void tma_load_2d(uint32_t dst, const CUtensorMap* tm, uint32_t bar, int c0, int c1) {
  asm volatile(
      "cp.async.bulk.tensor.2d.shared::cluster.global.mbarrier::complete_tx::bytes [%0], [%1, {%3, %4}], [%2];" ::"r"(dst),
      "l"(tm), "r"(bar), "r"(c0), "r"(c1)
      : "memory");
}
__device__ __forceinline__ void tma_load_2d_mc(uint32_t dst, const CUtensorMap* tm, uint32_t bar, int c0, int c1) {
  asm volatile(
      "cp.async.bulk.tensor.2d.shared::cluster.global.mbarrier::complete_tx::bytes.multicast::cluster [%0], [%1, {%3, %4}], [%2], %5;" ::"r"(dst),
      "l"(tm), "r"(bar), "r"(c0), "r"(c1), "h"((uint16_t)3)
      : "memory");
}
__device__ __forceinline__ void mbar_arrive_cluster(uint32_t bar, uint32_t cta) {
  asm volatile("{\n.reg .b32 ra;\nmapa.shared::cluster.u32 ra, %0, %1;\nmbarrier.arrive.shared::cluster.b64 _, [ra];\n}" ::"r"(bar), "r"(cta) : "memory");
}
__device__ __forceinline__ void prefetch_tmap(const CUtensorMap* tm) {
  asm volatile("prefetch.tensormap [%0];" ::"l"(tm) : "memory");
}
__device__ __forceinline__ void wgmma_fence() { asm volatile("wgmma.fence.sync.aligned;" ::: "memory"); }
__device__ __forceinline__ void wgmma_commit() { asm volatile("wgmma.commit_group.sync.aligned;" ::: "memory"); }
template <int N>
__device__ __forceinline__ void wgmma_wait() { asm volatile("wgmma.wait_group.sync.aligned %0;" ::"n"(N) : "memory"); }
__device__ __forceinline__ void bar_sync(int id, int n) { asm volatile("bar.sync %0, %1;" ::"r"(id), "r"(n) : "memory"); }
__device__ __forceinline__ void bar_arrive(int id, int n) { asm volatile("bar.arrive %0, %1;" ::"r"(id), "r"(n) : "memory"); }
__device__ __forceinline__ void fence_proxy_async() { asm volatile("fence.proxy.async.shared::cta;" ::: "memory"); }

__device__ __forceinline__ uint32_t ld_acquire(const uint32_t* p) {
  uint32_t v;
  asm volatile("ld.acquire.gpu.global.u32 %0, [%1];" : "=r"(v) : "l"(p) : "memory");
  return v;
}
__device__ __forceinline__ uint32_t ld_relaxed(const uint32_t* p) {
  uint32_t v;
  asm volatile("ld.relaxed.gpu.global.u32 %0, [%1];" : "=r"(v) : "l"(p));
  return v;
}
__device__ __forceinline__ void cluster_wait() { asm volatile("barrier.cluster.wait.aligned;" ::: "memory"); }
__device__ __forceinline__ void st_relaxed(uint32_t* p, uint32_t v) {
  asm volatile("st.relaxed.gpu.global.u32 [%0], %1;" ::"l"(p), "r"(v) : "memory");
}
__device__ __forceinline__ void wait_flag_eq(const uint32_t* p, uint32_t val) {
  uint32_t it = 0;
  while (ld_acquire(p) != val) {
    if (++it > kSpinLimit) break;
  }
}
__device__ __forceinline__ void wait_count_ge(const uint32_t* p, uint32_t val) {
  uint32_t it = 0;
  while ((int32_t)(ld_acquire(p) - val) < 0) {
    __nanosleep(64);
    if (++it > kSpinLimit) break;
  }
}
__device__ __forceinline__ void ldg_poll_u4(const void* p, uint32_t& a, uint32_t& b, uint32_t& c, uint32_t& d) {
  asm volatile("ld.relaxed.gpu.global.v4.u32 {%0,%1,%2,%3}, [%4];" : "=r"(a), "=r"(b), "=r"(c), "=r"(d) : "l"(p) : "memory");
}
template <int N>
__device__ __forceinline__ void recv_group(uint4* p, uint32_t* r) {
  uint32_t it = 0;
  while (true) {
    uint32_t mn = 0xffffffffu;
#pragma unroll
    for (int i = 0; i < 4 * N; i++) mn = min(mn, r[i]);
    if (!__any_sync(0xffffffffu, mn == 0u) || ++it > kSpinLimit) break;
#pragma unroll
    for (int q = 0; q < N; q++) ldg_poll_u4(p + q * 128, r[q * 4], r[q * 4 + 1], r[q * 4 + 2], r[q * 4 + 3]);
  }
#pragma unroll
  for (int i = 0; i < 4 * N; i++) r[i] = ~r[i];
#pragma unroll
  for (int q = 0; q < N; q++) asm volatile("st.global.v4.u32 [%0], {%1,%1,%1,%1};" ::"l"(p + q * 128), "r"(0u) : "memory");
}
__device__ __forceinline__ float4 ldg_cg_f4(const void* p) {
  float4 v;
  asm volatile("ld.global.cg.v4.f32 {%0,%1,%2,%3}, [%4];" : "=f"(v.x), "=f"(v.y), "=f"(v.z), "=f"(v.w) : "l"(p) : "memory");
  return v;
}
__device__ __forceinline__ void stg_u4(void* p, uint32_t a, uint32_t b, uint32_t c, uint32_t d) {
  asm volatile("st.global.v4.u32 [%0], {%1,%2,%3,%4};" ::"l"(p), "r"(a), "r"(b), "r"(c), "r"(d) : "memory");
}
__device__ __forceinline__ void stg_f4(void* p, float a, float b, float c, float d) {
  asm volatile("st.global.v4.f32 [%0], {%1,%2,%3,%4};" ::"l"(p), "f"(a), "f"(b), "f"(c), "f"(d) : "memory");
}
__device__ __forceinline__ void sts_u4(uint32_t addr, uint32_t a, uint32_t b, uint32_t c, uint32_t d) {
  asm volatile("st.shared.v4.u32 [%0], {%1,%2,%3,%4};" ::"r"(addr), "r"(a), "r"(b), "r"(c), "r"(d) : "memory");
}
__device__ __forceinline__ void lds_u4(uint32_t addr, uint32_t& a, uint32_t& b, uint32_t& c, uint32_t& d) {
  asm volatile("ld.shared.v4.u32 {%0,%1,%2,%3}, [%4];" : "=r"(a), "=r"(b), "=r"(c), "=r"(d) : "r"(addr) : "memory");
}
__device__ __forceinline__ uint32_t lds_u32(uint32_t addr) {
  uint32_t v;
  asm volatile("ld.shared.u32 %0, [%1];" : "=r"(v) : "r"(addr) : "memory");
  return v;
}
__device__ __forceinline__ void ldmatrix_x4(uint32_t addr, uint32_t& a, uint32_t& b, uint32_t& c, uint32_t& d) {
  asm volatile("ldmatrix.sync.aligned.m8n8.x4.shared.b16 {%0,%1,%2,%3}, [%4];" : "=r"(a), "=r"(b), "=r"(c), "=r"(d) : "r"(addr) : "memory");
}
__device__ __forceinline__ void ldmatrix_x4_trans(uint32_t addr, uint32_t& a, uint32_t& b, uint32_t& c, uint32_t& d) {
  asm volatile("ldmatrix.sync.aligned.m8n8.x4.trans.shared.b16 {%0,%1,%2,%3}, [%4];" : "=r"(a), "=r"(b), "=r"(c), "=r"(d) : "r"(addr) : "memory");
}
__device__ __forceinline__ void stmatrix_x4(uint32_t addr, uint32_t a, uint32_t b, uint32_t c, uint32_t d) {
  asm volatile("stmatrix.sync.aligned.m8n8.x4.shared.b16 [%0], {%1,%2,%3,%4};" ::"r"(addr), "r"(a), "r"(b), "r"(c), "r"(d) : "memory");
}
__device__ __forceinline__ void mma_16816(float (&c)[4], uint32_t a0, uint32_t a1, uint32_t a2, uint32_t a3, uint32_t b0, uint32_t b1) {
  asm volatile(
      "mma.sync.aligned.m16n8k16.row.col.f32.bf16.bf16.f32 {%0,%1,%2,%3}, {%4,%5,%6,%7}, {%8,%9}, {%0,%1,%2,%3};"
      : "+f"(c[0]), "+f"(c[1]), "+f"(c[2]), "+f"(c[3])
      : "r"(a0), "r"(a1), "r"(a2), "r"(a3), "r"(b0), "r"(b1));
}
__device__ __forceinline__ uint32_t pack_bf16(float lo, float hi) {
  uint32_t r;
  asm("cvt.rn.bf16x2.f32 %0, %1, %2;" : "=r"(r) : "f"(hi), "f"(lo));
  return r;
}
__device__ __forceinline__ uint32_t hsub2_bf16(uint32_t a, uint32_t b) {
  uint32_t r;
  asm("sub.rn.bf16x2 %0, %1, %2;" : "=r"(r) : "r"(a), "r"(b));
  return r;
}
__device__ __forceinline__ float ex2f(float x) {
  float r;
  asm("ex2.approx.ftz.f32 %0, %1;" : "=f"(r) : "f"(x));
  return r;
}
__device__ __forceinline__ float rcpf(float x) {
  float r;
  asm("rcp.approx.ftz.f32 %0, %1;" : "=f"(r) : "f"(x));
  return r;
}
__device__ __forceinline__ void red_add_v2(float* p, float a, float b) {
  asm volatile("red.relaxed.gpu.global.add.v2.f32 [%0], {%1,%2};" ::"l"(p), "f"(a), "f"(b) : "memory");
}
__device__ __forceinline__ void red_add(float* p, float a) {
  asm volatile("red.relaxed.gpu.global.add.f32 [%0], %1;" ::"l"(p), "f"(a) : "memory");
}
__device__ __forceinline__ float phi_f(float t) {
  float e = ex2f(t * 1.4426950408889634f);
  return (t > 0.f ? t + 1.f : e) + 1e-6f;
}

#define R8(a, o) "+f"(a[o + 0]), "+f"(a[o + 1]), "+f"(a[o + 2]), "+f"(a[o + 3]), "+f"(a[o + 4]), "+f"(a[o + 5]), "+f"(a[o + 6]), "+f"(a[o + 7])

#define W8(a, o) "=f"(a[o + 0]), "=f"(a[o + 1]), "=f"(a[o + 2]), "=f"(a[o + 3]), "=f"(a[o + 4]), "=f"(a[o + 5]), "=f"(a[o + 6]), "=f"(a[o + 7])
#define D32 "{%0,%1,%2,%3,%4,%5,%6,%7,%8,%9,%10,%11,%12,%13,%14,%15,%16,%17,%18,%19,%20,%21,%22,%23,%24,%25,%26,%27,%28,%29,%30,%31}"
#define D36 "{%0,%1,%2,%3,%4,%5,%6,%7,%8,%9,%10,%11,%12,%13,%14,%15,%16,%17,%18,%19,%20,%21,%22,%23,%24,%25,%26,%27,%28,%29,%30,%31,%32,%33,%34,%35}"

constexpr uint32_t kHi128 = (1024u >> 4) | (1u << 30);
constexpr uint32_t kHi64 = (512u >> 4) | (2u << 30);
__host__ __device__ constexpr uint32_t desc_lo(uint32_t off, uint32_t lbo) { return (off >> 4) | ((lbo >> 4) << 16); }

template <bool ACC, uint32_t LO, uint32_t HI>
__device__ __forceinline__ void wgmma_n64_rs(float (&d)[32], uint32_t a0, uint32_t a1, uint32_t a2, uint32_t a3, uint32_t base) {
  if (ACC) {
    asm volatile(
        "{\n.reg .pred p;\n.reg .b32 lo;\n.reg .b64 dd;\nsetp.eq.b32 p, 0, 0;\nadd.u32 lo, %36, %37;\nmov.b64 dd, {lo, %38};\n"
        "wgmma.mma_async.sync.aligned.m64n64k16.f32.bf16.bf16 " D32 ", {%32,%33,%34,%35}, dd, p, 1, 1, 1;\n}"
        : R8(d, 0), R8(d, 8), R8(d, 16), R8(d, 24)
        : "r"(a0), "r"(a1), "r"(a2), "r"(a3), "r"(base), "n"(LO), "n"(HI));
  } else {
    asm volatile(
        "{\n.reg .pred p;\n.reg .b32 lo;\n.reg .b64 dd;\nsetp.ne.b32 p, 0, 0;\nadd.u32 lo, %36, %37;\nmov.b64 dd, {lo, %38};\n"
        "wgmma.mma_async.sync.aligned.m64n64k16.f32.bf16.bf16 " D32 ", {%32,%33,%34,%35}, dd, p, 1, 1, 1;\n}"
        : W8(d, 0), W8(d, 8), W8(d, 16), W8(d, 24)
        : "r"(a0), "r"(a1), "r"(a2), "r"(a3), "r"(base), "n"(LO), "n"(HI));
  }
}
template <bool ACC, uint32_t LOA, uint32_t LOB>
__device__ __forceinline__ void wgmma_n72_ss_tt(float (&d)[36], uint32_t base) {
  if (ACC) {
    asm volatile(
        "{\n.reg .pred p;\n.reg .b32 lo;\n.reg .b64 da, db;\nsetp.eq.b32 p, 0, 0;\n"
        "add.u32 lo, %36, %37;\nmov.b64 da, {lo, %39};\nadd.u32 lo, %36, %38;\nmov.b64 db, {lo, %39};\n"
        "wgmma.mma_async.sync.aligned.m64n72k16.f32.bf16.bf16 " D36 ", da, db, p, 1, 1, 1, 1;\n}"
        : R8(d, 0), R8(d, 8), R8(d, 16), R8(d, 24), "+f"(d[32]), "+f"(d[33]), "+f"(d[34]), "+f"(d[35])
        : "r"(base), "n"(LOA), "n"(LOB), "n"(kHi128));
  } else {
    asm volatile(
        "{\n.reg .pred p;\n.reg .b32 lo;\n.reg .b64 da, db;\nsetp.ne.b32 p, 0, 0;\n"
        "add.u32 lo, %36, %37;\nmov.b64 da, {lo, %39};\nadd.u32 lo, %36, %38;\nmov.b64 db, {lo, %39};\n"
        "wgmma.mma_async.sync.aligned.m64n72k16.f32.bf16.bf16 " D36 ", da, db, p, 1, 1, 1, 1;\n}"
        : W8(d, 0), W8(d, 8), W8(d, 16), W8(d, 24), "=f"(d[32]), "=f"(d[33]), "=f"(d[34]), "=f"(d[35])
        : "r"(base), "n"(LOA), "n"(LOB), "n"(kHi128));
  }
}

#define INL __attribute__((always_inline))
template <int V> struct IC { static constexpr int value = V; };
template <int N, int I = 0, typename F>
__device__ __forceinline__ void static_for(F&& f) {
  if constexpr (I < N) { f(IC<I>{}); static_for<N, I + 1>(f); }
}

__host__ __device__ constexpr uint32_t stage_off(int st) {
  return st < 6 ? 131072u + (uint32_t)st * 16384u : (uint32_t)(st - 6) * 65536u + 49152u;
}

constexpr int B_FULL = 0, B_EMPTY = 8, B_XFULL = 16, B_XDONE = 32, B_KVREADY = 33, B_EV = 34, B_COUNT = 38;
constexpr uint32_t kBarOff = 229376;
constexpr int kSmemBytes = 229376 + 1024;

__host__ __device__ constexpr int p2_bi(int i) { return i < 7 ? 0 : i < 14 ? 1 : i < 16 ? 0 : i < 18 ? 1 : i / 9; }
__host__ __device__ constexpr int p2_kb(int i) { return i < 7 ? i : i < 14 ? i - 7 : i < 16 ? i - 7 : i < 18 ? i - 9 : i % 9; }

enum { K_NONE = 0, K_GU = 1, K_KV = 2, K_Q = 3 };

__global__ void __cluster_dims__(2, 1, 1) __launch_bounds__(384, 1)
fused_kernel(const __grid_constant__ CUtensorMap tm_x, const __grid_constant__ CUtensorMap tm_wqkv,
             const __grid_constant__ CUtensorMap tm_w1, const __grid_constant__ CUtensorMap tm_w3,
             const __grid_constant__ CUtensorMap tm_w2, const __grid_constant__ CUtensorMap tm_wo,
             const __nv_bfloat16* __restrict__ x, __nv_bfloat16* __restrict__ out) {
  extern __shared__ __align__(1024) uint8_t smem_raw[];
  const uint32_t sbase = smem_u32(smem_raw);
  const uint32_t bars = sbase + kBarOff;
  const int tid = threadIdx.x, lane = tid & 31;
  const int warp = __shfl_sync(0xffffffffu, tid >> 5, 0);
  const int cr = blockIdx.x & 1;
  const int r = (blockIdx.x >> 1) & 7, m = ((blockIdx.x >> 4) << 1) | cr, p = r >> 1, odd = r & 1;
#define BAR(i) (bars + 8u * (uint32_t)(i))
  if (tid == 256) {
    if (sbase & 1023u) __trap();
#pragma unroll
    for (int i = 0; i < 16; i++) mbar_init(BAR(B_XFULL + i), 1);
    fence_proxy_async();
#pragma unroll
    for (int b = 0; b < 16; b++) {
      mbar_expect_tx(BAR(B_XFULL + b), 8192);
      tma_load_2d(sbase + (b >> 3) * 65536 + (b & 7) * 8192, &tm_x, BAR(B_XFULL + b), (b & 7) * 64, m * 128 + (b >> 3) * 64);
    }
#pragma unroll
    for (int i = 0; i < 8; i++) { mbar_init(BAR(B_FULL + i), 1); mbar_init(BAR(B_EMPTY + i), 4); }
#pragma unroll
    for (int i = 0; i < 4; i++) mbar_init(BAR(B_EV + i), 4);
    mbar_init(BAR(B_XDONE), 2);
    mbar_init(BAR(B_KVREADY), 1);
    asm volatile("fence.mbarrier_init.release.cluster;" ::: "memory");
    fence_proxy_async();
  } else if (tid == 288) {
    prefetch_tmap(odd ? &tm_wqkv : (cr ? &tm_w3 : &tm_w1));
  }
  __syncwarp();
  asm volatile("barrier.cluster.arrive.relaxed.aligned;" ::: "memory");
  PROF((tid >> 7), 21);
  __syncthreads();

  if (warp >= 8) {
    asm volatile("setmaxnreg.dec.sync.aligned.u32 24;");
    PROF(2, 3);
    cluster_wait();
    PROF(2, 2);
    const uint32_t epoch = warp == 8 ? 0u : ld_relaxed(&g_epoch);
    const uint32_t tag = epoch + 1u;
    const int par = epoch & 1;
    if (warp == 8) {
      if (lane == 0) {
        for (int j = 0; j < 10; j++) {
          const CUtensorMap* tm;
          int col;
          if (!odd) {
            if (j < 8) { tm = cr ? &tm_w3 : &tm_w1; col = 7 * p * 64 + j * 32; }
            else { tm = &tm_wqkv; col = 128 * p + (j - 8) * 64 + cr * 32; }
          } else {
            if (j < 4) { tm = &tm_wqkv; col = 512 + cr * 512 + 128 * p + j * 32; }
            else { tm = cr ? &tm_w3 : &tm_w1; col = (7 * p + 4) * 64 + (j - 4) * 32; }
          }
          const int t = j >> 1;
          for (int kq = 0; kq < 4; kq++) {
            const int k = (j & 1) * 4 + kq;
            mbar_wait(BAR(B_EMPTY + k), k < 6 ? ((t & 1) ^ 1) : (t & 1));
            mbar_expect_tx(BAR(B_FULL + k), 16384);
            tma_load_2d_mc(sbase + stage_off(k) + cr * 8192, tm, BAR(B_FULL + k), col, kq * 128);
          }
        }
        for (int j = 0; j < 18; j++) {
          const int st = j & 7, n = 5 + (j >> 3);
          const int i = 2 * j + cr;
          const int bi = p2_bi(i), kb = p2_kb(i);
          const int col = odd * 256 + ((p + 1 + bi) & 3) * 64;
          const CUtensorMap* tmk;
          int row;
          if (!odd) {
            if (kb < 4) { tmk = &tm_w2; row = (7 * p + kb) * 64; }
            else if (kb < 6) { tmk = &tm_wo; row = (2 * p + kb - 4) * 64; }
            else { tmk = &tm_w2; row = (7 * p + 4 + kb - 6) * 64; }
          } else {
            if (kb < 3) { tmk = &tm_w2; row = (7 * p + 4 + kb) * 64; }
            else if (kb < 7) { tmk = &tm_w2; row = (7 * p + kb - 3) * 64; }
            else { tmk = &tm_wo; row = (2 * p + kb - 7) * 64; }
          }
          mbar_wait(BAR(B_EMPTY + st), st < 6 ? ((n & 1) ^ 1) : (n & 1));
          mbar_expect_tx(BAR(B_FULL + st), 16384);
          tma_load_2d_mc(sbase + stage_off(st) + cr * 8192, tmk, BAR(B_FULL + st), col, row);
        }
      }
    } else if (warp <= 10) {
      if (lane == 0 && odd) {
        const int w = warp - 9;
        for (int e = 0; e < 2; e++) {
          mbar_wait(BAR(B_EV + w * 2 + e), 0);
          __threadfence();
          atomicAdd(&g_kvcnt[p][0], 1u);
        }
      }
    } else {
      if (!odd) {
        {
          const int ce = m * 4 + p;
          float* kvn = &g_kv[par ^ 1][0][0][0];
          for (int i = lane; i < 128; i += 32) kvn[ce * 128 + i] = 0.f;
          if (lane < 8) (&g_z[par ^ 1][0][0])[ce * 8 + lane] = 0.f;
        }
        mbar_wait(BAR(B_XDONE), 0);
        wait_count_ge(&g_kvcnt[p][0], 64u * tag);
        const float* kvp = &g_kv[par][8 * p][0][0];
        const uint32_t dst0 = sbase + 5 * 8192, dst1 = dst0 + 65536;
#pragma unroll 4
        for (int i = 0; i < 16; i++) {
          float4 v = ldg_cg_f4(kvp + (i * 32 + lane) * 4);
          uint32_t lo = pack_bf16(v.x, v.y), hi = pack_bf16(v.z, v.w);
          uint32_t off = (uint32_t)(i * 32 + lane) * 8u;
          asm volatile("st.shared.v2.u32 [%0], {%1,%2};" ::"r"(dst0 + off), "r"(lo), "r"(hi) : "memory");
          asm volatile("st.shared.v2.u32 [%0], {%1,%2};" ::"r"(dst1 + off), "r"(lo), "r"(hi) : "memory");
        }
        {
          float4 v = ldg_cg_f4(&g_z[par][8 * p][0] + lane * 4);
          uint32_t lo = pack_bf16(v.x, v.y), hi = pack_bf16(v.z, v.w);
          uint32_t off = 4096u + (uint32_t)lane * 8u;
          asm volatile("st.shared.v2.u32 [%0], {%1,%2};" ::"r"(dst0 + off), "r"(lo), "r"(hi) : "memory");
          asm volatile("st.shared.v2.u32 [%0], {%1,%2};" ::"r"(dst1 + off), "r"(lo), "r"(hi) : "memory");
        }
        __syncwarp();
        if (lane == 0) mbar_arrive(BAR(B_KVREADY));
      }
    }
  } else {
    asm volatile("setmaxnreg.inc.sync.aligned.u32 240;");
    const int w = warp >> 2, wq = warp & 3, t128 = tid & 127;
    const int g = lane >> 2, tq = lane & 3;
    const uint32_t area = sbase + (uint32_t)w * 65536u;
    const bool elect = (t128 == 0);
    PROF(w, 22);
    const uint32_t dbase = (sbase & 0x3FFFFu) >> 4;
    uint32_t xoff = (uint32_t)((m * 4 + p) * 18 + w) * 8192u + (uint32_t)t128 * 16u;
    uint32_t stash = area + (uint32_t)t128 * 16u;
    asm volatile("" : "+r"(xoff), "+r"(stash));
    auto xptr = [&](int slot, int jj) INL { return (uint4*)((char*)g_xbuf + (xoff + (uint32_t)slot * 16384u + (uint32_t)jj * 2048u)); };
    uint32_t A[144];
    float rs0, rs1;
    auto release = [&](int st) INL {
      if (elect) { mbar_arrive_cluster(BAR(B_EMPTY + st), 0); mbar_arrive_cluster(BAR(B_EMPTY + st), 1); }
    };

    {
      const int row = wq * 16 + (lane & 7) + ((lane >> 3) & 1) * 8;
      const uint32_t rbase = area + row * 128;
      float s0[2][4] = {}, q0[2][4] = {}, q1[2][4] = {};
      const uint32_t ones = 0x3F803F80u;
#pragma unroll
      for (int b = 0; b < 8; b++) {
        mbar_wait(BAR(B_XFULL + w * 8 + b), 0);
        if (b == 0) PROF(w, 23);
        if (b == 7) PROF(w, 24);
#pragma unroll
        for (int kk = 0; kk < 4; kk++) {
          const int i = (b * 4 + kk) * 4;
          ldmatrix_x4(rbase + b * 8192 + (((kk * 2 + (lane >> 4)) ^ (row & 7)) << 4), A[i], A[i + 1], A[i + 2], A[i + 3]);
        }
#pragma unroll
        for (int kk = 0; kk < 4; kk++) {
          const int i = (b * 4 + kk) * 4;
          mma_16816(s0[kk & 1], A[i], A[i + 1], A[i + 2], A[i + 3], ones, ones);
          mma_16816(q0[kk & 1], A[i], A[i + 1], A[i + 2], A[i + 3], A[i], A[i + 2]);
          mma_16816(q1[kk & 1], A[i], A[i + 1], A[i + 2], A[i + 3], A[i + 1], A[i + 3]);
        }
      }
      const float mean0 = (s0[0][0] + s0[1][0]) * (1.f / 512.f), mean1 = (s0[0][2] + s0[1][2]) * (1.f / 512.f);
      const uint32_t m0 = pack_bf16(mean0, mean0), m1 = pack_bf16(mean1, mean1);
#pragma unroll
      for (int i = 0; i < 128; i += 2) {
        A[i] = hsub2_bf16(A[i], m0);
        A[i + 1] = hsub2_bf16(A[i + 1], m1);
      }
      float v0 = (g & 1) ? q0[0][1] + q0[1][1] : q0[0][0] + q0[1][0];
      float v1 = (g & 1) ? q1[0][3] + q1[1][3] : q1[0][2] + q1[1][2];
      const int src = 4 * g + (g >> 1);
      v0 = __shfl_sync(0xffffffffu, v0, src);
      v1 = __shfl_sync(0xffffffffu, v1, src);
      v0 = fmaxf(v0 * (1.f / 512.f) - mean0 * mean0, 0.f);
      v1 = fmaxf(v1 * (1.f / 512.f) - mean1 * mean1, 0.f);
      rs0 = rsqrtf(v0 + 1e-5f);
      rs1 = rsqrtf(v1 + 1e-5f);
      bar_sync(1 + w, 128);
      cluster_wait();
      PROF(w, 0);
      release(6); release(7);
      if (elect) mbar_arrive(BAR(B_XDONE));
    }

    auto gu_chunk = [&](float (&acc)[32], int f, int slot, int xslot, int hb) INL {
      const float c0 = rs0 * -1.4426950408889634f, c1 = rs1 * -1.4426950408889634f;
      const float q0 = rs0 * rs0, q1 = rs1 * rs1;
      uint32_t h[4];
#pragma unroll
      for (int i = 0; i < 4; i++) {
        const float ga = acc[f * 8 + 2 * i], gb = acc[f * 8 + 2 * i + 1];
        const float ua = acc[16 + f * 8 + 2 * i], ub = acc[16 + f * 8 + 2 * i + 1];
        const float c = (i & 1) ? c1 : c0, q = (i & 1) ? q1 : q0;
        const float da = 1.f + ex2f(fminf(ga * c, 60.f)), db = 1.f + ex2f(fminf(gb * c, 60.f));
        const float rq = rcpf(da * db) * q;
        h[i] = ~pack_bf16(ga * ua * (db * rq), gb * ub * (da * rq));
      }
      const int jj = hb * 2 + f;
      sts_u4(stash + slot * 8192 + jj * 2048, h[0], h[1], h[2], h[3]);
      stg_u4(xptr(xslot, jj), h[0], h[1], h[2], h[3]);
    };
    auto kv_stage = [&](float (&acc)[32], int c, int hb) INL {
      const int srow = wq * 16 + (lane & 7) + ((lane >> 3) & 1) * 8;
      const uint32_t base = area + (3 + c) * 8192 + srow * 128;
#pragma unroll
      for (int jj = 0; jj < 2; jj++) {
        const int a = c * 16 + jj * 8;
        uint32_t r0, r1, r2, r3;
        if (c == 0) {
          r0 = pack_bf16(phi_f(acc[a] * rs0), phi_f(acc[a + 1] * rs0));
          r1 = pack_bf16(phi_f(acc[a + 2] * rs1), phi_f(acc[a + 3] * rs1));
          r2 = pack_bf16(phi_f(acc[a + 4] * rs0), phi_f(acc[a + 5] * rs0));
          r3 = pack_bf16(phi_f(acc[a + 6] * rs1), phi_f(acc[a + 7] * rs1));
        } else {
          r0 = pack_bf16(acc[a] * rs0, acc[a + 1] * rs0);
          r1 = pack_bf16(acc[a + 2] * rs1, acc[a + 3] * rs1);
          r2 = pack_bf16(acc[a + 4] * rs0, acc[a + 5] * rs0);
          r3 = pack_bf16(acc[a + 6] * rs1, acc[a + 7] * rs1);
        }
        stmatrix_x4(base + (((hb * 4 + jj * 2 + (lane >> 4)) ^ (srow & 7)) << 4), r0, r1, r2, r3);
      }
    };
    auto q_head = [&](float (&acc)[32], int c, int slot, uint32_t b0, uint32_t b1, uint32_t b2, uint32_t b3, uint32_t z0, uint32_t z1) INL {
      const int a = c * 8;
      const uint32_t a0 = pack_bf16(phi_f(acc[a] * rs0), phi_f(acc[a + 1] * rs0));
      const uint32_t a1 = pack_bf16(phi_f(acc[a + 2] * rs1), phi_f(acc[a + 3] * rs1));
      const uint32_t a2 = pack_bf16(phi_f(acc[a + 4] * rs0), phi_f(acc[a + 5] * rs0));
      const uint32_t a3 = pack_bf16(phi_f(acc[a + 6] * rs1), phi_f(acc[a + 7] * rs1));
      float n0[4] = {0.f, 0.f, 0.f, 0.f}, n1[4] = {0.f, 0.f, 0.f, 0.f}, dn[4] = {0.f, 0.f, 0.f, 0.f};
      mma_16816(n0, a0, a1, a2, a3, b0, b1);
      mma_16816(n1, a0, a1, a2, a3, b2, b3);
      mma_16816(dn, a0, a1, a2, a3, z0, z1);
      const float i0 = __fdividef(1.f, dn[0] + 1e-6f), i1 = __fdividef(1.f, dn[2] + 1e-6f);
      const uint32_t o0 = ~pack_bf16(n0[0] * i0, n0[1] * i0), o1 = ~pack_bf16(n0[2] * i1, n0[3] * i1);
      const uint32_t o2 = ~pack_bf16(n1[0] * i0, n1[1] * i0), o3 = ~pack_bf16(n1[2] * i1, n1[3] * i1);
      sts_u4(stash + slot * 8192 + c * 2048, o0, o1, o2, o3);
      stg_u4(xptr(slot, c), o0, o1, o2, o3);
    };
    const uint32_t kvb = area + 5 * 8192;
    const uint32_t kvfrag = kvb + ((lane & 7) + ((lane >> 3) & 1) * 8) * 32 + (lane >> 4) * 16;
    auto signal = [&](int e) INL {
      __syncwarp();
      if (lane == 0) mbar_arrive(BAR(B_EV + w * 2 + e));
    };

    float accB[32];
#pragma unroll 1
    for (int t = 0; t < 5; t++) {
      float accA[32];
      const uint32_t ph = t & 1;
      const int kindP = t == 0 ? K_NONE : ((odd && t <= 2) ? K_KV : K_GU);
      const int kindC = odd ? (t < 2 ? K_KV : K_GU) : (t < 4 ? K_GU : K_Q);
      const int slotP = odd ? t - 3 : t - 1, xslotP = odd ? t + 3 : t - 1;
      const int slotC = odd ? t - 2 : t, xslotC = odd ? t + 4 : t;
      static_for<8>([&](auto kc) INL {
        constexpr int k = decltype(kc)::value;
        mbar_wait(BAR(B_FULL + k), ph);
        wgmma_fence();
        static_for<8>([&](auto kkc) INL {
          constexpr int kk = decltype(kkc)::value;
          constexpr int i = ((k & 3) * 8 + kk) * 4;
          constexpr uint32_t lo = desc_lo(stage_off(k) + kk * 1024, 8192);
          if constexpr (k < 4) wgmma_n64_rs<((k & 3) | kk) != 0, lo, kHi64>(accA, A[i], A[i + 1], A[i + 2], A[i + 3], dbase);
          else wgmma_n64_rs<((k & 3) | kk) != 0, lo, kHi64>(accB, A[i], A[i + 1], A[i + 2], A[i + 3], dbase);
        });
        wgmma_commit();
        if (k > 0) {
          wgmma_wait<1>();
          release(k - 1);
        }
        if constexpr (k < 4) {
          if (kindP == K_GU) {
            if (k == 1 || k == 2) gu_chunk(accB, k - 1, slotP, xslotP, 1);
          } else if (kindP == K_KV) {
            if (k == 1 || k == 2) kv_stage(accB, k - 1, 1);
            if (k == 3) {
              float kvacc[36];
              const int par = ld_relaxed(&g_epoch) & 1;
              fence_proxy_async();
              bar_sync(1 + w, 128);
              wgmma_fence();
              static_for<4>([&](auto kkc) INL {
                constexpr int kk = decltype(kkc)::value;
                wgmma_n72_ss_tt<kk != 0, desc_lo(3 * 8192 + kk * 2048, 0), desc_lo(4 * 8192 + kk * 2048, 8192 - kk * 2048)>(kvacc, dbase + w * 4096);
              });
              wgmma_commit();
              wgmma_wait<0>();
              float c[8];
#pragma unroll
              for (int i = 0; i < 8; i++)
                c[i] = wq == 0 ? kvacc[i] : (wq == 1 ? kvacc[8 + i] : (wq == 2 ? kvacc[16 + i] : kvacc[24 + i]));
              const int head = (2 * p + t - 1) * 4 + wq;
              float* kvp = &g_kv[par][head][0][0];
              red_add_v2(kvp + g * 16 + 2 * tq, c[0], c[1]);
              red_add_v2(kvp + (g + 8) * 16 + 2 * tq, c[2], c[3]);
              red_add_v2(kvp + g * 16 + 8 + 2 * tq, c[4], c[5]);
              red_add_v2(kvp + (g + 8) * 16 + 8 + 2 * tq, c[6], c[7]);
              if (tq == 0) {
                red_add(&g_z[par][head][g], kvacc[32]);
                red_add(&g_z[par][head][g + 8], kvacc[34]);
              }
              signal(t - 1);
            }
          }
        } else {
          constexpr int c = k - 4;
          if (kindC == K_GU) {
            if (c < 2) gu_chunk(accA, c, slotC, xslotC, 0);
          } else if (kindC == K_KV) {
            if (c == 0 && kindP == K_NONE) sts_u4(stash + 5 * 8192, 0x3F803F80u, 0x3F803F80u, 0x3F803F80u, 0x3F803F80u);
            if (c < 2) kv_stage(accA, c, 0);
          } else {
            if (c == 0) mbar_wait(BAR(B_KVREADY), 0);
            uint32_t b0, b1, b2, b3;
            ldmatrix_x4_trans(kvfrag + c * 512, b0, b1, b2, b3);
            const uint32_t z0 = lds_u32(kvb + 4096 + c * 32 + tq * 4), z1 = lds_u32(kvb + 4096 + c * 32 + 16 + tq * 4);
            q_head(accA, c, 4, b0, b1, b2, b3, z0, z1);
          }
        }
      });
      wgmma_wait<0>();
      release(7);
      PROF(w, 1 + 2 * t);
    }
    if (odd) {
      gu_chunk(accB, 0, 2, 8, 1);
      gu_chunk(accB, 1, 2, 8, 1);
    } else {
      uint32_t Bf[4][6];
#pragma unroll
      for (int c = 0; c < 4; c++) {
        ldmatrix_x4_trans(kvfrag + (4 + c) * 512, Bf[c][0], Bf[c][1], Bf[c][2], Bf[c][3]);
        Bf[c][4] = lds_u32(kvb + 4096 + (4 + c) * 32 + tq * 4);
        Bf[c][5] = lds_u32(kvb + 4096 + (4 + c) * 32 + 16 + tq * 4);
      }
      bar_sync(1 + w, 128);
#pragma unroll
      for (int c = 0; c < 4; c++) q_head(accB, c, 5, Bf[c][0], Bf[c][1], Bf[c][2], Bf[c][3], Bf[c][4], Bf[c][5]);
    }
    PROF(w, 10);

    const int n_own = odd ? 3 : 6;
    auto load_a = [&](int kb) INL {
      if (kb < n_own) {
#pragma unroll
        for (int jj = 0; jj < 4; jj++) {
          const int i = (kb * 4 + jj) * 4;
          lds_u4(stash + kb * 8192 + jj * 2048, A[i], A[i + 1], A[i + 2], A[i + 3]);
        }
      } else {
        const int xs = odd ? kb - 3 : kb;
#pragma unroll
        for (int jj = 0; jj < 4; jj++) {
          const int i = (kb * 4 + jj) * 4;
          ldg_poll_u4(xptr(xs, jj), A[i], A[i + 1], A[i + 2], A[i + 3]);
        }
      }
    };
    auto fix_a = [&](int kb) INL {
      if (kb >= n_own) {
        const int xs = odd ? kb - 3 : kb;
        recv_group<4>(xptr(xs, 0), &A[kb * 16]);
      } else {
#pragma unroll
        for (int i = 0; i < 16; i++) A[kb * 16 + i] = ~A[kb * 16 + i];
      }
    };
#pragma unroll
    for (int kb = 0; kb < 7; kb++) load_a(kb);
    PROF(w, 11);

    const int orow = m * 128 + w * 64 + wq * 16 + g;
    const int ocol = odd * 256 + p * 64 + 2 * tq;
    float acc2[2][32];
    uint32_t poff = (uint32_t)((m * 2 + odd) * 24 + w) * 16384u + (uint32_t)t128 * 16u;
    asm volatile("" : "+r"(poff));
    auto pptr = [&](int dest, int sl) INL { return (uint4*)((char*)g_pbuf + (poff + (uint32_t)(dest * 3 + sl) * 32768u)); };
    uint32_t P[3][32];
    uint32_t xr[16];
    auto send = [&](float (&acc)[32], int bi) INL {
      uint4* dst = pptr((p + 1 + bi) & 3, bi);
#pragma unroll
      for (int q = 0; q < 8; q++)
        stg_u4(dst + q * 128, ~__float_as_uint(acc[q * 4]), ~__float_as_uint(acc[q * 4 + 1]), ~__float_as_uint(acc[q * 4 + 2]), ~__float_as_uint(acc[q * 4 + 3]));
      PROF(w, 12 + 2 * bi);
    };
    auto fetch = [&](int sl) INL {
#pragma unroll
      for (int q = 0; q < 8; q++) ldg_poll_u4(pptr(p, sl) + q * 128, P[sl][q * 4], P[sl][q * 4 + 1], P[sl][q * 4 + 2], P[sl][q * 4 + 3]);
    };
    static_for<36>([&](auto ic) INL {
      constexpr int i = decltype(ic)::value, bi = p2_bi(i), kb = p2_kb(i), j = i >> 1, st = j & 7;
      if (i == 9) { load_a(7); load_a(8); }
      if (bi == 0) fix_a(kb);
      if ((i & 1) == 0) mbar_wait(BAR(B_FULL + st), (5 + (j >> 3)) & 1);
      wgmma_fence();
      static_for<4>([&](auto kkc) INL {
        constexpr int kk = decltype(kkc)::value, a = (kb * 4 + kk) * 4;
        wgmma_n64_rs<(kb | kk) != 0, desc_lo(stage_off(st) + (i & 1) * 8192 + kk * 2048, 0), kHi128>(acc2[bi & 1], A[a], A[a + 1], A[a + 2], A[a + 3], dbase);
      });
      wgmma_commit();
      if (i > 0) {
        wgmma_wait<1>();
        if ((i & 1) == 0 && j - 1 <= 9) release((j - 1) & 7);
      }
      if constexpr (i == 16) send(acc2[0], 0);
      if constexpr (i == 18) send(acc2[1], 1);
      if constexpr (i == 27) send(acc2[0], 2);
      if constexpr (i == 29) fetch(0);
      if constexpr (i == 31) fetch(1);
      if constexpr (i == 32) {
#pragma unroll
        for (int q = 0; q < 8; q++) {
          xr[2 * q] = __ldg((const uint32_t*)(x + (size_t)orow * kD + ocol + q * 8));
          xr[2 * q + 1] = __ldg((const uint32_t*)(x + (size_t)(orow + 8) * kD + ocol + q * 8));
        }
      }
      if constexpr (i == 34) fetch(2);
    });
#pragma unroll
    for (int sl = 0; sl < 3; sl++) recv_group<8>(pptr(p, sl), &P[sl][0]);
    wgmma_wait<0>();
    PROF(w, 18);
#pragma unroll
    for (int q = 0; q < 8; q++) {
      float rr[4];
#pragma unroll
      for (int e = 0; e < 4; e++)
        rr[e] = acc2[1][q * 4 + e] + __uint_as_float(P[0][q * 4 + e]) + __uint_as_float(P[1][q * 4 + e]) + __uint_as_float(P[2][q * 4 + e]);
      rr[0] += __uint_as_float(xr[2 * q] << 16);
      rr[1] += __uint_as_float(xr[2 * q] & 0xffff0000u);
      rr[2] += __uint_as_float(xr[2 * q + 1] << 16);
      rr[3] += __uint_as_float(xr[2 * q + 1] & 0xffff0000u);
      *(uint32_t*)(out + (size_t)orow * kD + ocol + q * 8) = pack_bf16(rr[0], rr[1]);
      *(uint32_t*)(out + (size_t)(orow + 8) * kD + ocol + q * 8) = pack_bf16(rr[2], rr[3]);
    }
    PROF(w, 19);
    if (tid == 0) {
      const uint32_t old = atomicAdd(&g_done, 1u);
      if ((old & 127u) == 127u) st_relaxed(&g_epoch, ld_relaxed(&g_epoch) + 1u);
    }
  }
#undef BAR
}

typedef CUresult (*EncodeFn)(CUtensorMap*, CUtensorMapDataType, cuuint32_t, void*, const cuuint64_t*, const cuuint64_t*,
                             const cuuint32_t*, const cuuint32_t*, CUtensorMapInterleave, CUtensorMapSwizzle,
                             CUtensorMapL2promotion, CUtensorMapFloatOOBfill);

void make_map(EncodeFn enc, CUtensorMap* tm, const void* ptr, int rows, int cols, bool narrow) {
  cuuint64_t gd[2] = {(cuuint64_t)cols, (cuuint64_t)rows};
  cuuint64_t gs[1] = {(cuuint64_t)cols * 2};
  cuuint32_t bd[2] = {narrow ? 32u : 64u, narrow ? 128u : 64u};
  cuuint32_t es[2] = {1, 1};
  enc(tm, CU_TENSOR_MAP_DATA_TYPE_BFLOAT16, 2, const_cast<void*>(ptr), gd, gs, bd, es, CU_TENSOR_MAP_INTERLEAVE_NONE,
      narrow ? CU_TENSOR_MAP_SWIZZLE_64B : CU_TENSOR_MAP_SWIZZLE_128B, CU_TENSOR_MAP_L2_PROMOTION_L2_256B, CU_TENSOR_MAP_FLOAT_OOB_FILL_NONE);
}

}

extern "C" void kernel_launch(void* const* d_in, const int* in_sizes, int n_in, void* d_out, int out_size) {
  static EncodeFn enc = nullptr;
  if (!enc) {
    void* fn = nullptr;
    cudaDriverEntryPointQueryResult qr;
    cudaGetDriverEntryPoint("cuTensorMapEncodeTiled", &fn, cudaEnableDefault, &qr);
    enc = (EncodeFn)fn;
    cudaFuncSetAttribute(fused_kernel, cudaFuncAttributeMaxDynamicSharedMemorySize, kSmemBytes);
  }
  CUtensorMap tm_x, tm_wqkv, tm_w1, tm_w3, tm_w2, tm_wo;
  make_map(enc, &tm_x, d_in[0], kS, kD, false);
  make_map(enc, &tm_wqkv, d_in[1], kD, 3 * kD, true);
  make_map(enc, &tm_wo, d_in[2], kD, kD, false);
  make_map(enc, &tm_w1, d_in[4], kD, kF, true);
  make_map(enc, &tm_w3, d_in[5], kD, kF, true);
  make_map(enc, &tm_w2, d_in[6], kF, kD, false);
  fused_kernel<<<128, 384, kSmemBytes>>>(tm_x, tm_wqkv, tm_w1, tm_w3, tm_w2, tm_wo, (const __nv_bfloat16*)d_in[0],
                                         (__nv_bfloat16*)d_out);
}
```

```cpp
#include <cuda_runtime.h>
#include <cuda_bf16.h>
#include <cuda.h>
#include <stdint.h>

namespace {

constexpr int kS = 2048, kD = 512, kF = 1792;
constexpr uint32_t kSpinLimit = 1u << 22;

__device__ uint4    g_xbuf[2][16][4][9][2][4][128];
__device__ uint4    g_pbuf[2][16][2][4][3][2][4][128];
constexpr uint32_t kXbufPar = 16u * 4 * 9 * 2 * 8192, kPbufPar = 16u * 2 * 4 * 3 * 2 * 8192;
__device__ float    g_kv[2][32][16][16];
__device__ float    g_z[2][32][16];
__device__ uint32_t g_kvcnt[4][32];
__device__ uint32_t g_epoch;
__device__ uint32_t g_done;
#define PROF(wg, i) do {} while (0)

__device__ __forceinline__ uint32_t smem_u32(const void* p) { return (uint32_t)__cvta_generic_to_shared(p); }
__device__ __forceinline__ void mbar_init(uint32_t bar, uint32_t cnt) {
  asm volatile("mbarrier.init.shared::cta.b64 [%0], %1;" ::"r"(bar), "r"(cnt) : "memory");
}
__device__ __forceinline__ void mbar_expect_tx(uint32_t bar, uint32_t bytes) {
  asm volatile("mbarrier.arrive.expect_tx.shared::cta.b64 _, [%0], %1;" ::"r"(bar), "r"(bytes) : "memory");
}
__device__ __forceinline__ void mbar_arrive(uint32_t bar) {
  asm volatile("mbarrier.arrive.shared::cta.b64 _, [%0];" ::"r"(bar) : "memory");
}
__device__ __forceinline__ void mbar_wait(uint32_t bar, uint32_t parity) {
  asm volatile(
      "{\n.reg .pred p;\n"
      "LAB_WAIT:\n"
      "mbarrier.try_wait.parity.shared::cta.b64 p, [%0], %1;\n"
      "@p bra DONE;\n"
      "bra LAB_WAIT;\n"
      "DONE:\n}" ::"r"(bar), "r"(parity) : "memory");
}
__device__ __forceinline__ void tma_load_2d(uint32_t dst, const CUtensorMap* tm, uint32_t bar, int c0, int c1) {
  asm volatile(
      "cp.async.bulk.tensor.2d.shared::cluster.global.mbarrier::complete_tx::bytes [%0], [%1, {%3, %4}], [%2];" ::"r"(dst),
      "l"(tm), "r"(bar), "r"(c0), "r"(c1)
      : "memory");
}
__device__ __forceinline__ void tma_load_2d_mc(uint32_t dst, const CUtensorMap* tm, uint32_t bar, int c0, int c1) {
  asm volatile(
      "cp.async.bulk.tensor.2d.shared::cluster.global.mbarrier::complete_tx::bytes.multicast::cluster [%0], [%1, {%3, %4}], [%2], %5;" ::"r"(dst),
      "l"(tm), "r"(bar), "r"(c0), "r"(c1), "h"((uint16_t)3)
      : "memory");
}
__device__ __forceinline__ void mbar_arrive_cluster(uint32_t bar, uint32_t cta) {
  asm volatile("{\n.reg .b32 ra;\nmapa.shared::cluster.u32 ra, %0, %1;\nmbarrier.arrive.shared::cluster.b64 _, [ra];\n}" ::"r"(bar), "r"(cta) : "memory");
}
__device__ __forceinline__ void prefetch_tmap(const CUtensorMap* tm) {
  asm volatile("prefetch.tensormap [%0];" ::"l"(tm) : "memory");
}
__device__ __forceinline__ void wgmma_fence() { asm volatile("wgmma.fence.sync.aligned;" ::: "memory"); }
__device__ __forceinline__ void wgmma_commit() { asm volatile("wgmma.commit_group.sync.aligned;" ::: "memory"); }
template <int N>
__device__ __forceinline__ void wgmma_wait() { asm volatile("wgmma.wait_group.sync.aligned %0;" ::"n"(N) : "memory"); }
__device__ __forceinline__ void bar_sync(int id, int n) { asm volatile("bar.sync %0, %1;" ::"r"(id), "r"(n) : "memory"); }
__device__ __forceinline__ void bar_arrive(int id, int n) { asm volatile("bar.arrive %0, %1;" ::"r"(id), "r"(n) : "memory"); }
__device__ __forceinline__ void fence_proxy_async() { asm volatile("fence.proxy.async.shared::cta;" ::: "memory"); }

__device__ __forceinline__ uint32_t ld_acquire(const uint32_t* p) {
  uint32_t v;
  asm volatile("ld.acquire.gpu.global.u32 %0, [%1];" : "=r"(v) : "l"(p) : "memory");
  return v;
}
__device__ __forceinline__ uint32_t ld_relaxed(const uint32_t* p) {
  uint32_t v;
  asm volatile("ld.relaxed.gpu.global.u32 %0, [%1];" : "=r"(v) : "l"(p));
  return v;
}
__device__ __forceinline__ void cluster_wait() { asm volatile("barrier.cluster.wait.aligned;" ::: "memory"); }
__device__ __forceinline__ void st_relaxed(uint32_t* p, uint32_t v) {
  asm volatile("st.relaxed.gpu.global.u32 [%0], %1;" ::"l"(p), "r"(v) : "memory");
}
__device__ __forceinline__ void wait_flag_eq(const uint32_t* p, uint32_t val) {
  uint32_t it = 0;
  while (ld_acquire(p) != val) {
    if (++it > kSpinLimit) break;
  }
}
__device__ __forceinline__ void wait_count_ge(const uint32_t* p, uint32_t val) {
  uint32_t it = 0;
  while ((int32_t)(ld_acquire(p) - val) < 0) {
    __nanosleep(64);
    if (++it > kSpinLimit) break;
  }
}
__device__ __forceinline__ void ldg_poll_u4(const void* p, uint32_t& a, uint32_t& b, uint32_t& c, uint32_t& d) {
  asm volatile("ld.relaxed.gpu.global.v4.u32 {%0,%1,%2,%3}, [%4];" : "=r"(a), "=r"(b), "=r"(c), "=r"(d) : "l"(p) : "memory");
}
template <int N>
__device__ __forceinline__ void recv_group(uint4* p, uint32_t* r) {
  uint32_t it = 0;
  while (true) {
    uint32_t mn = 0xffffffffu;
#pragma unroll
    for (int i = 0; i < 4 * N; i++) mn = min(mn, r[i]);
    if (!__any_sync(0xffffffffu, mn == 0u) || ++it > kSpinLimit) break;
#pragma unroll
    for (int q = 0; q < N; q++) ldg_poll_u4(p + q * 128, r[q * 4], r[q * 4 + 1], r[q * 4 + 2], r[q * 4 + 3]);
  }
#pragma unroll
  for (int i = 0; i < 4 * N; i++) r[i] = ~r[i];
}
__device__ __forceinline__ float4 ldg_cg_f4(const void* p) {
  float4 v;
  asm volatile("ld.global.cg.v4.f32 {%0,%1,%2,%3}, [%4];" : "=f"(v.x), "=f"(v.y), "=f"(v.z), "=f"(v.w) : "l"(p) : "memory");
  return v;
}
__device__ __forceinline__ void stg_u4(void* p, uint32_t a, uint32_t b, uint32_t c, uint32_t d) {
  asm volatile("st.global.v4.u32 [%0], {%1,%2,%3,%4};" ::"l"(p), "r"(a), "r"(b), "r"(c), "r"(d) : "memory");
}
__device__ __forceinline__ void stg_f4(void* p, float a, float b, float c, float d) {
  asm volatile("st.global.v4.f32 [%0], {%1,%2,%3,%4};" ::"l"(p), "f"(a), "f"(b), "f"(c), "f"(d) : "memory");
}
__device__ __forceinline__ void sts_u4(uint32_t addr, uint32_t a, uint32_t b, uint32_t c, uint32_t d) {
  asm volatile("st.shared.v4.u32 [%0], {%1,%2,%3,%4};" ::"r"(addr), "r"(a), "r"(b), "r"(c), "r"(d) : "memory");
}
__device__ __forceinline__ void lds_u4(uint32_t addr, uint32_t& a, uint32_t& b, uint32_t& c, uint32_t& d) {
  asm volatile("ld.shared.v4.u32 {%0,%1,%2,%3}, [%4];" : "=r"(a), "=r"(b), "=r"(c), "=r"(d) : "r"(addr) : "memory");
}
__device__ __forceinline__ uint32_t lds_u32(uint32_t addr) {
  uint32_t v;
  asm volatile("ld.shared.u32 %0, [%1];" : "=r"(v) : "r"(addr) : "memory");
  return v;
}
__device__ __forceinline__ void ldmatrix_x4(uint32_t addr, uint32_t& a, uint32_t& b, uint32_t& c, uint32_t& d) {
  asm volatile("ldmatrix.sync.aligned.m8n8.x4.shared.b16 {%0,%1,%2,%3}, [%4];" : "=r"(a), "=r"(b), "=r"(c), "=r"(d) : "r"(addr) : "memory");
}
__device__ __forceinline__ void ldmatrix_x4_trans(uint32_t addr, uint32_t& a, uint32_t& b, uint32_t& c, uint32_t& d) {
  asm volatile("ldmatrix.sync.aligned.m8n8.x4.trans.shared.b16 {%0,%1,%2,%3}, [%4];" : "=r"(a), "=r"(b), "=r"(c), "=r"(d) : "r"(addr) : "memory");
}
__device__ __forceinline__ void stmatrix_x4(uint32_t addr, uint32_t a, uint32_t b, uint32_t c, uint32_t d) {
  asm volatile("stmatrix.sync.aligned.m8n8.x4.shared.b16 [%0], {%1,%2,%3,%4};" ::"r"(addr), "r"(a), "r"(b), "r"(c), "r"(d) : "memory");
}
__device__ __forceinline__ void mma_16816(float (&c)[4], uint32_t a0, uint32_t a1, uint32_t a2, uint32_t a3, uint32_t b0, uint32_t b1) {
  asm volatile(
      "mma.sync.aligned.m16n8k16.row.col.f32.bf16.bf16.f32 {%0,%1,%2,%3}, {%4,%5,%6,%7}, {%8,%9}, {%0,%1,%2,%3};"
      : "+f"(c[0]), "+f"(c[1]), "+f"(c[2]), "+f"(c[3])
      : "r"(a0), "r"(a1), "r"(a2), "r"(a3), "r"(b0), "r"(b1));
}
__device__ __forceinline__ uint32_t pack_bf16(float lo, float hi) {
  uint32_t r;
  asm("cvt.rn.bf16x2.f32 %0, %1, %2;" : "=r"(r) : "f"(hi), "f"(lo));
  return r;
}
__device__ __forceinline__ uint32_t hsub2_bf16(uint32_t a, uint32_t b) {
  uint32_t r;
  asm("sub.rn.bf16x2 %0, %1, %2;" : "=r"(r) : "r"(a), "r"(b));
  return r;
}
__device__ __forceinline__ float ex2f(float x) {
  float r;
  asm("ex2.approx.ftz.f32 %0, %1;" : "=f"(r) : "f"(x));
  return r;
}
__device__ __forceinline__ float rcpf(float x) {
  float r;
  asm("rcp.approx.ftz.f32 %0, %1;" : "=f"(r) : "f"(x));
  return r;
}
__device__ __forceinline__ void red_add_v2(float* p, float a, float b) {
  asm volatile("red.relaxed.gpu.global.add.v2.f32 [%0], {%1,%2};" ::"l"(p), "f"(a), "f"(b) : "memory");
}
__device__ __forceinline__ void red_add(float* p, float a) {
  asm volatile("red.relaxed.gpu.global.add.f32 [%0], %1;" ::"l"(p), "f"(a) : "memory");
}
__device__ __forceinline__ float phi_f(float t) {
  float e = ex2f(t * 1.4426950408889634f);
  return (t > 0.f ? t + 1.f : e) + 1e-6f;
}

#define R8(a, o) "+f"(a[o + 0]), "+f"(a[o + 1]), "+f"(a[o + 2]), "+f"(a[o + 3]), "+f"(a[o + 4]), "+f"(a[o + 5]), "+f"(a[o + 6]), "+f"(a[o + 7])

#define W8(a, o) "=f"(a[o + 0]), "=f"(a[o + 1]), "=f"(a[o + 2]), "=f"(a[o + 3]), "=f"(a[o + 4]), "=f"(a[o + 5]), "=f"(a[o + 6]), "=f"(a[o + 7])
#define D32 "{%0,%1,%2,%3,%4,%5,%6,%7,%8,%9,%10,%11,%12,%13,%14,%15,%16,%17,%18,%19,%20,%21,%22,%23,%24,%25,%26,%27,%28,%29,%30,%31}"
#define D36 "{%0,%1,%2,%3,%4,%5,%6,%7,%8,%9,%10,%11,%12,%13,%14,%15,%16,%17,%18,%19,%20,%21,%22,%23,%24,%25,%26,%27,%28,%29,%30,%31,%32,%33,%34,%35}"

constexpr uint32_t kHi128 = (1024u >> 4) | (1u << 30);
constexpr uint32_t kHi64 = (512u >> 4) | (2u << 30);
__host__ __device__ constexpr uint32_t desc_lo(uint32_t off, uint32_t lbo) { return (off >> 4) | ((lbo >> 4) << 16); }

template <bool ACC, uint32_t LO, uint32_t HI>
__device__ __forceinline__ void wgmma_n64_rs(float (&d)[32], uint32_t a0, uint32_t a1, uint32_t a2, uint32_t a3, uint32_t base) {
  if (ACC) {
    asm volatile(
        "{\n.reg .pred p;\n.reg .b32 lo;\n.reg .b64 dd;\nsetp.eq.b32 p, 0, 0;\nadd.u32 lo, %36, %37;\nmov.b64 dd, {lo, %38};\n"
        "wgmma.mma_async.sync.aligned.m64n64k16.f32.bf16.bf16 " D32 ", {%32,%33,%34,%35}, dd, p, 1, 1, 1;\n}"
        : R8(d, 0), R8(d, 8), R8(d, 16), R8(d, 24)
        : "r"(a0), "r"(a1), "r"(a2), "r"(a3), "r"(base), "n"(LO), "n"(HI));
  } else {
    asm volatile(
        "{\n.reg .pred p;\n.reg .b32 lo;\n.reg .b64 dd;\nsetp.ne.b32 p, 0, 0;\nadd.u32 lo, %36, %37;\nmov.b64 dd, {lo, %38};\n"
        "wgmma.mma_async.sync.aligned.m64n64k16.f32.bf16.bf16 " D32 ", {%32,%33,%34,%35}, dd, p, 1, 1, 1;\n}"
        : W8(d, 0), W8(d, 8), W8(d, 16), W8(d, 24)
        : "r"(a0), "r"(a1), "r"(a2), "r"(a3), "r"(base), "n"(LO), "n"(HI));
  }
}
template <bool ACC, uint32_t LOA, uint32_t LOB>
__device__ __forceinline__ void wgmma_n72_ss_tt(float (&d)[36], uint32_t base) {
  if (ACC) {
    asm volatile(
        "{\n.reg .pred p;\n.reg .b32 lo;\n.reg .b64 da, db;\nsetp.eq.b32 p, 0, 0;\n"
        "add.u32 lo, %36, %37;\nmov.b64 da, {lo, %39};\nadd.u32 lo, %36, %38;\nmov.b64 db, {lo, %39};\n"
        "wgmma.mma_async.sync.aligned.m64n72k16.f32.bf16.bf16 " D36 ", da, db, p, 1, 1, 1, 1;\n}"
        : R8(d, 0), R8(d, 8), R8(d, 16), R8(d, 24), "+f"(d[32]), "+f"(d[33]), "+f"(d[34]), "+f"(d[35])
        : "r"(base), "n"(LOA), "n"(LOB), "n"(kHi128));
  } else {
    asm volatile(
        "{\n.reg .pred p;\n.reg .b32 lo;\n.reg .b64 da, db;\nsetp.ne.b32 p, 0, 0;\n"
        "add.u32 lo, %36, %37;\nmov.b64 da, {lo, %39};\nadd.u32 lo, %36, %38;\nmov.b64 db, {lo, %39};\n"
        "wgmma.mma_async.sync.aligned.m64n72k16.f32.bf16.bf16 " D36 ", da, db, p, 1, 1, 1, 1;\n}"
        : W8(d, 0), W8(d, 8), W8(d, 16), W8(d, 24), "=f"(d[32]), "=f"(d[33]), "=f"(d[34]), "=f"(d[35])
        : "r"(base), "n"(LOA), "n"(LOB), "n"(kHi128));
  }
}

#define INL __attribute__((always_inline))
template <int V> struct IC { static constexpr int value = V; };
template <int N, int I = 0, typename F>
__device__ __forceinline__ void static_for(F&& f) {
  if constexpr (I < N) { f(IC<I>{}); static_for<N, I + 1>(f); }
}

__host__ __device__ constexpr uint32_t stage_off(int st) {
  return st < 6 ? 131072u + (uint32_t)st * 16384u : (uint32_t)(st - 6) * 65536u + 49152u;
}

constexpr int B_FULL = 0, B_EMPTY = 8, B_XFULL = 16, B_XDONE = 32, B_KVREADY = 33, B_EV = 34, B_COUNT = 38;
constexpr uint32_t kBarOff = 229376;
constexpr int kSmemBytes = 229376 + 1024;

__host__ __device__ constexpr int p2_bi(int i) { return i < 7 ? 0 : i < 14 ? 1 : i < 16 ? 0 : i < 18 ? 1 : i / 9; }
__host__ __device__ constexpr int p2_kb(int i) { return i < 7 ? i : i < 14 ? i - 7 : i < 16 ? i - 7 : i < 18 ? i - 9 : i % 9; }

enum { K_NONE = 0, K_GU = 1, K_KV = 2, K_Q = 3 };

__global__ void __cluster_dims__(2, 1, 1) __launch_bounds__(384, 1)
fused_kernel(const __grid_constant__ CUtensorMap tm_x, const __grid_constant__ CUtensorMap tm_wqkv,
             const __grid_constant__ CUtensorMap tm_w1, const __grid_constant__ CUtensorMap tm_w3,
             const __grid_constant__ CUtensorMap tm_w2, const __grid_constant__ CUtensorMap tm_wo,
             const __nv_bfloat16* __restrict__ x, __nv_bfloat16* __restrict__ out) {
  extern __shared__ __align__(1024) uint8_t smem_raw[];
  const uint32_t sbase = smem_u32(smem_raw);
  const uint32_t bars = sbase + kBarOff;
  const int tid = threadIdx.x, lane = tid & 31;
  const int warp = __shfl_sync(0xffffffffu, tid >> 5, 0);
  const int cr = blockIdx.x & 1;
  const int r = (blockIdx.x >> 1) & 7, m = ((blockIdx.x >> 4) << 1) | cr, p = r >> 1, odd = r & 1;
#define BAR(i) (bars + 8u * (uint32_t)(i))
  if (tid == 256) {
    if (sbase & 1023u) __trap();
#pragma unroll
    for (int i = 0; i < 16; i++) mbar_init(BAR(B_XFULL + i), 1);
    fence_proxy_async();
#pragma unroll
    for (int b = 0; b < 16; b++) {
      mbar_expect_tx(BAR(B_XFULL + b), 8192);
      tma_load_2d(sbase + (b >> 3) * 65536 + (b & 7) * 8192, &tm_x, BAR(B_XFULL + b), (b & 7) * 64, m * 128 + (b >> 3) * 64);
    }
#pragma unroll
    for (int i = 0; i < 8; i++) { mbar_init(BAR(B_FULL + i), 1); mbar_init(BAR(B_EMPTY + i), 4); }
#pragma unroll
    for (int i = 0; i < 4; i++) mbar_init(BAR(B_EV + i), 4);
    mbar_init(BAR(B_XDONE), 2);
    mbar_init(BAR(B_KVREADY), 1);
    asm volatile("fence.mbarrier_init.release.cluster;" ::: "memory");
    fence_proxy_async();
  } else if (tid == 288) {
    prefetch_tmap(odd ? &tm_wqkv : (cr ? &tm_w3 : &tm_w1));
  }
  __syncwarp();
  asm volatile("barrier.cluster.arrive.relaxed.aligned;" ::: "memory");
  PROF((tid >> 7), 21);
  __syncthreads();

  if (warp >= 8) {
    asm volatile("setmaxnreg.dec.sync.aligned.u32 24;");
    PROF(2, 3);
    cluster_wait();
    PROF(2, 2);
    const uint32_t epoch = warp == 8 ? 0u : ld_relaxed(&g_epoch);
    const uint32_t tag = epoch + 1u;
    const int par = epoch & 1;
    if (warp == 8) {
      if (lane == 0) {
        for (int j = 0; j < 10; j++) {
          const CUtensorMap* tm;
          int col;
          if (!odd) {
            if (j < 8) { tm = cr ? &tm_w3 : &tm_w1; col = 7 * p * 64 + j * 32; }
            else { tm = &tm_wqkv; col = 128 * p + (j - 8) * 64 + cr * 32; }
          } else {
            if (j < 4) { tm = &tm_wqkv; col = 512 + cr * 512 + 128 * p + j * 32; }
            else { tm = cr ? &tm_w3 : &tm_w1; col = (7 * p + 4) * 64 + (j - 4) * 32; }
          }
          const int t = j >> 1;
          for (int kq = 0; kq < 4; kq++) {
            const int k = (j & 1) * 4 + kq;
            mbar_wait(BAR(B_EMPTY + k), k < 6 ? ((t & 1) ^ 1) : (t & 1));
            mbar_expect_tx(BAR(B_FULL + k), 16384);
            tma_load_2d_mc(sbase + stage_off(k) + cr * 8192, tm, BAR(B_FULL + k), col, kq * 128);
          }
        }
        for (int j = 0; j < 18; j++) {
          const int st = j & 7, n = 5 + (j >> 3);
          const int i = 2 * j + cr;
          const int bi = p2_bi(i), kb = p2_kb(i);
          const int col = odd * 256 + ((p + 1 + bi) & 3) * 64;
          const CUtensorMap* tmk;
          int row;
          if (!odd) {
            if (kb < 4) { tmk = &tm_w2; row = (7 * p + kb) * 64; }
            else if (kb < 6) { tmk = &tm_wo; row = (2 * p + kb - 4) * 64; }
            else { tmk = &tm_w2; row = (7 * p + 4 + kb - 6) * 64; }
          } else {
            if (kb < 3) { tmk = &tm_w2; row = (7 * p + 4 + kb) * 64; }
            else if (kb < 7) { tmk = &tm_w2; row = (7 * p + kb - 3) * 64; }
            else { tmk = &tm_wo; row = (2 * p + kb - 7) * 64; }
          }
          mbar_wait(BAR(B_EMPTY + st), st < 6 ? ((n & 1) ^ 1) : (n & 1));
          mbar_expect_tx(BAR(B_FULL + st), 16384);
          tma_load_2d_mc(sbase + stage_off(st) + cr * 8192, tmk, BAR(B_FULL + st), col, row);
        }
      }
    } else if (warp <= 10) {
      {
        const int w = warp - 9;
        const uint4 zero = make_uint4(0u, 0u, 0u, 0u);
        const int x0 = odd ? 0 : 6, nx = odd ? 6 : 3;
        for (int sl = 0; sl < nx; sl++) {
          uint4* d = &g_xbuf[par ^ 1][m][p][x0 + sl][w][0][0];
          for (int i = lane; i < 512; i += 32) d[i] = zero;
        }
        for (int sl = 0; sl < 3; sl++) {
          uint4* d = &g_pbuf[par ^ 1][m][odd][p][sl][w][0][0];
          for (int i = lane; i < 512; i += 32) d[i] = zero;
        }
      }
      if (lane == 0 && odd) {
        const int w = warp - 9;
        for (int e = 0; e < 2; e++) {
          mbar_wait(BAR(B_EV + w * 2 + e), 0);
          __threadfence();
          atomicAdd(&g_kvcnt[p][0], 1u);
        }
      }
    } else {
      if (!odd) {
        {
          const int ce = m * 4 + p;
          float* kvn = &g_kv[par ^ 1][0][0][0];
          for (int i = lane; i < 128; i += 32) kvn[ce * 128 + i] = 0.f;
          if (lane < 8) (&g_z[par ^ 1][0][0])[ce * 8 + lane] = 0.f;
        }
        mbar_wait(BAR(B_XDONE), 0);
        wait_count_ge(&g_kvcnt[p][0], 64u * tag);
        const float* kvp = &g_kv[par][8 * p][0][0];
        const uint32_t dst0 = sbase + 5 * 8192, dst1 = dst0 + 65536;
#pragma unroll 4
        for (int i = 0; i < 16; i++) {
          float4 v = ldg_cg_f4(kvp + (i * 32 + lane) * 4);
          uint32_t lo = pack_bf16(v.x, v.y), hi = pack_bf16(v.z, v.w);
          uint32_t off = (uint32_t)(i * 32 + lane) * 8u;
          asm volatile("st.shared.v2.u32 [%0], {%1,%2};" ::"r"(dst0 + off), "r"(lo), "r"(hi) : "memory");
          asm volatile("st.shared.v2.u32 [%0], {%1,%2};" ::"r"(dst1 + off), "r"(lo), "r"(hi) : "memory");
        }
        {
          float4 v = ldg_cg_f4(&g_z[par][8 * p][0] + lane * 4);
          uint32_t lo = pack_bf16(v.x, v.y), hi = pack_bf16(v.z, v.w);
          uint32_t off = 4096u + (uint32_t)lane * 8u;
          asm volatile("st.shared.v2.u32 [%0], {%1,%2};" ::"r"(dst0 + off), "r"(lo), "r"(hi) : "memory");
          asm volatile("st.shared.v2.u32 [%0], {%1,%2};" ::"r"(dst1 + off), "r"(lo), "r"(hi) : "memory");
        }
        __syncwarp();
        if (lane == 0) mbar_arrive(BAR(B_KVREADY));
      }
    }
  } else {
    asm volatile("setmaxnreg.inc.sync.aligned.u32 240;");
    const int w = warp >> 2, wq = warp & 3, t128 = tid & 127;
    const int g = lane >> 2, tq = lane & 3;
    const uint32_t area = sbase + (uint32_t)w * 65536u;
    const bool elect = (t128 == 0);
    PROF(w, 22);
    const uint32_t dbase = (sbase & 0x3FFFFu) >> 4;
    uint32_t xoff = (uint32_t)((m * 4 + p) * 18 + w) * 8192u + (uint32_t)t128 * 16u;
    uint32_t stash = area + (uint32_t)t128 * 16u;
    asm volatile("{\n.reg .u32 e;\nld.relaxed.gpu.global.u32 e, [%2];\nand.b32 e, e, 1;\nmad.lo.u32 %0, e, %3, %0;\n}"
                 : "+r"(xoff), "+r"(stash) : "l"(&g_epoch), "n"(kXbufPar));
    auto xptr = [&](int slot, int jj) INL { return (uint4*)((char*)g_xbuf + (xoff + (uint32_t)slot * 16384u + (uint32_t)jj * 2048u)); };
    uint32_t A[144];
    float rs0, rs1;
    auto release = [&](int st) INL {
      if (elect) { mbar_arrive_cluster(BAR(B_EMPTY + st), 0); mbar_arrive_cluster(BAR(B_EMPTY + st), 1); }
    };

    {
      const int row = wq * 16 + (lane & 7) + ((lane >> 3) & 1) * 8;
      const uint32_t rbase = area + row * 128;
      float s0[2][4] = {}, q0[2][4] = {}, q1[2][4] = {};
      const uint32_t ones = 0x3F803F80u;
#pragma unroll
      for (int b = 0; b < 8; b++) {
        mbar_wait(BAR(B_XFULL + w * 8 + b), 0);
        if (b == 0) PROF(w, 23);
        if (b == 7) PROF(w, 24);
#pragma unroll
        for (int kk = 0; kk < 4; kk++) {
          const int i = (b * 4 + kk) * 4;
          ldmatrix_x4(rbase + b * 8192 + (((kk * 2 + (lane >> 4)) ^ (row & 7)) << 4), A[i], A[i + 1], A[i + 2], A[i + 3]);
        }
#pragma unroll
        for (int kk = 0; kk < 4; kk++) {
          const int i = (b * 4 + kk) * 4;
          mma_16816(s0[kk & 1], A[i], A[i + 1], A[i + 2], A[i + 3], ones, ones);
          mma_16816(q0[kk & 1], A[i], A[i + 1], A[i + 2], A[i + 3], A[i], A[i + 2]);
          mma_16816(q1[kk & 1], A[i], A[i + 1], A[i + 2], A[i + 3], A[i + 1], A[i + 3]);
        }
      }
      const float mean0 = (s0[0][0] + s0[1][0]) * (1.f / 512.f), mean1 = (s0[0][2] + s0[1][2]) * (1.f / 512.f);
      const uint32_t m0 = pack_bf16(mean0, mean0), m1 = pack_bf16(mean1, mean1);
#pragma unroll
      for (int i = 0; i < 128; i += 2) {
        A[i] = hsub2_bf16(A[i], m0);
        A[i + 1] = hsub2_bf16(A[i + 1], m1);
      }
      float v0 = (g & 1) ? q0[0][1] + q0[1][1] : q0[0][0] + q0[1][0];
      float v1 = (g & 1) ? q1[0][3] + q1[1][3] : q1[0][2] + q1[1][2];
      const int src = 4 * g + (g >> 1);
      v0 = __shfl_sync(0xffffffffu, v0, src);
      v1 = __shfl_sync(0xffffffffu, v1, src);
      v0 = fmaxf(v0 * (1.f / 512.f) - mean0 * mean0, 0.f);
      v1 = fmaxf(v1 * (1.f / 512.f) - mean1 * mean1, 0.f);
      rs0 = rsqrtf(v0 + 1e-5f);
      rs1 = rsqrtf(v1 + 1e-5f);
      bar_sync(1 + w, 128);
      cluster_wait();
      PROF(w, 0);
      release(6); release(7);
      if (elect) mbar_arrive(BAR(B_XDONE));
    }

    auto gu_chunk = [&](float (&acc)[32], int f, int slot, int xslot, int hb) INL {
      const float c0 = rs0 * -1.4426950408889634f, c1 = rs1 * -1.4426950408889634f;
      const float q0 = rs0 * rs0, q1 = rs1 * rs1;
      uint32_t h[4];
#pragma unroll
      for (int i = 0; i < 4; i++) {
        const float ga = acc[f * 8 + 2 * i], gb = acc[f * 8 + 2 * i + 1];
        const float ua = acc[16 + f * 8 + 2 * i], ub = acc[16 + f * 8 + 2 * i + 1];
        const float c = (i & 1) ? c1 : c0, q = (i & 1) ? q1 : q0;
        const float da = 1.f + ex2f(fminf(ga * c, 60.f)), db = 1.f + ex2f(fminf(gb * c, 60.f));
        const float rq = rcpf(da * db) * q;
        h[i] = ~pack_bf16(ga * ua * (db * rq), gb * ub * (da * rq));
      }
      const int jj = hb * 2 + f;
      sts_u4(stash + slot * 8192 + jj * 2048, h[0], h[1], h[2], h[3]);
      stg_u4(xptr(xslot, jj), h[0], h[1], h[2], h[3]);
    };
    auto kv_stage = [&](float (&acc)[32], int c, int hb) INL {
      const int srow = wq * 16 + (lane & 7) + ((lane >> 3) & 1) * 8;
      const uint32_t base = area + (3 + c) * 8192 + srow * 128;
#pragma unroll
      for (int jj = 0; jj < 2; jj++) {
        const int a = c * 16 + jj * 8;
        uint32_t r0, r1, r2, r3;
        if (c == 0) {
          r0 = pack_bf16(phi_f(acc[a] * rs0), phi_f(acc[a + 1] * rs0));
          r1 = pack_bf16(phi_f(acc[a + 2] * rs1), phi_f(acc[a + 3] * rs1));
          r2 = pack_bf16(phi_f(acc[a + 4] * rs0), phi_f(acc[a + 5] * rs0));
          r3 = pack_bf16(phi_f(acc[a + 6] * rs1), phi_f(acc[a + 7] * rs1));
        } else {
          r0 = pack_bf16(acc[a] * rs0, acc[a + 1] * rs0);
          r1 = pack_bf16(acc[a + 2] * rs1, acc[a + 3] * rs1);
          r2 = pack_bf16(acc[a + 4] * rs0, acc[a + 5] * rs0);
          r3 = pack_bf16(acc[a + 6] * rs1, acc[a + 7] * rs1);
        }
        stmatrix_x4(base + (((hb * 4 + jj * 2 + (lane >> 4)) ^ (srow & 7)) << 4), r0, r1, r2, r3);
      }
    };
    auto q_head = [&](float (&acc)[32], int c, int slot, uint32_t b0, uint32_t b1, uint32_t b2, uint32_t b3, uint32_t z0, uint32_t z1) INL {
      const int a = c * 8;
      const uint32_t a0 = pack_bf16(phi_f(acc[a] * rs0), phi_f(acc[a + 1] * rs0));
      const uint32_t a1 = pack_bf16(phi_f(acc[a + 2] * rs1), phi_f(acc[a + 3] * rs1));
      const uint32_t a2 = pack_bf16(phi_f(acc[a + 4] * rs0), phi_f(acc[a + 5] * rs0));
      const uint32_t a3 = pack_bf16(phi_f(acc[a + 6] * rs1), phi_f(acc[a + 7] * rs1));
      float n0[4] = {0.f, 0.f, 0.f, 0.f}, n1[4] = {0.f, 0.f, 0.f, 0.f}, dn[4] = {0.f, 0.f, 0.f, 0.f};
      mma_16816(n0, a0, a1, a2, a3, b0, b1);
      mma_16816(n1, a0, a1, a2, a3, b2, b3);
      mma_16816(dn, a0, a1, a2, a3, z0, z1);
      const float i0 = __fdividef(1.f, dn[0] + 1e-6f), i1 = __fdividef(1.f, dn[2] + 1e-6f);
      const uint32_t o0 = ~pack_bf16(n0[0] * i0, n0[1] * i0), o1 = ~pack_bf16(n0[2] * i1, n0[3] * i1);
      const uint32_t o2 = ~pack_bf16(n1[0] * i0, n1[1] * i0), o3 = ~pack_bf16(n1[2] * i1, n1[3] * i1);
      sts_u4(stash + slot * 8192 + c * 2048, o0, o1, o2, o3);
      stg_u4(xptr(slot, c), o0, o1, o2, o3);
    };
    const uint32_t kvb = area + 5 * 8192;
    const uint32_t kvfrag = kvb + ((lane & 7) + ((lane >> 3) & 1) * 8) * 32 + (lane >> 4) * 16;
    auto signal = [&](int e) INL {
      __syncwarp();
      if (lane == 0) mbar_arrive(BAR(B_EV + w * 2 + e));
    };

    float accB[32];
#pragma unroll 1
    for (int t = 0; t < 5; t++) {
      float accA[32];
      const uint32_t ph = t & 1;
      const int kindP = t == 0 ? K_NONE : ((odd && t <= 2) ? K_KV : K_GU);
      const int kindC = odd ? (t < 2 ? K_KV : K_GU) : (t < 4 ? K_GU : K_Q);
      const int slotP = odd ? t - 3 : t - 1, xslotP = odd ? t + 3 : t - 1;
      const int slotC = odd ? t - 2 : t, xslotC = odd ? t + 4 : t;
      static_for<8>([&](auto kc) INL {
        constexpr int k = decltype(kc)::value;
        mbar_wait(BAR(B_FULL + k), ph);
        wgmma_fence();
        static_for<8>([&](auto kkc) INL {
          constexpr int kk = decltype(kkc)::value;
          constexpr int i = ((k & 3) * 8 + kk) * 4;
          constexpr uint32_t lo = desc_lo(stage_off(k) + kk * 1024, 8192);
          if constexpr (k < 4) wgmma_n64_rs<((k & 3) | kk) != 0, lo, kHi64>(accA, A[i], A[i + 1], A[i + 2], A[i + 3], dbase);
          else wgmma_n64_rs<((k & 3) | kk) != 0, lo, kHi64>(accB, A[i], A[i + 1], A[i + 2], A[i + 3], dbase);
        });
        wgmma_commit();
        if (k > 0) {
          wgmma_wait<1>();
          release(k - 1);
        }
        if constexpr (k < 4) {
          if (kindP == K_GU) {
            if (k == 1 || k == 2) gu_chunk(accB, k - 1, slotP, xslotP, 1);
          } else if (kindP == K_KV) {
            if (k == 1 || k == 2) kv_stage(accB, k - 1, 1);
            if (k == 3) {
              float kvacc[36];
              const int par = xoff >= kXbufPar;
              fence_proxy_async();
              bar_sync(1 + w, 128);
              wgmma_fence();
              static_for<4>([&](auto kkc) INL {
                constexpr int kk = decltype(kkc)::value;
                wgmma_n72_ss_tt<kk != 0, desc_lo(3 * 8192 + kk * 2048, 0), desc_lo(4 * 8192 + kk * 2048, 8192 - kk * 2048)>(kvacc, dbase + w * 4096);
              });
              wgmma_commit();
              wgmma_wait<0>();
              float c[8];
#pragma unroll
              for (int i = 0; i < 8; i++)
                c[i] = wq == 0 ? kvacc[i] : (wq == 1 ? kvacc[8 + i] : (wq == 2 ? kvacc[16 + i] : kvacc[24 + i]));
              const int head = (2 * p + t - 1) * 4 + wq;
              float* kvp = &g_kv[par][head][0][0];
              red_add_v2(kvp + g * 16 + 2 * tq, c[0], c[1]);
              red_add_v2(kvp + (g + 8) * 16 + 2 * tq, c[2], c[3]);
              red_add_v2(kvp + g * 16 + 8 + 2 * tq, c[4], c[5]);
              red_add_v2(kvp + (g + 8) * 16 + 8 + 2 * tq, c[6], c[7]);
              if (tq == 0) {
                red_add(&g_z[par][head][g], kvacc[32]);
                red_add(&g_z[par][head][g + 8], kvacc[34]);
              }
              signal(t - 1);
            }
          }
        } else {
          constexpr int c = k - 4;
          if (kindC == K_GU) {
            if (c < 2) gu_chunk(accA, c, slotC, xslotC, 0);
          } else if (kindC == K_KV) {
            if (c == 0 && kindP == K_NONE) sts_u4(stash + 5 * 8192, 0x3F803F80u, 0x3F803F80u, 0x3F803F80u, 0x3F803F80u);
            if (c < 2) kv_stage(accA, c, 0);
          } else {
            if (c == 0) mbar_wait(BAR(B_KVREADY), 0);
            uint32_t b0, b1, b2, b3;
            ldmatrix_x4_trans(kvfrag + c * 512, b0, b1, b2, b3);
            const uint32_t z0 = lds_u32(kvb + 4096 + c * 32 + tq * 4), z1 = lds_u32(kvb + 4096 + c * 32 + 16 + tq * 4);
            q_head(accA, c, 4, b0, b1, b2, b3, z0, z1);
          }
        }
      });
      wgmma_wait<0>();
      release(7);
      PROF(w, 1 + 2 * t);
    }
    if (odd) {
      gu_chunk(accB, 0, 2, 8, 1);
      gu_chunk(accB, 1, 2, 8, 1);
    } else {
      uint32_t Bf[4][6];
#pragma unroll
      for (int c = 0; c < 4; c++) {
        ldmatrix_x4_trans(kvfrag + (4 + c) * 512, Bf[c][0], Bf[c][1], Bf[c][2], Bf[c][3]);
        Bf[c][4] = lds_u32(kvb + 4096 + (4 + c) * 32 + tq * 4);
        Bf[c][5] = lds_u32(kvb + 4096 + (4 + c) * 32 + 16 + tq * 4);
      }
      bar_sync(1 + w, 128);
#pragma unroll
      for (int c = 0; c < 4; c++) q_head(accB, c, 5, Bf[c][0], Bf[c][1], Bf[c][2], Bf[c][3], Bf[c][4], Bf[c][5]);
    }
    PROF(w, 10);

    const int n_own = odd ? 3 : 6;
    auto load_a = [&](int kb) INL {
      if (kb < n_own) {
#pragma unroll
        for (int jj = 0; jj < 4; jj++) {
          const int i = (kb * 4 + jj) * 4;
          lds_u4(stash + kb * 8192 + jj * 2048, A[i], A[i + 1], A[i + 2], A[i + 3]);
        }
      } else {
        const int xs = odd ? kb - 3 : kb;
#pragma unroll
        for (int jj = 0; jj < 4; jj++) {
          const int i = (kb * 4 + jj) * 4;
          ldg_poll_u4(xptr(xs, jj), A[i], A[i + 1], A[i + 2], A[i + 3]);
        }
      }
    };
    auto fix_a = [&](int kb) INL {
      if (kb >= n_own) {
        const int xs = odd ? kb - 3 : kb;
        recv_group<4>(xptr(xs, 0), &A[kb * 16]);
      } else {
#pragma unroll
        for (int i = 0; i < 16; i++) A[kb * 16 + i] = ~A[kb * 16 + i];
      }
    };
#pragma unroll
    for (int kb = 0; kb < 7; kb++) load_a(kb);
    PROF(w, 11);

    const int orow = m * 128 + w * 64 + wq * 16 + g;
    const int ocol = odd * 256 + p * 64 + 2 * tq;
    float acc2[2][32];
    uint32_t poff = (uint32_t)((m * 2 + odd) * 24 + w) * 8192u + (uint32_t)t128 * 16u + (xoff >= kXbufPar ? kPbufPar : 0u);
    asm volatile("" : "+r"(poff));
    auto pptr = [&](int dest, int sl) INL { return (uint4*)((char*)g_pbuf + (poff + (uint32_t)(dest * 3 + sl) * 16384u)); };
    uint32_t P[3][16];
    uint32_t xr[16];
    auto send = [&](float (&acc)[32], int bi) INL {
      uint4* dst = pptr((p + 1 + bi) & 3, bi);
#pragma unroll
      for (int q = 0; q < 4; q++)
        stg_u4(dst + q * 128, ~pack_bf16(acc[q * 8], acc[q * 8 + 1]), ~pack_bf16(acc[q * 8 + 2], acc[q * 8 + 3]),
               ~pack_bf16(acc[q * 8 + 4], acc[q * 8 + 5]), ~pack_bf16(acc[q * 8 + 6], acc[q * 8 + 7]));
      PROF(w, 12 + 2 * bi);
    };
    auto fetch = [&](int sl) INL {
#pragma unroll
      for (int q = 0; q < 4; q++) ldg_poll_u4(pptr(p, sl) + q * 128, P[sl][q * 4], P[sl][q * 4 + 1], P[sl][q * 4 + 2], P[sl][q * 4 + 3]);
    };
    static_for<36>([&](auto ic) INL {
      constexpr int i = decltype(ic)::value, bi = p2_bi(i), kb = p2_kb(i), j = i >> 1, st = j & 7;
      if (i == 9) { load_a(7); load_a(8); }
      if (i == 14) PROF(w, 2);
      if (bi == 0) fix_a(kb);
      if (i == 15) PROF(w, 4);
      if (i == 7) PROF(w, 6);
      if ((i & 1) == 0) mbar_wait(BAR(B_FULL + st), (5 + (j >> 3)) & 1);
      wgmma_fence();
      static_for<4>([&](auto kkc) INL {
        constexpr int kk = decltype(kkc)::value, a = (kb * 4 + kk) * 4;
        wgmma_n64_rs<(kb | kk) != 0, desc_lo(stage_off(st) + (i & 1) * 8192 + kk * 2048, 0), kHi128>(acc2[bi & 1], A[a], A[a + 1], A[a + 2], A[a + 3], dbase);
      });
      wgmma_commit();
      if (i > 0) {
        wgmma_wait<1>();
        if ((i & 1) == 0 && j - 1 <= 9) release((j - 1) & 7);
      }
      if constexpr (i == 16) send(acc2[0], 0);
      if constexpr (i == 18) send(acc2[1], 1);
      if constexpr (i == 27) send(acc2[0], 2);
      if constexpr (i == 29) fetch(0);
      if constexpr (i == 31) fetch(1);
      if constexpr (i == 32) {
#pragma unroll
        for (int q = 0; q < 8; q++) {
          xr[2 * q] = __ldg((const uint32_t*)(x + (size_t)orow * kD + ocol + q * 8));
          xr[2 * q + 1] = __ldg((const uint32_t*)(x + (size_t)(orow + 8) * kD + ocol + q * 8));
        }
      }
      if constexpr (i == 34) fetch(2);
    });
#pragma unroll
    for (int sl = 0; sl < 3; sl++) { PROF(w, 13 + 2 * sl); recv_group<4>(pptr(p, sl), &P[sl][0]); }
    wgmma_wait<0>();
    PROF(w, 18);
#pragma unroll
    for (int q = 0; q < 8; q++) {
      float rr[4];
      rr[0] = acc2[1][q * 4 + 0] + __uint_as_float(xr[2 * q] << 16);
      rr[1] = acc2[1][q * 4 + 1] + __uint_as_float(xr[2 * q] & 0xffff0000u);
      rr[2] = acc2[1][q * 4 + 2] + __uint_as_float(xr[2 * q + 1] << 16);
      rr[3] = acc2[1][q * 4 + 3] + __uint_as_float(xr[2 * q + 1] & 0xffff0000u);
#pragma unroll
      for (int sl = 0; sl < 3; sl++) {
        rr[0] += __uint_as_float(P[sl][2 * q] << 16);
        rr[1] += __uint_as_float(P[sl][2 * q] & 0xffff0000u);
        rr[2] += __uint_as_float(P[sl][2 * q + 1] << 16);
        rr[3] += __uint_as_float(P[sl][2 * q + 1] & 0xffff0000u);
      }
      *(uint32_t*)(out + (size_t)orow * kD + ocol + q * 8) = pack_bf16(rr[0], rr[1]);
      *(uint32_t*)(out + (size_t)(orow + 8) * kD + ocol + q * 8) = pack_bf16(rr[2], rr[3]);
    }
    PROF(w, 19);
    if (tid == 0) {
      const uint32_t old = atomicAdd(&g_done, 1u);
      if ((old & 127u) == 127u) st_relaxed(&g_epoch, ld_relaxed(&g_epoch) + 1u);
    }
  }
#undef BAR
}

typedef CUresult (*EncodeFn)(CUtensorMap*, CUtensorMapDataType, cuuint32_t, void*, const cuuint64_t*, const cuuint64_t*,
                             const cuuint32_t*, const cuuint32_t*, CUtensorMapInterleave, CUtensorMapSwizzle,
                             CUtensorMapL2promotion, CUtensorMapFloatOOBfill);

void make_map(EncodeFn enc, CUtensorMap* tm, const void* ptr, int rows, int cols, bool narrow) {
  cuuint64_t gd[2] = {(cuuint64_t)cols, (cuuint64_t)rows};
  cuuint64_t gs[1] = {(cuuint64_t)cols * 2};
  cuuint32_t bd[2] = {narrow ? 32u : 64u, narrow ? 128u : 64u};
  cuuint32_t es[2] = {1, 1};
  enc(tm, CU_TENSOR_MAP_DATA_TYPE_BFLOAT16, 2, const_cast<void*>(ptr), gd, gs, bd, es, CU_TENSOR_MAP_INTERLEAVE_NONE,
      narrow ? CU_TENSOR_MAP_SWIZZLE_64B : CU_TENSOR_MAP_SWIZZLE_128B, CU_TENSOR_MAP_L2_PROMOTION_L2_256B, CU_TENSOR_MAP_FLOAT_OOB_FILL_NONE);
}

}

extern "C" void kernel_launch(void* const* d_in, const int* in_sizes, int n_in, void* d_out, int out_size) {
  static EncodeFn enc = nullptr;
  if (!enc) {
    void* fn = nullptr;
    cudaDriverEntryPointQueryResult qr;
    cudaGetDriverEntryPoint("cuTensorMapEncodeTiled", &fn, cudaEnableDefault, &qr);
    enc = (EncodeFn)fn;
    cudaFuncSetAttribute(fused_kernel, cudaFuncAttributeMaxDynamicSharedMemorySize, kSmemBytes);
  }
  CUtensorMap tm_x, tm_wqkv, tm_w1, tm_w3, tm_w2, tm_wo;
  make_map(enc, &tm_x, d_in[0], kS, kD, false);
  make_map(enc, &tm_wqkv, d_in[1], kD, 3 * kD, true);
  make_map(enc, &tm_wo, d_in[2], kD, kD, false);
  make_map(enc, &tm_w1, d_in[4], kD, kF, true);
  make_map(enc, &tm_w3, d_in[5], kD, kF, true);
  make_map(enc, &tm_w2, d_in[6], kF, kD, false);
  fused_kernel<<<128, 384, kSmemBytes>>>(tm_x, tm_wqkv, tm_w1, tm_w3, tm_w2, tm_wo, (const __nv_bfloat16*)d_in[0],
                                         (__nv_bfloat16*)d_out);
}
```

```cpp
#include <cuda_runtime.h>
#include <cuda_bf16.h>
#include <cuda.h>
#include <stdint.h>

namespace {

constexpr int kS = 2048, kD = 512, kF = 1792;
constexpr uint32_t kSpinLimit = 1u << 22;

__device__ uint4    g_xbuf[2][16][4][9][2][4][128];
__device__ uint4    g_pbuf[2][16][2][4][3][2][4][128];
constexpr uint32_t kXbufPar = 16u * 4 * 9 * 2 * 8192, kPbufPar = 16u * 2 * 4 * 3 * 2 * 8192;
__device__ float    g_kv[2][32][16][16];
__device__ float    g_z[2][32][16];
__device__ uint32_t g_kvcnt[4][32];
__device__ uint32_t g_epoch;
__device__ uint32_t g_done;
#define PROF(wg, i) do {} while (0)

__device__ __forceinline__ uint32_t smem_u32(const void* p) { return (uint32_t)__cvta_generic_to_shared(p); }
__device__ __forceinline__ void mbar_init(uint32_t bar, uint32_t cnt) {
  asm volatile("mbarrier.init.shared::cta.b64 [%0], %1;" ::"r"(bar), "r"(cnt) : "memory");
}
__device__ __forceinline__ void mbar_expect_tx(uint32_t bar, uint32_t bytes) {
  asm volatile("mbarrier.arrive.expect_tx.shared::cta.b64 _, [%0], %1;" ::"r"(bar), "r"(bytes) : "memory");
}
__device__ __forceinline__ void mbar_arrive(uint32_t bar) {
  asm volatile("mbarrier.arrive.shared::cta.b64 _, [%0];" ::"r"(bar) : "memory");
}
__device__ __forceinline__ void mbar_wait(uint32_t bar, uint32_t parity) {
  asm volatile(
      "{\n.reg .pred p;\n"
      "LAB_WAIT:\n"
      "mbarrier.try_wait.parity.shared::cta.b64 p, [%0], %1;\n"
      "@p bra DONE;\n"
      "bra LAB_WAIT;\n"
      "DONE:\n}" ::"r"(bar), "r"(parity) : "memory");
}
__device__ __forceinline__ void tma_load_2d(uint32_t dst, const CUtensorMap* tm, uint32_t bar, int c0, int c1) {
  asm volatile(
      "cp.async.bulk.tensor.2d.shared::cluster.global.mbarrier::complete_tx::bytes [%0], [%1, {%3, %4}], [%2];" ::"r"(dst),
      "l"(tm), "r"(bar), "r"(c0), "r"(c1)
      : "memory");
}
__device__ __forceinline__ void tma_load_2d_mc(uint32_t dst, const CUtensorMap* tm, uint32_t bar, int c0, int c1) {
  asm volatile(
      "cp.async.bulk.tensor.2d.shared::cluster.global.mbarrier::complete_tx::bytes.multicast::cluster [%0], [%1, {%3, %4}], [%2], %5;" ::"r"(dst),
      "l"(tm), "r"(bar), "r"(c0), "r"(c1), "h"((uint16_t)3)
      : "memory");
}
__device__ __forceinline__ void mbar_arrive_cluster(uint32_t bar, uint32_t cta) {
  asm volatile("{\n.reg .b32 ra;\nmapa.shared::cluster.u32 ra, %0, %1;\nmbarrier.arrive.shared::cluster.b64 _, [ra];\n}" ::"r"(bar), "r"(cta) : "memory");
}
__device__ __forceinline__ void prefetch_tmap(const CUtensorMap* tm) {
  asm volatile("prefetch.tensormap [%0];" ::"l"(tm) : "memory");
}
__device__ __forceinline__ void wgmma_fence() { asm volatile("wgmma.fence.sync.aligned;" ::: "memory"); }
__device__ __forceinline__ void wgmma_commit() { asm volatile("wgmma.commit_group.sync.aligned;" ::: "memory"); }
template <int N>
__device__ __forceinline__ void wgmma_wait() { asm volatile("wgmma.wait_group.sync.aligned %0;" ::"n"(N) : "memory"); }
__device__ __forceinline__ void bar_sync(int id, int n) { asm volatile("bar.sync %0, %1;" ::"r"(id), "r"(n) : "memory"); }
__device__ __forceinline__ void bar_arrive(int id, int n) { asm volatile("bar.arrive %0, %1;" ::"r"(id), "r"(n) : "memory"); }
__device__ __forceinline__ void fence_proxy_async() { asm volatile("fence.proxy.async.shared::cta;" ::: "memory"); }

__device__ __forceinline__ uint32_t ld_acquire(const uint32_t* p) {
  uint32_t v;
  asm volatile("ld.acquire.gpu.global.u32 %0, [%1];" : "=r"(v) : "l"(p) : "memory");
  return v;
}
__device__ __forceinline__ uint32_t ld_relaxed(const uint32_t* p) {
  uint32_t v;
  asm volatile("ld.relaxed.gpu.global.u32 %0, [%1];" : "=r"(v) : "l"(p));
  return v;
}
__device__ __forceinline__ void cluster_wait() { asm volatile("barrier.cluster.wait.aligned;" ::: "memory"); }
__device__ __forceinline__ void st_relaxed(uint32_t* p, uint32_t v) {
  asm volatile("st.relaxed.gpu.global.u32 [%0], %1;" ::"l"(p), "r"(v) : "memory");
}
__device__ __forceinline__ void wait_flag_eq(const uint32_t* p, uint32_t val) {
  uint32_t it = 0;
  while (ld_acquire(p) != val) {
    if (++it > kSpinLimit) break;
  }
}
__device__ __forceinline__ void wait_count_ge(const uint32_t* p, uint32_t val) {
  uint32_t it = 0;
  while ((int32_t)(ld_acquire(p) - val) < 0) {
    __nanosleep(64);
    if (++it > kSpinLimit) break;
  }
}
__device__ __forceinline__ void ldg_poll_u4(const void* p, uint32_t& a, uint32_t& b, uint32_t& c, uint32_t& d) {
  asm volatile("ld.relaxed.gpu.global.v4.u32 {%0,%1,%2,%3}, [%4];" : "=r"(a), "=r"(b), "=r"(c), "=r"(d) : "l"(p) : "memory");
}
template <int N>
__device__ __forceinline__ void recv_group(uint4* p, uint32_t* r) {
  uint32_t it = 0;
  while (true) {
    uint32_t mn = 0xffffffffu;
#pragma unroll
    for (int i = 0; i < 4 * N; i++) mn = min(mn, r[i]);
    if (!__any_sync(0xffffffffu, mn == 0u) || ++it > kSpinLimit) break;
#pragma unroll
    for (int q = 0; q < N; q++) ldg_poll_u4(p + q * 128, r[q * 4], r[q * 4 + 1], r[q * 4 + 2], r[q * 4 + 3]);
  }
#pragma unroll
  for (int i = 0; i < 4 * N; i++) r[i] = ~r[i];
}
__device__ __forceinline__ float4 ldg_cg_f4(const void* p) {
  float4 v;
  asm volatile("ld.global.cg.v4.f32 {%0,%1,%2,%3}, [%4];" : "=f"(v.x), "=f"(v.y), "=f"(v.z), "=f"(v.w) : "l"(p) : "memory");
  return v;
}
__device__ __forceinline__ void stg_u4(void* p, uint32_t a, uint32_t b, uint32_t c, uint32_t d) {
  asm volatile("st.global.v4.u32 [%0], {%1,%2,%3,%4};" ::"l"(p), "r"(a), "r"(b), "r"(c), "r"(d) : "memory");
}
__device__ __forceinline__ void stg_f4(void* p, float a, float b, float c, float d) {
  asm volatile("st.global.v4.f32 [%0], {%1,%2,%3,%4};" ::"l"(p), "f"(a), "f"(b), "f"(c), "f"(d) : "memory");
}
__device__ __forceinline__ void sts_u4(uint32_t addr, uint32_t a, uint32_t b, uint32_t c, uint32_t d) {
  asm volatile("st.shared.v4.u32 [%0], {%1,%2,%3,%4};" ::"r"(addr), "r"(a), "r"(b), "r"(c), "r"(d) : "memory");
}
__device__ __forceinline__ void lds_u4(uint32_t addr, uint32_t& a, uint32_t& b, uint32_t& c, uint32_t& d) {
  asm volatile("ld.shared.v4.u32 {%0,%1,%2,%3}, [%4];" : "=r"(a), "=r"(b), "=r"(c), "=r"(d) : "r"(addr) : "memory");
}
__device__ __forceinline__ uint32_t lds_u32(uint32_t addr) {
  uint32_t v;
  asm volatile("ld.shared.u32 %0, [%1];" : "=r"(v) : "r"(addr) : "memory");
  return v;
}
__device__ __forceinline__ void ldmatrix_x4(uint32_t addr, uint32_t& a, uint32_t& b, uint32_t& c, uint32_t& d) {
  asm volatile("ldmatrix.sync.aligned.m8n8.x4.shared.b16 {%0,%1,%2,%3}, [%4];" : "=r"(a), "=r"(b), "=r"(c), "=r"(d) : "r"(addr) : "memory");
}
__device__ __forceinline__ void ldmatrix_x4_trans(uint32_t addr, uint32_t& a, uint32_t& b, uint32_t& c, uint32_t& d) {
  asm volatile("ldmatrix.sync.aligned.m8n8.x4.trans.shared.b16 {%0,%1,%2,%3}, [%4];" : "=r"(a), "=r"(b), "=r"(c), "=r"(d) : "r"(addr) : "memory");
}
__device__ __forceinline__ void stmatrix_x4(uint32_t addr, uint32_t a, uint32_t b, uint32_t c, uint32_t d) {
  asm volatile("stmatrix.sync.aligned.m8n8.x4.shared.b16 [%0], {%1,%2,%3,%4};" ::"r"(addr), "r"(a), "r"(b), "r"(c), "r"(d) : "memory");
}
__device__ __forceinline__ void mma_16816(float (&c)[4], uint32_t a0, uint32_t a1, uint32_t a2, uint32_t a3, uint32_t b0, uint32_t b1) {
  asm volatile(
      "mma.sync.aligned.m16n8k16.row.col.f32.bf16.bf16.f32 {%0,%1,%2,%3}, {%4,%5,%6,%7}, {%8,%9}, {%0,%1,%2,%3};"
      : "+f"(c[0]), "+f"(c[1]), "+f"(c[2]), "+f"(c[3])
      : "r"(a0), "r"(a1), "r"(a2), "r"(a3), "r"(b0), "r"(b1));
}
__device__ __forceinline__ uint32_t pack_bf16(float lo, float hi) {
  uint32_t r;
  asm("cvt.rn.bf16x2.f32 %0, %1, %2;" : "=r"(r) : "f"(hi), "f"(lo));
  return r;
}
__device__ __forceinline__ uint32_t hsub2_bf16(uint32_t a, uint32_t b) {
  uint32_t r;
  asm("sub.rn.bf16x2 %0, %1, %2;" : "=r"(r) : "r"(a), "r"(b));
  return r;
}
__device__ __forceinline__ float ex2f(float x) {
  float r;
  asm("ex2.approx.ftz.f32 %0, %1;" : "=f"(r) : "f"(x));
  return r;
}
__device__ __forceinline__ float rcpf(float x) {
  float r;
  asm("rcp.approx.ftz.f32 %0, %1;" : "=f"(r) : "f"(x));
  return r;
}
__device__ __forceinline__ void red_add_v2(float* p, float a, float b) {
  asm volatile("red.relaxed.gpu.global.add.v2.f32 [%0], {%1,%2};" ::"l"(p), "f"(a), "f"(b) : "memory");
}
__device__ __forceinline__ void red_add(float* p, float a) {
  asm volatile("red.relaxed.gpu.global.add.f32 [%0], %1;" ::"l"(p), "f"(a) : "memory");
}
__device__ __forceinline__ float phi_f(float t) {
  float e = ex2f(t * 1.4426950408889634f);
  return (t > 0.f ? t + 1.f : e) + 1e-6f;
}

#define R8(a, o) "+f"(a[o + 0]), "+f"(a[o + 1]), "+f"(a[o + 2]), "+f"(a[o + 3]), "+f"(a[o + 4]), "+f"(a[o + 5]), "+f"(a[o + 6]), "+f"(a[o + 7])

#define W8(a, o) "=f"(a[o + 0]), "=f"(a[o + 1]), "=f"(a[o + 2]), "=f"(a[o + 3]), "=f"(a[o + 4]), "=f"(a[o + 5]), "=f"(a[o + 6]), "=f"(a[o + 7])
#define D32 "{%0,%1,%2,%3,%4,%5,%6,%7,%8,%9,%10,%11,%12,%13,%14,%15,%16,%17,%18,%19,%20,%21,%22,%23,%24,%25,%26,%27,%28,%29,%30,%31}"
#define D36 "{%0,%1,%2,%3,%4,%5,%6,%7,%8,%9,%10,%11,%12,%13,%14,%15,%16,%17,%18,%19,%20,%21,%22,%23,%24,%25,%26,%27,%28,%29,%30,%31,%32,%33,%34,%35}"

constexpr uint32_t kHi128 = (1024u >> 4) | (1u << 30);
constexpr uint32_t kHi64 = (512u >> 4) | (2u << 30);
__host__ __device__ constexpr uint32_t desc_lo(uint32_t off, uint32_t lbo) { return (off >> 4) | ((lbo >> 4) << 16); }

template <bool ACC, uint32_t LO, uint32_t HI>
__device__ __forceinline__ void wgmma_n64_rs(float (&d)[32], uint32_t a0, uint32_t a1, uint32_t a2, uint32_t a3, uint32_t base) {
  if (ACC) {
    asm volatile(
        "{\n.reg .pred p;\n.reg .b32 lo;\n.reg .b64 dd;\nsetp.eq.b32 p, 0, 0;\nadd.u32 lo, %36, %37;\nmov.b64 dd, {lo, %38};\n"
        "wgmma.mma_async.sync.aligned.m64n64k16.f32.bf16.bf16 " D32 ", {%32,%33,%34,%35}, dd, p, 1, 1, 1;\n}"
        : R8(d, 0), R8(d, 8), R8(d, 16), R8(d, 24)
        : "r"(a0), "r"(a1), "r"(a2), "r"(a3), "r"(base), "n"(LO), "n"(HI));
  } else {
    asm volatile(
        "{\n.reg .pred p;\n.reg .b32 lo;\n.reg .b64 dd;\nsetp.ne.b32 p, 0, 0;\nadd.u32 lo, %36, %37;\nmov.b64 dd, {lo, %38};\n"
        "wgmma.mma_async.sync.aligned.m64n64k16.f32.bf16.bf16 " D32 ", {%32,%33,%34,%35}, dd, p, 1, 1, 1;\n}"
        : W8(d, 0), W8(d, 8), W8(d, 16), W8(d, 24)
        : "r"(a0), "r"(a1), "r"(a2), "r"(a3), "r"(base), "n"(LO), "n"(HI));
  }
}
template <bool ACC, uint32_t LOA, uint32_t LOB>
__device__ __forceinline__ void wgmma_n72_ss_tt(float (&d)[36], uint32_t base) {
  if (ACC) {
    asm volatile(
        "{\n.reg .pred p;\n.reg .b32 lo;\n.reg .b64 da, db;\nsetp.eq.b32 p, 0, 0;\n"
        "add.u32 lo, %36, %37;\nmov.b64 da, {lo, %39};\nadd.u32 lo, %36, %38;\nmov.b64 db, {lo, %39};\n"
        "wgmma.mma_async.sync.aligned.m64n72k16.f32.bf16.bf16 " D36 ", da, db, p, 1, 1, 1, 1;\n}"
        : R8(d, 0), R8(d, 8), R8(d, 16), R8(d, 24), "+f"(d[32]), "+f"(d[33]), "+f"(d[34]), "+f"(d[35])
        : "r"(base), "n"(LOA), "n"(LOB), "n"(kHi128));
  } else {
    asm volatile(
        "{\n.reg .pred p;\n.reg .b32 lo;\n.reg .b64 da, db;\nsetp.ne.b32 p, 0, 0;\n"
        "add.u32 lo, %36, %37;\nmov.b64 da, {lo, %39};\nadd.u32 lo, %36, %38;\nmov.b64 db, {lo, %39};\n"
        "wgmma.mma_async.sync.aligned.m64n72k16.f32.bf16.bf16 " D36 ", da, db, p, 1, 1, 1, 1;\n}"
        : W8(d, 0), W8(d, 8), W8(d, 16), W8(d, 24), "=f"(d[32]), "=f"(d[33]), "=f"(d[34]), "=f"(d[35])
        : "r"(base), "n"(LOA), "n"(LOB), "n"(kHi128));
  }
}

#define INL __attribute__((always_inline))
template <int V> struct IC { static constexpr int value = V; };
template <int N, int I = 0, typename F>
__device__ __forceinline__ void static_for(F&& f) {
  if constexpr (I < N) { f(IC<I>{}); static_for<N, I + 1>(f); }
}

__host__ __device__ constexpr uint32_t stage_off(int st) {
  return st < 6 ? 131072u + (uint32_t)st * 16384u : (uint32_t)(st - 6) * 65536u + 49152u;
}

constexpr int B_FULL = 0, B_EMPTY = 8, B_XFULL = 16, B_XDONE = 32, B_KVREADY = 33, B_EV = 34, B_COUNT = 38;
constexpr uint32_t kBarOff = 229376;
constexpr int kSmemBytes = 229376 + 1024;

__host__ __device__ constexpr int p2_bi(int i) { return i < 7 ? 0 : i < 14 ? 1 : i < 16 ? 0 : i < 18 ? 1 : i / 9; }
__host__ __device__ constexpr int p2_kb(int i) { return i < 7 ? i : i < 14 ? i - 7 : i < 16 ? i - 7 : i < 18 ? i - 9 : i % 9; }

enum { K_NONE = 0, K_GU = 1, K_KV = 2, K_Q = 3 };

__global__ void __cluster_dims__(2, 1, 1) __launch_bounds__(384, 1)
fused_kernel(const __grid_constant__ CUtensorMap tm_x, const __grid_constant__ CUtensorMap tm_wqkv,
             const __grid_constant__ CUtensorMap tm_w1, const __grid_constant__ CUtensorMap tm_w3,
             const __grid_constant__ CUtensorMap tm_w2, const __grid_constant__ CUtensorMap tm_wo,
             const __nv_bfloat16* __restrict__ x, __nv_bfloat16* __restrict__ out) {
  extern __shared__ __align__(1024) uint8_t smem_raw[];
  const uint32_t sbase = smem_u32(smem_raw);
  const uint32_t bars = sbase + kBarOff;
  const int tid = threadIdx.x, lane = tid & 31;
  const int warp = __shfl_sync(0xffffffffu, tid >> 5, 0);
  const int cr = blockIdx.x & 1;
  const int r = (blockIdx.x >> 1) & 7, m = ((blockIdx.x >> 4) << 1) | cr, p = r >> 1, odd = r & 1;
#define BAR(i) (bars + 8u * (uint32_t)(i))
  if (tid == 256) {
    if (sbase & 1023u) __trap();
#pragma unroll
    for (int i = 0; i < 16; i++) mbar_init(BAR(B_XFULL + i), 1);
    fence_proxy_async();
#pragma unroll
    for (int b = 0; b < 16; b++) {
      mbar_expect_tx(BAR(B_XFULL + b), 8192);
      tma_load_2d(sbase + (b >> 3) * 65536 + (b & 7) * 8192, &tm_x, BAR(B_XFULL + b), (b & 7) * 64, m * 128 + (b >> 3) * 64);
    }
#pragma unroll
    for (int i = 0; i < 8; i++) { mbar_init(BAR(B_FULL + i), 1); mbar_init(BAR(B_EMPTY + i), 4); }
#pragma unroll
    for (int i = 0; i < 4; i++) mbar_init(BAR(B_EV + i), 4);
    mbar_init(BAR(B_XDONE), 2);
    mbar_init(BAR(B_KVREADY), 1);
    asm volatile("fence.mbarrier_init.release.cluster;" ::: "memory");
    fence_proxy_async();
  } else if (tid == 288) {
    prefetch_tmap(odd ? &tm_wqkv : (cr ? &tm_w3 : &tm_w1));
  }
  __syncwarp();
  asm volatile("barrier.cluster.arrive.relaxed.aligned;" ::: "memory");
  PROF((tid >> 7), 21);
  __syncthreads();

  if (warp >= 8) {
    asm volatile("setmaxnreg.dec.sync.aligned.u32 24;");
    PROF(2, 3);
    cluster_wait();
    PROF(2, 2);
    const uint32_t epoch = warp == 8 ? 0u : ld_relaxed(&g_epoch);
    const uint32_t tag = epoch + 1u;
    const int par = epoch & 1;
    if (warp == 8) {
      if (lane == 0) {
        for (int j = 0; j < 10; j++) {
          const CUtensorMap* tm;
          int col;
          if (!odd) {
            if (j < 8) { tm = cr ? &tm_w3 : &tm_w1; col = 7 * p * 64 + j * 32; }
            else { tm = &tm_wqkv; col = 128 * p + (j - 8) * 64 + cr * 32; }
          } else {
            if (j < 4) { tm = &tm_wqkv; col = 512 + cr * 512 + 128 * p + j * 32; }
            else { tm = cr ? &tm_w3 : &tm_w1; col = (7 * p + 4) * 64 + (j - 4) * 32; }
          }
          const int t = j >> 1;
          for (int kq = 0; kq < 4; kq++) {
            const int k = (j & 1) * 4 + kq;
            mbar_wait(BAR(B_EMPTY + k), k < 6 ? ((t & 1) ^ 1) : (t & 1));
            mbar_expect_tx(BAR(B_FULL + k), 16384);
            tma_load_2d_mc(sbase + stage_off(k) + cr * 8192, tm, BAR(B_FULL + k), col, kq * 128);
          }
        }
        for (int j = 0; j < 18; j++) {
          const int st = j & 7, n = 5 + (j >> 3);
          const int i = 2 * j + cr;
          const int bi = p2_bi(i), kb = p2_kb(i);
          const int col = odd * 256 + ((p + 1 + bi) & 3) * 64;
          const CUtensorMap* tmk;
          int row;
          if (!odd) {
            if (kb < 4) { tmk = &tm_w2; row = (7 * p + kb) * 64; }
            else if (kb < 6) { tmk = &tm_wo; row = (2 * p + kb - 4) * 64; }
            else { tmk = &tm_w2; row = (7 * p + 4 + kb - 6) * 64; }
          } else {
            if (kb < 3) { tmk = &tm_w2; row = (7 * p + 4 + kb) * 64; }
            else if (kb < 7) { tmk = &tm_w2; row = (7 * p + kb - 3) * 64; }
            else { tmk = &tm_wo; row = (2 * p + kb - 7) * 64; }
          }
          mbar_wait(BAR(B_EMPTY + st), st < 6 ? ((n & 1) ^ 1) : (n & 1));
          mbar_expect_tx(BAR(B_FULL + st), 16384);
          tma_load_2d_mc(sbase + stage_off(st) + cr * 8192, tmk, BAR(B_FULL + st), col, row);
        }
      }
    } else if (warp <= 10) {
      {
        const int w = warp - 9;
        mbar_wait(BAR(B_XDONE), 0);
        const uint4 zero = make_uint4(0u, 0u, 0u, 0u);
        const int x0 = odd ? 0 : 6, nx = odd ? 6 : 3;
        for (int sl = 0; sl < nx; sl++) {
          uint4* d = &g_xbuf[par ^ 1][m][p][x0 + sl][w][0][0];
          for (int i = lane; i < 512; i += 32) d[i] = zero;
          __nanosleep(300);
        }
        for (int sl = 0; sl < 3; sl++) {
          uint4* d = &g_pbuf[par ^ 1][m][odd][p][sl][w][0][0];
          for (int i = lane; i < 512; i += 32) d[i] = zero;
        }
      }
      if (lane == 0 && odd) {
        const int w = warp - 9;
        for (int e = 0; e < 2; e++) {
          mbar_wait(BAR(B_EV + w * 2 + e), 0);
          __threadfence();
          atomicAdd(&g_kvcnt[p][0], 1u);
        }
      }
    } else {
      if (!odd) {
        {
          const int ce = m * 4 + p;
          float* kvn = &g_kv[par ^ 1][0][0][0];
          for (int i = lane; i < 128; i += 32) kvn[ce * 128 + i] = 0.f;
          if (lane < 8) (&g_z[par ^ 1][0][0])[ce * 8 + lane] = 0.f;
        }
        mbar_wait(BAR(B_XDONE), 0);
        wait_count_ge(&g_kvcnt[p][0], 64u * tag);
        const float* kvp = &g_kv[par][8 * p][0][0];
        const uint32_t dst0 = sbase + 5 * 8192, dst1 = dst0 + 65536;
#pragma unroll 4
        for (int i = 0; i < 16; i++) {
          float4 v = ldg_cg_f4(kvp + (i * 32 + lane) * 4);
          uint32_t lo = pack_bf16(v.x, v.y), hi = pack_bf16(v.z, v.w);
          uint32_t off = (uint32_t)(i * 32 + lane) * 8u;
          asm volatile("st.shared.v2.u32 [%0], {%1,%2};" ::"r"(dst0 + off), "r"(lo), "r"(hi) : "memory");
          asm volatile("st.shared.v2.u32 [%0], {%1,%2};" ::"r"(dst1 + off), "r"(lo), "r"(hi) : "memory");
        }
        {
          float4 v = ldg_cg_f4(&g_z[par][8 * p][0] + lane * 4);
          uint32_t lo = pack_bf16(v.x, v.y), hi = pack_bf16(v.z, v.w);
          uint32_t off = 4096u + (uint32_t)lane * 8u;
          asm volatile("st.shared.v2.u32 [%0], {%1,%2};" ::"r"(dst0 + off), "r"(lo), "r"(hi) : "memory");
          asm volatile("st.shared.v2.u32 [%0], {%1,%2};" ::"r"(dst1 + off), "r"(lo), "r"(hi) : "memory");
        }
        __syncwarp();
        if (lane == 0) mbar_arrive(BAR(B_KVREADY));
      }
    }
  } else {
    asm volatile("setmaxnreg.inc.sync.aligned.u32 240;");
    const int w = warp >> 2, wq = warp & 3, t128 = tid & 127;
    const int g = lane >> 2, tq = lane & 3;
    const uint32_t area = sbase + (uint32_t)w * 65536u;
    const bool elect = (t128 == 0);
    PROF(w, 22);
    const uint32_t dbase = (sbase & 0x3FFFFu) >> 4;
    uint32_t xoff = (uint32_t)((m * 4 + p) * 18 + w) * 8192u + (uint32_t)t128 * 16u;
    uint32_t stash = area + (uint32_t)t128 * 16u;
    const uint32_t epoch_c = ld_relaxed(&g_epoch);
    auto xptr = [&](int slot, int jj) INL { return (uint4*)((char*)g_xbuf + (xoff + (uint32_t)slot * 16384u + (uint32_t)jj * 2048u)); };
    uint32_t A[144];
    float rs0, rs1;
    auto release = [&](int st) INL {
      if (elect) { mbar_arrive_cluster(BAR(B_EMPTY + st), 0); mbar_arrive_cluster(BAR(B_EMPTY + st), 1); }
    };

    {
      const int row = wq * 16 + (lane & 7) + ((lane >> 3) & 1) * 8;
      const uint32_t rbase = area + row * 128;
      float s0[2][4] = {}, q0[2][4] = {}, q1[2][4] = {};
      const uint32_t ones = 0x3F803F80u;
#pragma unroll
      for (int b = 0; b < 8; b++) {
        mbar_wait(BAR(B_XFULL + w * 8 + b), 0);
        if (b == 0) PROF(w, 23);
        if (b == 7) PROF(w, 24);
#pragma unroll
        for (int kk = 0; kk < 4; kk++) {
          const int i = (b * 4 + kk) * 4;
          ldmatrix_x4(rbase + b * 8192 + (((kk * 2 + (lane >> 4)) ^ (row & 7)) << 4), A[i], A[i + 1], A[i + 2], A[i + 3]);
        }
#pragma unroll
        for (int kk = 0; kk < 4; kk++) {
          const int i = (b * 4 + kk) * 4;
          mma_16816(s0[kk & 1], A[i], A[i + 1], A[i + 2], A[i + 3], ones, ones);
          mma_16816(q0[kk & 1], A[i], A[i + 1], A[i + 2], A[i + 3], A[i], A[i + 2]);
          mma_16816(q1[kk & 1], A[i], A[i + 1], A[i + 2], A[i + 3], A[i + 1], A[i + 3]);
        }
      }
      const float mean0 = (s0[0][0] + s0[1][0]) * (1.f / 512.f), mean1 = (s0[0][2] + s0[1][2]) * (1.f / 512.f);
      const uint32_t m0 = pack_bf16(mean0, mean0), m1 = pack_bf16(mean1, mean1);
#pragma unroll
      for (int i = 0; i < 128; i += 2) {
        A[i] = hsub2_bf16(A[i], m0);
        A[i + 1] = hsub2_bf16(A[i + 1], m1);
      }
      float v0 = (g & 1) ? q0[0][1] + q0[1][1] : q0[0][0] + q0[1][0];
      float v1 = (g & 1) ? q1[0][3] + q1[1][3] : q1[0][2] + q1[1][2];
      const int src = 4 * g + (g >> 1);
      v0 = __shfl_sync(0xffffffffu, v0, src);
      v1 = __shfl_sync(0xffffffffu, v1, src);
      v0 = fmaxf(v0 * (1.f / 512.f) - mean0 * mean0, 0.f);
      v1 = fmaxf(v1 * (1.f / 512.f) - mean1 * mean1, 0.f);
      rs0 = rsqrtf(v0 + 1e-5f);
      rs1 = rsqrtf(v1 + 1e-5f);
      bar_sync(1 + w, 128);
      cluster_wait();
      xoff += (epoch_c & 1u) * kXbufPar;
      asm volatile("" : "+r"(xoff), "+r"(stash));
      PROF(w, 0);
      release(6); release(7);
      if (elect) mbar_arrive(BAR(B_XDONE));
    }

    auto gu_chunk = [&](float (&acc)[32], int f, int slot, int xslot, int hb) INL {
      const float c0 = rs0 * -1.4426950408889634f, c1 = rs1 * -1.4426950408889634f;
      const float q0 = rs0 * rs0, q1 = rs1 * rs1;
      uint32_t h[4];
#pragma unroll
      for (int i = 0; i < 4; i++) {
        const float ga = acc[f * 8 + 2 * i], gb = acc[f * 8 + 2 * i + 1];
        const float ua = acc[16 + f * 8 + 2 * i], ub = acc[16 + f * 8 + 2 * i + 1];
        const float c = (i & 1) ? c1 : c0, q = (i & 1) ? q1 : q0;
        const float da = 1.f + ex2f(fminf(ga * c, 60.f)), db = 1.f + ex2f(fminf(gb * c, 60.f));
        const float rq = rcpf(da * db) * q;
        h[i] = ~pack_bf16(ga * ua * (db * rq), gb * ub * (da * rq));
      }
      const int jj = hb * 2 + f;
      sts_u4(stash + slot * 8192 + jj * 2048, h[0], h[1], h[2], h[3]);
      stg_u4(xptr(xslot, jj), h[0], h[1], h[2], h[3]);
    };
    auto kv_stage = [&](float (&acc)[32], int c, int hb) INL {
      const int srow = wq * 16 + (lane & 7) + ((lane >> 3) & 1) * 8;
      const uint32_t base = area + (3 + c) * 8192 + srow * 128;
#pragma unroll
      for (int jj = 0; jj < 2; jj++) {
        const int a = c * 16 + jj * 8;
        uint32_t r0, r1, r2, r3;
        if (c == 0) {
          r0 = pack_bf16(phi_f(acc[a] * rs0), phi_f(acc[a + 1] * rs0));
          r1 = pack_bf16(phi_f(acc[a + 2] * rs1), phi_f(acc[a + 3] * rs1));
          r2 = pack_bf16(phi_f(acc[a + 4] * rs0), phi_f(acc[a + 5] * rs0));
          r3 = pack_bf16(phi_f(acc[a + 6] * rs1), phi_f(acc[a + 7] * rs1));
        } else {
          r0 = pack_bf16(acc[a] * rs0, acc[a + 1] * rs0);
          r1 = pack_bf16(acc[a + 2] * rs1, acc[a + 3] * rs1);
          r2 = pack_bf16(acc[a + 4] * rs0, acc[a + 5] * rs0);
          r3 = pack_bf16(acc[a + 6] * rs1, acc[a + 7] * rs1);
        }
        stmatrix_x4(base + (((hb * 4 + jj * 2 + (lane >> 4)) ^ (srow & 7)) << 4), r0, r1, r2, r3);
      }
    };
    auto q_head = [&](float (&acc)[32], int c, int slot, uint32_t b0, uint32_t b1, uint32_t b2, uint32_t b3, uint32_t z0, uint32_t z1) INL {
      const int a = c * 8;
      const uint32_t a0 = pack_bf16(phi_f(acc[a] * rs0), phi_f(acc[a + 1] * rs0));
      const uint32_t a1 = pack_bf16(phi_f(acc[a + 2] * rs1), phi_f(acc[a + 3] * rs1));
      const uint32_t a2 = pack_bf16(phi_f(acc[a + 4] * rs0), phi_f(acc[a + 5] * rs0));
      const uint32_t a3 = pack_bf16(phi_f(acc[a + 6] * rs1), phi_f(acc[a + 7] * rs1));
      float n0[4] = {0.f, 0.f, 0.f, 0.f}, n1[4] = {0.f, 0.f, 0.f, 0.f}, dn[4] = {0.f, 0.f, 0.f, 0.f};
      mma_16816(n0, a0, a1, a2, a3, b0, b1);
      mma_16816(n1, a0, a1, a2, a3, b2, b3);
      mma_16816(dn, a0, a1, a2, a3, z0, z1);
      const float i0 = __fdividef(1.f, dn[0] + 1e-6f), i1 = __fdividef(1.f, dn[2] + 1e-6f);
      const uint32_t o0 = ~pack_bf16(n0[0] * i0, n0[1] * i0), o1 = ~pack_bf16(n0[2] * i1, n0[3] * i1);
      const uint32_t o2 = ~pack_bf16(n1[0] * i0, n1[1] * i0), o3 = ~pack_bf16(n1[2] * i1, n1[3] * i1);
      sts_u4(stash + slot * 8192 + c * 2048, o0, o1, o2, o3);
      stg_u4(xptr(slot, c), o0, o1, o2, o3);
    };
    const uint32_t kvb = area + 5 * 8192;
    const uint32_t kvfrag = kvb + ((lane & 7) + ((lane >> 3) & 1) * 8) * 32 + (lane >> 4) * 16;
    auto signal = [&](int e) INL {
      __syncwarp();
      if (lane == 0) mbar_arrive(BAR(B_EV + w * 2 + e));
    };

    float accB[32];
#pragma unroll 1
    for (int t = 0; t < 5; t++) {
      float accA[32];
      const uint32_t ph = t & 1;
      const int kindP = t == 0 ? K_NONE : ((odd && t <= 2) ? K_KV : K_GU);
      const int kindC = odd ? (t < 2 ? K_KV : K_GU) : (t < 4 ? K_GU : K_Q);
      const int slotP = odd ? t - 3 : t - 1, xslotP = odd ? t + 3 : t - 1;
      const int slotC = odd ? t - 2 : t, xslotC = odd ? t + 4 : t;
      static_for<8>([&](auto kc) INL {
        constexpr int k = decltype(kc)::value;
        mbar_wait(BAR(B_FULL + k), ph);
        wgmma_fence();
        static_for<8>([&](auto kkc) INL {
          constexpr int kk = decltype(kkc)::value;
          constexpr int i = ((k & 3) * 8 + kk) * 4;
          constexpr uint32_t lo = desc_lo(stage_off(k) + kk * 1024, 8192);
          if constexpr (k < 4) wgmma_n64_rs<((k & 3) | kk) != 0, lo, kHi64>(accA, A[i], A[i + 1], A[i + 2], A[i + 3], dbase);
          else wgmma_n64_rs<((k & 3) | kk) != 0, lo, kHi64>(accB, A[i], A[i + 1], A[i + 2], A[i + 3], dbase);
        });
        wgmma_commit();
        if (k > 0) {
          wgmma_wait<1>();
          release(k - 1);
        }
        if constexpr (k < 4) {
          if (kindP == K_GU) {
            if (k == 1 || k == 2) gu_chunk(accB, k - 1, slotP, xslotP, 1);
          } else if (kindP == K_KV) {
            if (k == 1 || k == 2) kv_stage(accB, k - 1, 1);
            if (k == 3) {
              float kvacc[36];
              const int par = xoff >= kXbufPar;
              fence_proxy_async();
              bar_sync(1 + w, 128);
              wgmma_fence();
              static_for<4>([&](auto kkc) INL {
                constexpr int kk = decltype(kkc)::value;
                wgmma_n72_ss_tt<kk != 0, desc_lo(3 * 8192 + kk * 2048, 0), desc_lo(4 * 8192 + kk * 2048, 8192 - kk * 2048)>(kvacc, dbase + w * 4096);
              });
              wgmma_commit();
              wgmma_wait<0>();
              float c[8];
#pragma unroll
              for (int i = 0; i < 8; i++)
                c[i] = wq == 0 ? kvacc[i] : (wq == 1 ? kvacc[8 + i] : (wq == 2 ? kvacc[16 + i] : kvacc[24 + i]));
              const int head = (2 * p + t - 1) * 4 + wq;
              float* kvp = &g_kv[par][head][0][0];
              red_add_v2(kvp + g * 16 + 2 * tq, c[0], c[1]);
              red_add_v2(kvp + (g + 8) * 16 + 2 * tq, c[2], c[3]);
              red_add_v2(kvp + g * 16 + 8 + 2 * tq, c[4], c[5]);
              red_add_v2(kvp + (g + 8) * 16 + 8 + 2 * tq, c[6], c[7]);
              if (tq == 0) {
                red_add(&g_z[par][head][g], kvacc[32]);
                red_add(&g_z[par][head][g + 8], kvacc[34]);
              }
              signal(t - 1);
            }
          }
        } else {
          constexpr int c = k - 4;
          if (kindC == K_GU) {
            if (c < 2) gu_chunk(accA, c, slotC, xslotC, 0);
          } else if (kindC == K_KV) {
            if (c == 0 && kindP == K_NONE) sts_u4(stash + 5 * 8192, 0x3F803F80u, 0x3F803F80u, 0x3F803F80u, 0x3F803F80u);
            if (c < 2) kv_stage(accA, c, 0);
          } else {
            if (c == 0) mbar_wait(BAR(B_KVREADY), 0);
            uint32_t b0, b1, b2, b3;
            ldmatrix_x4_trans(kvfrag + c * 512, b0, b1, b2, b3);
            const uint32_t z0 = lds_u32(kvb + 4096 + c * 32 + tq * 4), z1 = lds_u32(kvb + 4096 + c * 32 + 16 + tq * 4);
            q_head(accA, c, 4, b0, b1, b2, b3, z0, z1);
          }
        }
      });
      wgmma_wait<0>();
      release(7);
      PROF(w, 1 + 2 * t);
    }
    if (odd) {
      gu_chunk(accB, 0, 2, 8, 1);
      gu_chunk(accB, 1, 2, 8, 1);
    } else {
      uint32_t Bf[4][6];
#pragma unroll
      for (int c = 0; c < 4; c++) {
        ldmatrix_x4_trans(kvfrag + (4 + c) * 512, Bf[c][0], Bf[c][1], Bf[c][2], Bf[c][3]);
        Bf[c][4] = lds_u32(kvb + 4096 + (4 + c) * 32 + tq * 4);
        Bf[c][5] = lds_u32(kvb + 4096 + (4 + c) * 32 + 16 + tq * 4);
      }
      bar_sync(1 + w, 128);
#pragma unroll
      for (int c = 0; c < 4; c++) q_head(accB, c, 5, Bf[c][0], Bf[c][1], Bf[c][2], Bf[c][3], Bf[c][4], Bf[c][5]);
    }
    PROF(w, 10);

    const int n_own = odd ? 3 : 6;
    auto load_a = [&](int kb) INL {
      if (kb < n_own) {
#pragma unroll
        for (int jj = 0; jj < 4; jj++) {
          const int i = (kb * 4 + jj) * 4;
          lds_u4(stash + kb * 8192 + jj * 2048, A[i], A[i + 1], A[i + 2], A[i + 3]);
        }
      } else {
        const int xs = odd ? kb - 3 : kb;
#pragma unroll
        for (int jj = 0; jj < 4; jj++) {
          const int i = (kb * 4 + jj) * 4;
          ldg_poll_u4(xptr(xs, jj), A[i], A[i + 1], A[i + 2], A[i + 3]);
        }
      }
    };
    auto fix_a = [&](int kb) INL {
      if (kb >= n_own) {
        const int xs = odd ? kb - 3 : kb;
        recv_group<4>(xptr(xs, 0), &A[kb * 16]);
      } else {
#pragma unroll
        for (int i = 0; i < 16; i++) A[kb * 16 + i] = ~A[kb * 16 + i];
      }
    };
#pragma unroll
    for (int kb = 0; kb < 7; kb++) load_a(kb);
    PROF(w, 11);

    const int orow = m * 128 + w * 64 + wq * 16 + g;
    const int ocol = odd * 256 + p * 64 + 2 * tq;
    float acc2[2][32];
    uint32_t poff = (uint32_t)((m * 2 + odd) * 24 + w) * 8192u + (uint32_t)t128 * 16u + (xoff >= kXbufPar ? kPbufPar : 0u);
    asm volatile("" : "+r"(poff));
    auto pptr = [&](int dest, int sl) INL { return (uint4*)((char*)g_pbuf + (poff + (uint32_t)(dest * 3 + sl) * 16384u)); };
    uint32_t P[3][16];
    uint32_t xr[16];
    auto send = [&](float (&acc)[32], int bi) INL {
      uint4* dst = pptr((p + 1 + bi) & 3, bi);
#pragma unroll
      for (int q = 0; q < 4; q++)
        stg_u4(dst + q * 128, ~pack_bf16(acc[q * 8], acc[q * 8 + 1]), ~pack_bf16(acc[q * 8 + 2], acc[q * 8 + 3]),
               ~pack_bf16(acc[q * 8 + 4], acc[q * 8 + 5]), ~pack_bf16(acc[q * 8 + 6], acc[q * 8 + 7]));
      PROF(w, 12 + 2 * bi);
    };
    auto fetch = [&](int sl) INL {
#pragma unroll
      for (int q = 0; q < 4; q++) ldg_poll_u4(pptr(p, sl) + q * 128, P[sl][q * 4], P[sl][q * 4 + 1], P[sl][q * 4 + 2], P[sl][q * 4 + 3]);
    };
    static_for<36>([&](auto ic) INL {
      constexpr int i = decltype(ic)::value, bi = p2_bi(i), kb = p2_kb(i), j = i >> 1, st = j & 7;
      if (i == 9) { load_a(7); load_a(8); }
      if (i == 14) PROF(w, 2);
      if (bi == 0) fix_a(kb);
      if (i == 15) PROF(w, 4);
      if (i == 7) PROF(w, 6);
      if ((i & 1) == 0) mbar_wait(BAR(B_FULL + st), (5 + (j >> 3)) & 1);
      wgmma_fence();
      static_for<4>([&](auto kkc) INL {
        constexpr int kk = decltype(kkc)::value, a = (kb * 4 + kk) * 4;
        wgmma_n64_rs<(kb | kk) != 0, desc_lo(stage_off(st) + (i & 1) * 8192 + kk * 2048, 0), kHi128>(acc2[bi & 1], A[a], A[a + 1], A[a + 2], A[a + 3], dbase);
      });
      wgmma_commit();
      if (i > 0) {
        wgmma_wait<1>();
        if ((i & 1) == 0 && j - 1 <= 9) release((j - 1) & 7);
      }
      if constexpr (i == 16) send(acc2[0], 0);
      if constexpr (i == 18) send(acc2[1], 1);
      if constexpr (i == 27) send(acc2[0], 2);
      if constexpr (i == 29) fetch(0);
      if constexpr (i == 31) fetch(1);
      if constexpr (i == 32) {
#pragma unroll
        for (int q = 0; q < 8; q++) {
          xr[2 * q] = __ldg((const uint32_t*)(x + (size_t)orow * kD + ocol + q * 8));
          xr[2 * q + 1] = __ldg((const uint32_t*)(x + (size_t)(orow + 8) * kD + ocol + q * 8));
        }
      }
      if constexpr (i == 34) fetch(2);
    });
#pragma unroll
    for (int sl = 0; sl < 3; sl++) { PROF(w, 13 + 2 * sl); recv_group<4>(pptr(p, sl), &P[sl][0]); }
    wgmma_wait<0>();
    PROF(w, 18);
#pragma unroll
    for (int q = 0; q < 8; q++) {
      float rr[4];
      rr[0] = acc2[1][q * 4 + 0] + __uint_as_float(xr[2 * q] << 16);
      rr[1] = acc2[1][q * 4 + 1] + __uint_as_float(xr[2 * q] & 0xffff0000u);
      rr[2] = acc2[1][q * 4 + 2] + __uint_as_float(xr[2 * q + 1] << 16);
      rr[3] = acc2[1][q * 4 + 3] + __uint_as_float(xr[2 * q + 1] & 0xffff0000u);
#pragma unroll
      for (int sl = 0; sl < 3; sl++) {
        rr[0] += __uint_as_float(P[sl][2 * q] << 16);
        rr[1] += __uint_as_float(P[sl][2 * q] & 0xffff0000u);
        rr[2] += __uint_as_float(P[sl][2 * q + 1] << 16);
        rr[3] += __uint_as_float(P[sl][2 * q + 1] & 0xffff0000u);
      }
      *(uint32_t*)(out + (size_t)orow * kD + ocol + q * 8) = pack_bf16(rr[0], rr[1]);
      *(uint32_t*)(out + (size_t)(orow + 8) * kD + ocol + q * 8) = pack_bf16(rr[2], rr[3]);
    }
    PROF(w, 19);
    if (tid == 0) {
      const uint32_t old = atomicAdd(&g_done, 1u);
      if ((old & 127u) == 127u) st_relaxed(&g_epoch, ld_relaxed(&g_epoch) + 1u);
    }
  }
#undef BAR
}

typedef CUresult (*EncodeFn)(CUtensorMap*, CUtensorMapDataType, cuuint32_t, void*, const cuuint64_t*, const cuuint64_t*,
                             const cuuint32_t*, const cuuint32_t*, CUtensorMapInterleave, CUtensorMapSwizzle,
                             CUtensorMapL2promotion, CUtensorMapFloatOOBfill);

void make_map(EncodeFn enc, CUtensorMap* tm, const void* ptr, int rows, int cols, bool narrow) {
  cuuint64_t gd[2] = {(cuuint64_t)cols, (cuuint64_t)rows};
  cuuint64_t gs[1] = {(cuuint64_t)cols * 2};
  cuuint32_t bd[2] = {narrow ? 32u : 64u, narrow ? 128u : 64u};
  cuuint32_t es[2] = {1, 1};
  enc(tm, CU_TENSOR_MAP_DATA_TYPE_BFLOAT16, 2, const_cast<void*>(ptr), gd, gs, bd, es, CU_TENSOR_MAP_INTERLEAVE_NONE,
      narrow ? CU_TENSOR_MAP_SWIZZLE_64B : CU_TENSOR_MAP_SWIZZLE_128B, CU_TENSOR_MAP_L2_PROMOTION_L2_256B, CU_TENSOR_MAP_FLOAT_OOB_FILL_NONE);
}

}

extern "C" void kernel_launch(void* const* d_in, const int* in_sizes, int n_in, void* d_out, int out_size) {
  static EncodeFn enc = nullptr;
  if (!enc) {
    void* fn = nullptr;
    cudaDriverEntryPointQueryResult qr;
    cudaGetDriverEntryPoint("cuTensorMapEncodeTiled", &fn, cudaEnableDefault, &qr);
    enc = (EncodeFn)fn;
    cudaFuncSetAttribute(fused_kernel, cudaFuncAttributeMaxDynamicSharedMemorySize, kSmemBytes);
  }
  CUtensorMap tm_x, tm_wqkv, tm_w1, tm_w3, tm_w2, tm_wo;
  make_map(enc, &tm_x, d_in[0], kS, kD, false);
  make_map(enc, &tm_wqkv, d_in[1], kD, 3 * kD, true);
  make_map(enc, &tm_wo, d_in[2], kD, kD, false);
  make_map(enc, &tm_w1, d_in[4], kD, kF, true);
  make_map(enc, &tm_w3, d_in[5], kD, kF, true);
  make_map(enc, &tm_w2, d_in[6], kF, kD, false);
  fused_kernel<<<128, 384, kSmemBytes>>>(tm_x, tm_wqkv, tm_w1, tm_w3, tm_w2, tm_wo, (const __nv_bfloat16*)d_in[0],
                                         (__nv_bfloat16*)d_out);
}
```

```cpp
#include <cuda_runtime.h>
#include <cuda_bf16.h>
#include <cuda.h>
#include <stdint.h>

namespace {

constexpr int kS = 2048, kD = 512, kF = 1792;
constexpr uint32_t kSpinLimit = 1u << 22;

__device__ uint4    g_xbuf[16][4][9][2][4][128];
__device__ uint4    g_pbuf[16][2][4][3][2][4][128];
__device__ float    g_kv[2][32][16][16];
__device__ float    g_z[2][32][16];
__device__ uint32_t g_kvcnt[4][32];
__device__ uint32_t g_epoch;
__device__ uint32_t g_done;
#define PROF(wg, i) do {} while (0)
#define TWAIT(acc, stmt) do { stmt; } while (0)

__device__ __forceinline__ uint32_t smem_u32(const void* p) { return (uint32_t)__cvta_generic_to_shared(p); }
__device__ __forceinline__ void mbar_init(uint32_t bar, uint32_t cnt) {
  asm volatile("mbarrier.init.shared::cta.b64 [%0], %1;" ::"r"(bar), "r"(cnt) : "memory");
}
__device__ __forceinline__ void mbar_expect_tx(uint32_t bar, uint32_t bytes) {
  asm volatile("mbarrier.arrive.expect_tx.shared::cta.b64 _, [%0], %1;" ::"r"(bar), "r"(bytes) : "memory");
}
__device__ __forceinline__ void mbar_arrive(uint32_t bar) {
  asm volatile("mbarrier.arrive.shared::cta.b64 _, [%0];" ::"r"(bar) : "memory");
}
__device__ __forceinline__ void mbar_wait(uint32_t bar, uint32_t parity) {
  asm volatile(
      "{\n.reg .pred p;\n"
      "LAB_WAIT:\n"
      "mbarrier.try_wait.parity.shared::cta.b64 p, [%0], %1;\n"
      "@p bra DONE;\n"
      "bra LAB_WAIT;\n"
      "DONE:\n}" ::"r"(bar), "r"(parity) : "memory");
}
__device__ __forceinline__ void tma_load_2d(uint32_t dst, const CUtensorMap* tm, uint32_t bar, int c0, int c1) {
  asm volatile(
      "cp.async.bulk.tensor.2d.shared::cluster.global.mbarrier::complete_tx::bytes [%0], [%1, {%3, %4}], [%2];" ::"r"(dst),
      "l"(tm), "r"(bar), "r"(c0), "r"(c1)
      : "memory");
}
__device__ __forceinline__ void tma_load_2d_mc(uint32_t dst, const CUtensorMap* tm, uint32_t bar, int c0, int c1) {
  asm volatile(
      "cp.async.bulk.tensor.2d.shared::cluster.global.mbarrier::complete_tx::bytes.multicast::cluster [%0], [%1, {%3, %4}], [%2], %5;" ::"r"(dst),
      "l"(tm), "r"(bar), "r"(c0), "r"(c1), "h"((uint16_t)3)
      : "memory");
}
__device__ __forceinline__ void mbar_arrive_cluster(uint32_t bar, uint32_t cta) {
  asm volatile("{\n.reg .b32 ra;\nmapa.shared::cluster.u32 ra, %0, %1;\nmbarrier.arrive.shared::cluster.b64 _, [ra];\n}" ::"r"(bar), "r"(cta) : "memory");
}
__device__ __forceinline__ void prefetch_tmap(const CUtensorMap* tm) {
  asm volatile("prefetch.tensormap [%0];" ::"l"(tm) : "memory");
}
__device__ __forceinline__ void wgmma_fence() { asm volatile("wgmma.fence.sync.aligned;" ::: "memory"); }
__device__ __forceinline__ void wgmma_commit() { asm volatile("wgmma.commit_group.sync.aligned;" ::: "memory"); }
template <int N>
__device__ __forceinline__ void wgmma_wait() { asm volatile("wgmma.wait_group.sync.aligned %0;" ::"n"(N) : "memory"); }
__device__ __forceinline__ void bar_sync(int id, int n) { asm volatile("bar.sync %0, %1;" ::"r"(id), "r"(n) : "memory"); }
__device__ __forceinline__ void bar_arrive(int id, int n) { asm volatile("bar.arrive %0, %1;" ::"r"(id), "r"(n) : "memory"); }
__device__ __forceinline__ void fence_proxy_async() { asm volatile("fence.proxy.async.shared::cta;" ::: "memory"); }

__device__ __forceinline__ uint32_t ld_acquire(const uint32_t* p) {
  uint32_t v;
  asm volatile("ld.acquire.gpu.global.u32 %0, [%1];" : "=r"(v) : "l"(p) : "memory");
  return v;
}
__device__ __forceinline__ uint32_t ld_relaxed(const uint32_t* p) {
  uint32_t v;
  asm volatile("ld.relaxed.gpu.global.u32 %0, [%1];" : "=r"(v) : "l"(p));
  return v;
}
__device__ __forceinline__ void cluster_wait() { asm volatile("barrier.cluster.wait.aligned;" ::: "memory"); }
__device__ __forceinline__ void st_relaxed(uint32_t* p, uint32_t v) {
  asm volatile("st.relaxed.gpu.global.u32 [%0], %1;" ::"l"(p), "r"(v) : "memory");
}
__device__ __forceinline__ void wait_flag_eq(const uint32_t* p, uint32_t val) {
  uint32_t it = 0;
  while (ld_acquire(p) != val) {
    if (++it > kSpinLimit) break;
  }
}
__device__ __forceinline__ void wait_count_ge(const uint32_t* p, uint32_t val) {
  uint32_t it = 0;
  while ((int32_t)(ld_acquire(p) - val) < 0) {
    __nanosleep(64);
    if (++it > kSpinLimit) break;
  }
}
__device__ __forceinline__ void ldg_poll_u4(const void* p, uint32_t& a, uint32_t& b, uint32_t& c, uint32_t& d) {
  asm volatile("ld.relaxed.gpu.global.v4.u32 {%0,%1,%2,%3}, [%4];" : "=r"(a), "=r"(b), "=r"(c), "=r"(d) : "l"(p) : "memory");
}
template <int N>
__device__ __forceinline__ void recv_group(const uint4* p, uint32_t* r, uint32_t tag) {
  uint32_t it = 0;
  while (true) {
    uint32_t bad = 0u;
#pragma unroll
    for (int i = 0; i < 4 * N; i++) bad |= r[i] ^ tag;
    if (!__any_sync(0xffffffffu, (bad & 1u) != 0u) || ++it > kSpinLimit) break;
#pragma unroll
    for (int q = 0; q < N; q++) ldg_poll_u4(p + q * 128, r[q * 4], r[q * 4 + 1], r[q * 4 + 2], r[q * 4 + 3]);
  }
}
__device__ __forceinline__ uint32_t tagged(uint32_t v, uint32_t tag) { return (v & ~1u) | tag; }
__device__ __forceinline__ float4 ldg_cg_f4(const void* p) {
  float4 v;
  asm volatile("ld.global.cg.v4.f32 {%0,%1,%2,%3}, [%4];" : "=f"(v.x), "=f"(v.y), "=f"(v.z), "=f"(v.w) : "l"(p) : "memory");
  return v;
}
__device__ __forceinline__ void stg_u4(void* p, uint32_t a, uint32_t b, uint32_t c, uint32_t d) {
  asm volatile("st.global.v4.u32 [%0], {%1,%2,%3,%4};" ::"l"(p), "r"(a), "r"(b), "r"(c), "r"(d) : "memory");
}
__device__ __forceinline__ void stg_f4(void* p, float a, float b, float c, float d) {
  asm volatile("st.global.v4.f32 [%0], {%1,%2,%3,%4};" ::"l"(p), "f"(a), "f"(b), "f"(c), "f"(d) : "memory");
}
__device__ __forceinline__ void sts_u4(uint32_t addr, uint32_t a, uint32_t b, uint32_t c, uint32_t d) {
  asm volatile("st.shared.v4.u32 [%0], {%1,%2,%3,%4};" ::"r"(addr), "r"(a), "r"(b), "r"(c), "r"(d) : "memory");
}
__device__ __forceinline__ void lds_u4(uint32_t addr, uint32_t& a, uint32_t& b, uint32_t& c, uint32_t& d) {
  asm volatile("ld.shared.v4.u32 {%0,%1,%2,%3}, [%4];" : "=r"(a), "=r"(b), "=r"(c), "=r"(d) : "r"(addr) : "memory");
}
__device__ __forceinline__ uint32_t lds_u32(uint32_t addr) {
  uint32_t v;
  asm volatile("ld.shared.u32 %0, [%1];" : "=r"(v) : "r"(addr) : "memory");
  return v;
}
__device__ __forceinline__ void ldmatrix_x4(uint32_t addr, uint32_t& a, uint32_t& b, uint32_t& c, uint32_t& d) {
  asm volatile("ldmatrix.sync.aligned.m8n8.x4.shared.b16 {%0,%1,%2,%3}, [%4];" : "=r"(a), "=r"(b), "=r"(c), "=r"(d) : "r"(addr) : "memory");
}
__device__ __forceinline__ void ldmatrix_x4_trans(uint32_t addr, uint32_t& a, uint32_t& b, uint32_t& c, uint32_t& d) {
  asm volatile("ldmatrix.sync.aligned.m8n8.x4.trans.shared.b16 {%0,%1,%2,%3}, [%4];" : "=r"(a), "=r"(b), "=r"(c), "=r"(d) : "r"(addr) : "memory");
}
__device__ __forceinline__ void stmatrix_x4(uint32_t addr, uint32_t a, uint32_t b, uint32_t c, uint32_t d) {
  asm volatile("stmatrix.sync.aligned.m8n8.x4.shared.b16 [%0], {%1,%2,%3,%4};" ::"r"(addr), "r"(a), "r"(b), "r"(c), "r"(d) : "memory");
}
__device__ __forceinline__ void mma_16816(float (&c)[4], uint32_t a0, uint32_t a1, uint32_t a2, uint32_t a3, uint32_t b0, uint32_t b1) {
  asm volatile(
      "mma.sync.aligned.m16n8k16.row.col.f32.bf16.bf16.f32 {%0,%1,%2,%3}, {%4,%5,%6,%7}, {%8,%9}, {%0,%1,%2,%3};"
      : "+f"(c[0]), "+f"(c[1]), "+f"(c[2]), "+f"(c[3])
      : "r"(a0), "r"(a1), "r"(a2), "r"(a3), "r"(b0), "r"(b1));
}
__device__ __forceinline__ uint32_t pack_bf16(float lo, float hi) {
  uint32_t r;
  asm("cvt.rn.bf16x2.f32 %0, %1, %2;" : "=r"(r) : "f"(hi), "f"(lo));
  return r;
}
__device__ __forceinline__ uint32_t hsub2_bf16(uint32_t a, uint32_t b) {
  uint32_t r;
  asm("sub.rn.bf16x2 %0, %1, %2;" : "=r"(r) : "r"(a), "r"(b));
  return r;
}
__device__ __forceinline__ float ex2f(float x) {
  float r;
  asm("ex2.approx.ftz.f32 %0, %1;" : "=f"(r) : "f"(x));
  return r;
}
__device__ __forceinline__ float rcpf(float x) {
  float r;
  asm("rcp.approx.ftz.f32 %0, %1;" : "=f"(r) : "f"(x));
  return r;
}
__device__ __forceinline__ void red_add_v2(float* p, float a, float b) {
  asm volatile("red.relaxed.gpu.global.add.v2.f32 [%0], {%1,%2};" ::"l"(p), "f"(a), "f"(b) : "memory");
}
__device__ __forceinline__ void red_add(float* p, float a) {
  asm volatile("red.relaxed.gpu.global.add.f32 [%0], %1;" ::"l"(p), "f"(a) : "memory");
}
__device__ __forceinline__ float phi_f(float t) {
  float e = ex2f(t * 1.4426950408889634f);
  return (t > 0.f ? t + 1.f : e) + 1e-6f;
}

#define R8(a, o) "+f"(a[o + 0]), "+f"(a[o + 1]), "+f"(a[o + 2]), "+f"(a[o + 3]), "+f"(a[o + 4]), "+f"(a[o + 5]), "+f"(a[o + 6]), "+f"(a[o + 7])

#define W8(a, o) "=f"(a[o + 0]), "=f"(a[o + 1]), "=f"(a[o + 2]), "=f"(a[o + 3]), "=f"(a[o + 4]), "=f"(a[o + 5]), "=f"(a[o + 6]), "=f"(a[o + 7])
#define D32 "{%0,%1,%2,%3,%4,%5,%6,%7,%8,%9,%10,%11,%12,%13,%14,%15,%16,%17,%18,%19,%20,%21,%22,%23,%24,%25,%26,%27,%28,%29,%30,%31}"
#define D36 "{%0,%1,%2,%3,%4,%5,%6,%7,%8,%9,%10,%11,%12,%13,%14,%15,%16,%17,%18,%19,%20,%21,%22,%23,%24,%25,%26,%27,%28,%29,%30,%31,%32,%33,%34,%35}"

constexpr uint32_t kHi128 = (1024u >> 4) | (1u << 30);
constexpr uint32_t kHi64 = (512u >> 4) | (2u << 30);
__host__ __device__ constexpr uint32_t desc_lo(uint32_t off, uint32_t lbo) { return (off >> 4) | ((lbo >> 4) << 16); }

template <bool ACC, uint32_t LO, uint32_t HI>
__device__ __forceinline__ void wgmma_n64_rs(float (&d)[32], uint32_t a0, uint32_t a1, uint32_t a2, uint32_t a3, uint32_t base) {
  if (ACC) {
    asm volatile(
        "{\n.reg .pred p;\n.reg .b32 lo;\n.reg .b64 dd;\nsetp.eq.b32 p, 0, 0;\nadd.u32 lo, %36, %37;\nmov.b64 dd, {lo, %38};\n"
        "wgmma.mma_async.sync.aligned.m64n64k16.f32.bf16.bf16 " D32 ", {%32,%33,%34,%35}, dd, p, 1, 1, 1;\n}"
        : R8(d, 0), R8(d, 8), R8(d, 16), R8(d, 24)
        : "r"(a0), "r"(a1), "r"(a2), "r"(a3), "r"(base), "n"(LO), "n"(HI));
  } else {
    asm volatile(
        "{\n.reg .pred p;\n.reg .b32 lo;\n.reg .b64 dd;\nsetp.ne.b32 p, 0, 0;\nadd.u32 lo, %36, %37;\nmov.b64 dd, {lo, %38};\n"
        "wgmma.mma_async.sync.aligned.m64n64k16.f32.bf16.bf16 " D32 ", {%32,%33,%34,%35}, dd, p, 1, 1, 1;\n}"
        : W8(d, 0), W8(d, 8), W8(d, 16), W8(d, 24)
        : "r"(a0), "r"(a1), "r"(a2), "r"(a3), "r"(base), "n"(LO), "n"(HI));
  }
}
template <bool ACC, uint32_t LOA, uint32_t LOB>
__device__ __forceinline__ void wgmma_n72_ss_tt(float (&d)[36], uint32_t base) {
  if (ACC) {
    asm volatile(
        "{\n.reg .pred p;\n.reg .b32 lo;\n.reg .b64 da, db;\nsetp.eq.b32 p, 0, 0;\n"
        "add.u32 lo, %36, %37;\nmov.b64 da, {lo, %39};\nadd.u32 lo, %36, %38;\nmov.b64 db, {lo, %39};\n"
        "wgmma.mma_async.sync.aligned.m64n72k16.f32.bf16.bf16 " D36 ", da, db, p, 1, 1, 1, 1;\n}"
        : R8(d, 0), R8(d, 8), R8(d, 16), R8(d, 24), "+f"(d[32]), "+f"(d[33]), "+f"(d[34]), "+f"(d[35])
        : "r"(base), "n"(LOA), "n"(LOB), "n"(kHi128));
  } else {
    asm volatile(
        "{\n.reg .pred p;\n.reg .b32 lo;\n.reg .b64 da, db;\nsetp.ne.b32 p, 0, 0;\n"
        "add.u32 lo, %36, %37;\nmov.b64 da, {lo, %39};\nadd.u32 lo, %36, %38;\nmov.b64 db, {lo, %39};\n"
        "wgmma.mma_async.sync.aligned.m64n72k16.f32.bf16.bf16 " D36 ", da, db, p, 1, 1, 1, 1;\n}"
        : W8(d, 0), W8(d, 8), W8(d, 16), W8(d, 24), "=f"(d[32]), "=f"(d[33]), "=f"(d[34]), "=f"(d[35])
        : "r"(base), "n"(LOA), "n"(LOB), "n"(kHi128));
  }
}

#define INL __attribute__((always_inline))
template <int V> struct IC { static constexpr int value = V; };
template <int N, int I = 0, typename F>
__device__ __forceinline__ void static_for(F&& f) {
  if constexpr (I < N) { f(IC<I>{}); static_for<N, I + 1>(f); }
}

__host__ __device__ constexpr uint32_t stage_off(int st) {
  return st < 6 ? 131072u + (uint32_t)st * 16384u : (uint32_t)(st - 6) * 65536u + 49152u;
}

constexpr int B_FULL = 0, B_EMPTY = 8, B_XFULL = 16, B_XDONE = 32, B_KVREADY = 33, B_EV = 34, B_COUNT = 38;
constexpr uint32_t kBarOff = 229376;
constexpr int kSmemBytes = 229376 + 1024;

__host__ __device__ constexpr int p2_bi(int i) { return i < 7 ? 0 : i < 14 ? 1 : i < 16 ? 0 : i < 18 ? 1 : i / 9; }
__host__ __device__ constexpr int p2_kb(int i) { return i < 7 ? i : i < 14 ? i - 7 : i < 16 ? i - 7 : i < 18 ? i - 9 : i % 9; }

enum { K_NONE = 0, K_GU = 1, K_KV = 2, K_Q = 3 };

__global__ void __cluster_dims__(2, 1, 1) __launch_bounds__(384, 1)
fused_kernel(const __grid_constant__ CUtensorMap tm_x, const __grid_constant__ CUtensorMap tm_wqkv,
             const __grid_constant__ CUtensorMap tm_w1, const __grid_constant__ CUtensorMap tm_w3,
             const __grid_constant__ CUtensorMap tm_w2, const __grid_constant__ CUtensorMap tm_wo,
             const __nv_bfloat16* __restrict__ x, __nv_bfloat16* __restrict__ out) {
  extern __shared__ __align__(1024) uint8_t smem_raw[];
  const uint32_t sbase = smem_u32(smem_raw);
  const uint32_t bars = sbase + kBarOff;
  const int tid = threadIdx.x, lane = tid & 31;
  const int warp = __shfl_sync(0xffffffffu, tid >> 5, 0);
  const int cr = blockIdx.x & 1;
  const int r = (blockIdx.x >> 1) & 7, m = ((blockIdx.x >> 4) << 1) | cr, p = r >> 1, odd = r & 1;
#define BAR(i) (bars + 8u * (uint32_t)(i))
  if (tid == 256) {
    if (sbase & 1023u) __trap();
#pragma unroll
    for (int i = 0; i < 16; i++) mbar_init(BAR(B_XFULL + i), 1);
    fence_proxy_async();
#pragma unroll
    for (int b = 0; b < 16; b++) {
      mbar_expect_tx(BAR(B_XFULL + b), 8192);
      tma_load_2d(sbase + (b >> 3) * 65536 + (b & 7) * 8192, &tm_x, BAR(B_XFULL + b), (b & 7) * 64, m * 128 + (b >> 3) * 64);
    }
#pragma unroll
    for (int i = 0; i < 8; i++) { mbar_init(BAR(B_FULL + i), 1); mbar_init(BAR(B_EMPTY + i), 4); }
#pragma unroll
    for (int i = 0; i < 4; i++) mbar_init(BAR(B_EV + i), 4);
    mbar_init(BAR(B_XDONE), 2);
    mbar_init(BAR(B_KVREADY), 1);
    asm volatile("fence.mbarrier_init.release.cluster;" ::: "memory");
    fence_proxy_async();
  } else if (tid == 288) {
    prefetch_tmap(odd ? &tm_wqkv : (cr ? &tm_w3 : &tm_w1));
  }
  __syncwarp();
  asm volatile("barrier.cluster.arrive.relaxed.aligned;" ::: "memory");
  PROF((tid >> 7), 21);
  __syncthreads();

  if (warp >= 8) {
    asm volatile("setmaxnreg.dec.sync.aligned.u32 24;");
    PROF(2, 3);
    cluster_wait();
    PROF(2, 2);
    const uint32_t epoch = warp == 8 ? 0u : ld_relaxed(&g_epoch);
    const uint32_t tag = epoch + 1u;
    const int par = epoch & 1;
    if (warp == 8) {
      if (lane == 0) {
        for (int j = 0; j < 10; j++) {
          const CUtensorMap* tm;
          int col;
          if (!odd) {
            if (j < 8) { tm = cr ? &tm_w3 : &tm_w1; col = 7 * p * 64 + j * 32; }
            else { tm = &tm_wqkv; col = 128 * p + (j - 8) * 64 + cr * 32; }
          } else {
            if (j < 4) { tm = &tm_wqkv; col = 512 + cr * 512 + 128 * p + j * 32; }
            else { tm = cr ? &tm_w3 : &tm_w1; col = (7 * p + 4) * 64 + (j - 4) * 32; }
          }
          const int t = j >> 1;
          for (int kq = 0; kq < 4; kq++) {
            const int k = (j & 1) * 4 + kq;
            mbar_wait(BAR(B_EMPTY + k), k < 6 ? ((t & 1) ^ 1) : (t & 1));
            mbar_expect_tx(BAR(B_FULL + k), 16384);
            tma_load_2d_mc(sbase + stage_off(k) + cr * 8192, tm, BAR(B_FULL + k), col, kq * 128);
          }
        }
        for (int j = 0; j < 18; j++) {
          const int st = j & 7, n = 5 + (j >> 3);
          const int i = 2 * j + cr;
          const int bi = p2_bi(i), kb = p2_kb(i);
          const int col = odd * 256 + ((p + 1 + bi) & 3) * 64;
          const CUtensorMap* tmk;
          int row;
          if (!odd) {
            if (kb < 4) { tmk = &tm_w2; row = (7 * p + kb) * 64; }
            else if (kb < 6) { tmk = &tm_wo; row = (2 * p + kb - 4) * 64; }
            else { tmk = &tm_w2; row = (7 * p + 4 + kb - 6) * 64; }
          } else {
            if (kb < 3) { tmk = &tm_w2; row = (7 * p + 4 + kb) * 64; }
            else if (kb < 7) { tmk = &tm_w2; row = (7 * p + kb - 3) * 64; }
            else { tmk = &tm_wo; row = (2 * p + kb - 7) * 64; }
          }
          mbar_wait(BAR(B_EMPTY + st), st < 6 ? ((n & 1) ^ 1) : (n & 1));
          mbar_expect_tx(BAR(B_FULL + st), 16384);
          tma_load_2d_mc(sbase + stage_off(st) + cr * 8192, tmk, BAR(B_FULL + st), col, row);
        }
      }
    } else if (warp <= 10) {
      if (lane == 0 && odd) {
        const int w = warp - 9;
        for (int e = 0; e < 2; e++) {
          mbar_wait(BAR(B_EV + w * 2 + e), 0);
          __threadfence();
          atomicAdd(&g_kvcnt[p][0], 1u);
        }
      }
    } else {
      if (!odd) {
        {
          const int ce = m * 4 + p;
          float* kvn = &g_kv[par ^ 1][0][0][0];
          for (int i = lane; i < 128; i += 32) kvn[ce * 128 + i] = 0.f;
          if (lane < 8) (&g_z[par ^ 1][0][0])[ce * 8 + lane] = 0.f;
        }
        mbar_wait(BAR(B_XDONE), 0);
        wait_count_ge(&g_kvcnt[p][0], 64u * tag);
        const float* kvp = &g_kv[par][8 * p][0][0];
        const uint32_t dst0 = sbase + 5 * 8192, dst1 = dst0 + 65536;
#pragma unroll 4
        for (int i = 0; i < 16; i++) {
          float4 v = ldg_cg_f4(kvp + (i * 32 + lane) * 4);
          uint32_t lo = pack_bf16(v.x, v.y), hi = pack_bf16(v.z, v.w);
          uint32_t off = (uint32_t)(i * 32 + lane) * 8u;
          asm volatile("st.shared.v2.u32 [%0], {%1,%2};" ::"r"(dst0 + off), "r"(lo), "r"(hi) : "memory");
          asm volatile("st.shared.v2.u32 [%0], {%1,%2};" ::"r"(dst1 + off), "r"(lo), "r"(hi) : "memory");
        }
        {
          float4 v = ldg_cg_f4(&g_z[par][8 * p][0] + lane * 4);
          uint32_t lo = pack_bf16(v.x, v.y), hi = pack_bf16(v.z, v.w);
          uint32_t off = 4096u + (uint32_t)lane * 8u;
          asm volatile("st.shared.v2.u32 [%0], {%1,%2};" ::"r"(dst0 + off), "r"(lo), "r"(hi) : "memory");
          asm volatile("st.shared.v2.u32 [%0], {%1,%2};" ::"r"(dst1 + off), "r"(lo), "r"(hi) : "memory");
        }
        __syncwarp();
        if (lane == 0) mbar_arrive(BAR(B_KVREADY));
      }
    }
  } else {
    asm volatile("setmaxnreg.inc.sync.aligned.u32 240;");
    const int w = warp >> 2, wq = warp & 3, t128 = tid & 127;
    const int g = lane >> 2, tq = lane & 3;
    const uint32_t area = sbase + (uint32_t)w * 65536u;
    const bool elect = (t128 == 0);
    PROF(w, 22);
    const uint32_t dbase = (sbase & 0x3FFFFu) >> 4;
    uint32_t xoff = (uint32_t)((m * 4 + p) * 18 + w) * 8192u + (uint32_t)t128 * 16u;
    uint32_t stash = area + (uint32_t)t128 * 16u;
    const uint32_t epoch_c = ld_relaxed(&g_epoch);
    auto xptr = [&](int slot, int jj) INL { return (uint4*)((char*)g_xbuf + ((xoff & ~1u) + (uint32_t)slot * 16384u + (uint32_t)jj * 2048u)); };
    uint32_t A[144];
    float rs0, rs1;
    auto release = [&](int st) INL {
      if (elect) { mbar_arrive_cluster(BAR(B_EMPTY + st), 0); mbar_arrive_cluster(BAR(B_EMPTY + st), 1); }
    };

    {
      const int row = wq * 16 + (lane & 7) + ((lane >> 3) & 1) * 8;
      const uint32_t rbase = area + row * 128;
      float s0[2][4] = {}, q0[2][4] = {}, q1[2][4] = {};
      const uint32_t ones = 0x3F803F80u;
#pragma unroll
      for (int b = 0; b < 8; b++) {
        mbar_wait(BAR(B_XFULL + w * 8 + b), 0);
        if (b == 0) PROF(w, 23);
        if (b == 7) PROF(w, 24);
#pragma unroll
        for (int kk = 0; kk < 4; kk++) {
          const int i = (b * 4 + kk) * 4;
          ldmatrix_x4(rbase + b * 8192 + (((kk * 2 + (lane >> 4)) ^ (row & 7)) << 4), A[i], A[i + 1], A[i + 2], A[i + 3]);
        }
#pragma unroll
        for (int kk = 0; kk < 4; kk++) {
          const int i = (b * 4 + kk) * 4;
          mma_16816(s0[kk & 1], A[i], A[i + 1], A[i + 2], A[i + 3], ones, ones);
          mma_16816(q0[kk & 1], A[i], A[i + 1], A[i + 2], A[i + 3], A[i], A[i + 2]);
          mma_16816(q1[kk & 1], A[i], A[i + 1], A[i + 2], A[i + 3], A[i + 1], A[i + 3]);
        }
      }
      const float mean0 = (s0[0][0] + s0[1][0]) * (1.f / 512.f), mean1 = (s0[0][2] + s0[1][2]) * (1.f / 512.f);
      const uint32_t m0 = pack_bf16(mean0, mean0), m1 = pack_bf16(mean1, mean1);
#pragma unroll
      for (int i = 0; i < 128; i += 2) {
        A[i] = hsub2_bf16(A[i], m0);
        A[i + 1] = hsub2_bf16(A[i + 1], m1);
      }
      float v0 = (g & 1) ? q0[0][1] + q0[1][1] : q0[0][0] + q0[1][0];
      float v1 = (g & 1) ? q1[0][3] + q1[1][3] : q1[0][2] + q1[1][2];
      const int src = 4 * g + (g >> 1);
      v0 = __shfl_sync(0xffffffffu, v0, src);
      v1 = __shfl_sync(0xffffffffu, v1, src);
      v0 = fmaxf(v0 * (1.f / 512.f) - mean0 * mean0, 0.f);
      v1 = fmaxf(v1 * (1.f / 512.f) - mean1 * mean1, 0.f);
      rs0 = rsqrtf(v0 + 1e-5f);
      rs1 = rsqrtf(v1 + 1e-5f);
      bar_sync(1 + w, 128);
      cluster_wait();
      xoff |= (epoch_c & 1u) ^ 1u;
      asm volatile("" : "+r"(xoff), "+r"(stash));
      PROF(w, 0);
      release(6); release(7);
      if (elect) mbar_arrive(BAR(B_XDONE));
    }

    auto gu_chunk = [&](float (&acc)[32], int f, int slot, int xslot, int hb) INL {
      const float c0 = rs0 * -1.4426950408889634f, c1 = rs1 * -1.4426950408889634f;
      const float q0 = rs0 * rs0, q1 = rs1 * rs1;
      uint32_t h[4];
#pragma unroll
      for (int i = 0; i < 4; i++) {
        const float ga = acc[f * 8 + 2 * i], gb = acc[f * 8 + 2 * i + 1];
        const float ua = acc[16 + f * 8 + 2 * i], ub = acc[16 + f * 8 + 2 * i + 1];
        const float c = (i & 1) ? c1 : c0, q = (i & 1) ? q1 : q0;
        const float da = 1.f + ex2f(fminf(ga * c, 60.f)), db = 1.f + ex2f(fminf(gb * c, 60.f));
        const float rq = rcpf(da * db) * q;
        h[i] = tagged(pack_bf16(ga * ua * (db * rq), gb * ub * (da * rq)), xoff & 1u);
      }
      const int jj = hb * 2 + f;
      sts_u4(stash + slot * 8192 + jj * 2048, h[0], h[1], h[2], h[3]);
      stg_u4(xptr(xslot, jj), h[0], h[1], h[2], h[3]);
    };
    auto kv_stage = [&](float (&acc)[32], int c, int hb) INL {
      const int srow = wq * 16 + (lane & 7) + ((lane >> 3) & 1) * 8;
      const uint32_t base = area + (3 + c) * 8192 + srow * 128;
#pragma unroll
      for (int jj = 0; jj < 2; jj++) {
        const int a = c * 16 + jj * 8;
        uint32_t r0, r1, r2, r3;
        if (c == 0) {
          r0 = pack_bf16(phi_f(acc[a] * rs0), phi_f(acc[a + 1] * rs0));
          r1 = pack_bf16(phi_f(acc[a + 2] * rs1), phi_f(acc[a + 3] * rs1));
          r2 = pack_bf16(phi_f(acc[a + 4] * rs0), phi_f(acc[a + 5] * rs0));
          r3 = pack_bf16(phi_f(acc[a + 6] * rs1), phi_f(acc[a + 7] * rs1));
        } else {
          r0 = pack_bf16(acc[a] * rs0, acc[a + 1] * rs0);
          r1 = pack_bf16(acc[a + 2] * rs1, acc[a + 3] * rs1);
          r2 = pack_bf16(acc[a + 4] * rs0, acc[a + 5] * rs0);
          r3 = pack_bf16(acc[a + 6] * rs1, acc[a + 7] * rs1);
        }
        stmatrix_x4(base + (((hb * 4 + jj * 2 + (lane >> 4)) ^ (srow & 7)) << 4), r0, r1, r2, r3);
      }
    };
    auto q_head = [&](float (&acc)[32], int c, int slot, uint32_t b0, uint32_t b1, uint32_t b2, uint32_t b3, uint32_t z0, uint32_t z1) INL {
      const int a = c * 8;
      const uint32_t a0 = pack_bf16(phi_f(acc[a] * rs0), phi_f(acc[a + 1] * rs0));
      const uint32_t a1 = pack_bf16(phi_f(acc[a + 2] * rs1), phi_f(acc[a + 3] * rs1));
      const uint32_t a2 = pack_bf16(phi_f(acc[a + 4] * rs0), phi_f(acc[a + 5] * rs0));
      const uint32_t a3 = pack_bf16(phi_f(acc[a + 6] * rs1), phi_f(acc[a + 7] * rs1));
      float n0[4] = {0.f, 0.f, 0.f, 0.f}, n1[4] = {0.f, 0.f, 0.f, 0.f}, dn[4] = {0.f, 0.f, 0.f, 0.f};
      mma_16816(n0, a0, a1, a2, a3, b0, b1);
      mma_16816(n1, a0, a1, a2, a3, b2, b3);
      mma_16816(dn, a0, a1, a2, a3, z0, z1);
      const float i0 = __fdividef(1.f, dn[0] + 1e-6f), i1 = __fdividef(1.f, dn[2] + 1e-6f);
      const uint32_t tg = xoff & 1u;
      const uint32_t o0 = tagged(pack_bf16(n0[0] * i0, n0[1] * i0), tg), o1 = tagged(pack_bf16(n0[2] * i1, n0[3] * i1), tg);
      const uint32_t o2 = tagged(pack_bf16(n1[0] * i0, n1[1] * i0), tg), o3 = tagged(pack_bf16(n1[2] * i1, n1[3] * i1), tg);
      sts_u4(stash + slot * 8192 + c * 2048, o0, o1, o2, o3);
      stg_u4(xptr(slot, c), o0, o1, o2, o3);
    };
    const uint32_t kvb = area + 5 * 8192;
    const uint32_t kvfrag = kvb + ((lane & 7) + ((lane >> 3) & 1) * 8) * 32 + (lane >> 4) * 16;
    auto signal = [&](int e) INL {
      __syncwarp();
      if (lane == 0) mbar_arrive(BAR(B_EV + w * 2 + e));
    };

    float accB[32];
    int tw1 = 0, tw2 = 0, tw3 = 0;
#pragma unroll 1
    for (int t = 0; t < 5; t++) {
      float accA[32];
      const uint32_t ph = t & 1;
      const int kindP = t == 0 ? K_NONE : ((odd && t <= 2) ? K_KV : K_GU);
      const int kindC = odd ? (t < 2 ? K_KV : K_GU) : (t < 4 ? K_GU : K_Q);
      const int slotP = odd ? t - 3 : t - 1, xslotP = odd ? t + 3 : t - 1;
      const int slotC = odd ? t - 2 : t, xslotC = odd ? t + 4 : t;
      static_for<8>([&](auto kc) INL {
        constexpr int k = decltype(kc)::value;
        TWAIT(tw1, mbar_wait(BAR(B_FULL + k), ph));
        wgmma_fence();
        static_for<8>([&](auto kkc) INL {
          constexpr int kk = decltype(kkc)::value;
          constexpr int i = ((k & 3) * 8 + kk) * 4;
          constexpr uint32_t lo = desc_lo(stage_off(k) + kk * 1024, 8192);
          if constexpr (k < 4) wgmma_n64_rs<((k & 3) | kk) != 0, lo, kHi64>(accA, A[i], A[i + 1], A[i + 2], A[i + 3], dbase);
          else wgmma_n64_rs<((k & 3) | kk) != 0, lo, kHi64>(accB, A[i], A[i + 1], A[i + 2], A[i + 3], dbase);
        });
        wgmma_commit();
        if (k > 0) {
          TWAIT(tw3, wgmma_wait<1>());
          release(k - 1);
        }
        if constexpr (k < 4) {
          if (kindP == K_GU) {
            if (k == 1 || k == 2) gu_chunk(accB, k - 1, slotP, xslotP, 1);
          } else if (kindP == K_KV) {
            if (k == 1 || k == 2) kv_stage(accB, k - 1, 1);
            if (k == 3) {
              float kvacc[36];
              const int par = (xoff & 1u) ^ 1u;
              fence_proxy_async();
              bar_sync(1 + w, 128);
              wgmma_fence();
              static_for<4>([&](auto kkc) INL {
                constexpr int kk = decltype(kkc)::value;
                wgmma_n72_ss_tt<kk != 0, desc_lo(3 * 8192 + kk * 2048, 0), desc_lo(4 * 8192 + kk * 2048, 8192 - kk * 2048)>(kvacc, dbase + w * 4096);
              });
              wgmma_commit();
              wgmma_wait<0>();
              float c[8];
#pragma unroll
              for (int i = 0; i < 8; i++)
                c[i] = wq == 0 ? kvacc[i] : (wq == 1 ? kvacc[8 + i] : (wq == 2 ? kvacc[16 + i] : kvacc[24 + i]));
              const int head = (2 * p + t - 1) * 4 + wq;
              float* kvp = &g_kv[par][head][0][0];
              red_add_v2(kvp + g * 16 + 2 * tq, c[0], c[1]);
              red_add_v2(kvp + (g + 8) * 16 + 2 * tq, c[2], c[3]);
              red_add_v2(kvp + g * 16 + 8 + 2 * tq, c[4], c[5]);
              red_add_v2(kvp + (g + 8) * 16 + 8 + 2 * tq, c[6], c[7]);
              if (tq == 0) {
                red_add(&g_z[par][head][g], kvacc[32]);
                red_add(&g_z[par][head][g + 8], kvacc[34]);
              }
              signal(t - 1);
            }
          }
        } else {
          constexpr int c = k - 4;
          if (kindC == K_GU) {
            if (c < 2) gu_chunk(accA, c, slotC, xslotC, 0);
          } else if (kindC == K_KV) {
            if (c == 0 && kindP == K_NONE) sts_u4(stash + 5 * 8192, 0x3F803F80u, 0x3F803F80u, 0x3F803F80u, 0x3F803F80u);
            if (c < 2) kv_stage(accA, c, 0);
          } else {
            if (c == 0) mbar_wait(BAR(B_KVREADY), 0);
            uint32_t b0, b1, b2, b3;
            ldmatrix_x4_trans(kvfrag + c * 512, b0, b1, b2, b3);
            const uint32_t z0 = lds_u32(kvb + 4096 + c * 32 + tq * 4), z1 = lds_u32(kvb + 4096 + c * 32 + 16 + tq * 4);
            q_head(accA, c, 4, b0, b1, b2, b3, z0, z1);
          }
        }
      });
      wgmma_wait<0>();
      release(7);
      PROF(w, 1 + 2 * t);
    }
    if (odd) {
      gu_chunk(accB, 0, 2, 8, 1);
      gu_chunk(accB, 1, 2, 8, 1);
    } else {
      uint32_t Bf[4][6];
#pragma unroll
      for (int c = 0; c < 4; c++) {
        ldmatrix_x4_trans(kvfrag + (4 + c) * 512, Bf[c][0], Bf[c][1], Bf[c][2], Bf[c][3]);
        Bf[c][4] = lds_u32(kvb + 4096 + (4 + c) * 32 + tq * 4);
        Bf[c][5] = lds_u32(kvb + 4096 + (4 + c) * 32 + 16 + tq * 4);
      }
      bar_sync(1 + w, 128);
#pragma unroll
      for (int c = 0; c < 4; c++) q_head(accB, c, 5, Bf[c][0], Bf[c][1], Bf[c][2], Bf[c][3], Bf[c][4], Bf[c][5]);
    }
    PROF(w, 10);

    const int n_own = odd ? 3 : 6;
    auto load_a = [&](int kb) INL {
      if (kb < n_own) {
#pragma unroll
        for (int jj = 0; jj < 4; jj++) {
          const int i = (kb * 4 + jj) * 4;
          lds_u4(stash + kb * 8192 + jj * 2048, A[i], A[i + 1], A[i + 2], A[i + 3]);
        }
      } else {
        const int xs = odd ? kb - 3 : kb;
#pragma unroll
        for (int jj = 0; jj < 4; jj++) {
          const int i = (kb * 4 + jj) * 4;
          ldg_poll_u4(xptr(xs, jj), A[i], A[i + 1], A[i + 2], A[i + 3]);
        }
      }
    };
    auto fix_a = [&](int kb) INL {
      if (kb >= n_own) {
        const int xs = odd ? kb - 3 : kb;
        recv_group<4>(xptr(xs, 0), &A[kb * 16], xoff & 1u);
      }
    };
#pragma unroll
    for (int kb = 0; kb < 7; kb++) load_a(kb);
    PROF(w, 11);

    const int orow = m * 128 + w * 64 + wq * 16 + g;
    const int ocol = odd * 256 + p * 64 + 2 * tq;
    float acc2[2][32];
    uint32_t poff = (uint32_t)((m * 2 + odd) * 24 + w) * 8192u + (uint32_t)t128 * 16u;
    asm volatile("" : "+r"(poff));
    auto pptr = [&](int dest, int sl) INL { return (uint4*)((char*)g_pbuf + (poff + (uint32_t)(dest * 3 + sl) * 16384u)); };
    uint32_t P[3][16];
    uint32_t xr[16];
    auto send = [&](float (&acc)[32], int bi) INL {
      uint4* dst = pptr((p + 1 + bi) & 3, bi);
#pragma unroll
      for (int q = 0; q < 4; q++)
        stg_u4(dst + q * 128, tagged(pack_bf16(acc[q * 8], acc[q * 8 + 1]), xoff & 1u), tagged(pack_bf16(acc[q * 8 + 2], acc[q * 8 + 3]), xoff & 1u),
               tagged(pack_bf16(acc[q * 8 + 4], acc[q * 8 + 5]), xoff & 1u), tagged(pack_bf16(acc[q * 8 + 6], acc[q * 8 + 7]), xoff & 1u));
      PROF(w, 12 + 2 * bi);
    };
    auto fetch = [&](int sl) INL {
#pragma unroll
      for (int q = 0; q < 4; q++) ldg_poll_u4(pptr(p, sl) + q * 128, P[sl][q * 4], P[sl][q * 4 + 1], P[sl][q * 4 + 2], P[sl][q * 4 + 3]);
    };
    static_for<36>([&](auto ic) INL {
      constexpr int i = decltype(ic)::value, bi = p2_bi(i), kb = p2_kb(i), j = i >> 1, st = j & 7;
      if (i == 9) { load_a(7); load_a(8); }
      if (i == 14) PROF(w, 2);
      if (bi == 0 && kb >= 3) fix_a(kb);
      if (i == 15) PROF(w, 4);
      if (i == 7) PROF(w, 6);
      if ((i & 1) == 0) TWAIT(tw2, mbar_wait(BAR(B_FULL + st), (5 + (j >> 3)) & 1));
      wgmma_fence();
      static_for<4>([&](auto kkc) INL {
        constexpr int kk = decltype(kkc)::value, a = (kb * 4 + kk) * 4;
        wgmma_n64_rs<(kb | kk) != 0, desc_lo(stage_off(st) + (i & 1) * 8192 + kk * 2048, 0), kHi128>(acc2[bi & 1], A[a], A[a + 1], A[a + 2], A[a + 3], dbase);
      });
      wgmma_commit();
      if (i > 0) {
        wgmma_wait<1>();
        if ((i & 1) == 0 && j - 1 <= 9) release((j - 1) & 7);
      }
      if constexpr (i == 16) send(acc2[0], 0);
      if constexpr (i == 18) send(acc2[1], 1);
      if constexpr (i == 27) send(acc2[0], 2);
      if constexpr (i == 29) fetch(0);
      if constexpr (i == 31) fetch(1);
      if constexpr (i == 32) {
#pragma unroll
        for (int q = 0; q < 8; q++) {
          xr[2 * q] = __ldg((const uint32_t*)(x + (size_t)orow * kD + ocol + q * 8));
          xr[2 * q + 1] = __ldg((const uint32_t*)(x + (size_t)(orow + 8) * kD + ocol + q * 8));
        }
      }
      if constexpr (i == 34) fetch(2);
    });
#pragma unroll
    for (int sl = 0; sl < 3; sl++) { PROF(w, 13 + 2 * sl); recv_group<4>(pptr(p, sl), &P[sl][0], xoff & 1u); }
    wgmma_wait<0>();
    PROF(w, 18);
#pragma unroll
    for (int q = 0; q < 8; q++) {
      float rr[4];
      rr[0] = acc2[1][q * 4 + 0] + __uint_as_float(xr[2 * q] << 16);
      rr[1] = acc2[1][q * 4 + 1] + __uint_as_float(xr[2 * q] & 0xffff0000u);
      rr[2] = acc2[1][q * 4 + 2] + __uint_as_float(xr[2 * q + 1] << 16);
      rr[3] = acc2[1][q * 4 + 3] + __uint_as_float(xr[2 * q + 1] & 0xffff0000u);
#pragma unroll
      for (int sl = 0; sl < 3; sl++) {
        rr[0] += __uint_as_float(P[sl][2 * q] << 16);
        rr[1] += __uint_as_float(P[sl][2 * q] & 0xffff0000u);
        rr[2] += __uint_as_float(P[sl][2 * q + 1] << 16);
        rr[3] += __uint_as_float(P[sl][2 * q + 1] & 0xffff0000u);
      }
      *(uint32_t*)(out + (size_t)orow * kD + ocol + q * 8) = pack_bf16(rr[0], rr[1]);
      *(uint32_t*)(out + (size_t)(orow + 8) * kD + ocol + q * 8) = pack_bf16(rr[2], rr[3]);
    }
    PROF(w, 19);
    if (tid == 0) {
      const uint32_t old = atomicAdd(&g_done, 1u);
      if ((old & 127u) == 127u) st_relaxed(&g_epoch, ld_relaxed(&g_epoch) + 1u);
    }
  }
#undef BAR
}

typedef CUresult (*EncodeFn)(CUtensorMap*, CUtensorMapDataType, cuuint32_t, void*, const cuuint64_t*, const cuuint64_t*,
                             const cuuint32_t*, const cuuint32_t*, CUtensorMapInterleave, CUtensorMapSwizzle,
                             CUtensorMapL2promotion, CUtensorMapFloatOOBfill);

void make_map(EncodeFn enc, CUtensorMap* tm, const void* ptr, int rows, int cols, bool narrow) {
  cuuint64_t gd[2] = {(cuuint64_t)cols, (cuuint64_t)rows};
  cuuint64_t gs[1] = {(cuuint64_t)cols * 2};
  cuuint32_t bd[2] = {narrow ? 32u : 64u, narrow ? 128u : 64u};
  cuuint32_t es[2] = {1, 1};
  enc(tm, CU_TENSOR_MAP_DATA_TYPE_BFLOAT16, 2, const_cast<void*>(ptr), gd, gs, bd, es, CU_TENSOR_MAP_INTERLEAVE_NONE,
      narrow ? CU_TENSOR_MAP_SWIZZLE_64B : CU_TENSOR_MAP_SWIZZLE_128B, CU_TENSOR_MAP_L2_PROMOTION_L2_256B, CU_TENSOR_MAP_FLOAT_OOB_FILL_NONE);
}

}

extern "C" void kernel_launch(void* const* d_in, const int* in_sizes, int n_in, void* d_out, int out_size) {
  static EncodeFn enc = nullptr;
  if (!enc) {
    void* fn = nullptr;
    cudaDriverEntryPointQueryResult qr;
    cudaGetDriverEntryPoint("cuTensorMapEncodeTiled", &fn, cudaEnableDefault, &qr);
    enc = (EncodeFn)fn;
    cudaFuncSetAttribute(fused_kernel, cudaFuncAttributeMaxDynamicSharedMemorySize, kSmemBytes);
  }
  CUtensorMap tm_x, tm_wqkv, tm_w1, tm_w3, tm_w2, tm_wo;
  make_map(enc, &tm_x, d_in[0], kS, kD, false);
  make_map(enc, &tm_wqkv, d_in[1], kD, 3 * kD, true);
  make_map(enc, &tm_wo, d_in[2], kD, kD, false);
  make_map(enc, &tm_w1, d_in[4], kD, kF, true);
  make_map(enc, &tm_w3, d_in[5], kD, kF, true);
  make_map(enc, &tm_w2, d_in[6], kF, kD, false);
  fused_kernel<<<128, 384, kSmemBytes>>>(tm_x, tm_wqkv, tm_w1, tm_w3, tm_w2, tm_wo, (const __nv_bfloat16*)d_in[0],
                                         (__nv_bfloat16*)d_out);
}
```

```cpp
#include <cuda_runtime.h>
#include <cuda_bf16.h>
#include <cuda.h>
#include <stdint.h>

namespace {

constexpr int kS = 2048, kD = 512, kF = 1792;
constexpr uint32_t kSpinLimit = 1u << 22;

__device__ uint4    g_xbuf[16][4][9][2][4][128];
__device__ uint4    g_pbuf[16][2][4][3][2][4][128];
__device__ float    g_kv[2][32][16][16];
__device__ float    g_z[2][32][16];
__device__ uint32_t g_kvcnt[4][32];
__device__ uint32_t g_epoch;
__device__ uint32_t g_done;
#define PROF(wg, i) do {} while (0)
#define TWAIT(acc, stmt) do { stmt; } while (0)

__device__ __forceinline__ uint32_t smem_u32(const void* p) { return (uint32_t)__cvta_generic_to_shared(p); }
__device__ __forceinline__ void mbar_init(uint32_t bar, uint32_t cnt) {
  asm volatile("mbarrier.init.shared::cta.b64 [%0], %1;" ::"r"(bar), "r"(cnt) : "memory");
}
__device__ __forceinline__ void mbar_expect_tx(uint32_t bar, uint32_t bytes) {
  asm volatile("mbarrier.arrive.expect_tx.shared::cta.b64 _, [%0], %1;" ::"r"(bar), "r"(bytes) : "memory");
}
__device__ __forceinline__ void mbar_arrive(uint32_t bar) {
  asm volatile("mbarrier.arrive.shared::cta.b64 _, [%0];" ::"r"(bar) : "memory");
}
__device__ __forceinline__ void mbar_wait(uint32_t bar, uint32_t parity) {
  asm volatile(
      "{\n.reg .pred p;\n"
      "LAB_WAIT:\n"
      "mbarrier.try_wait.parity.shared::cta.b64 p, [%0], %1;\n"
      "@p bra DONE;\n"
      "bra LAB_WAIT;\n"
      "DONE:\n}" ::"r"(bar), "r"(parity) : "memory");
}
__device__ __forceinline__ void tma_load_2d(uint32_t dst, const CUtensorMap* tm, uint32_t bar, int c0, int c1) {
  asm volatile(
      "cp.async.bulk.tensor.2d.shared::cluster.global.mbarrier::complete_tx::bytes [%0], [%1, {%3, %4}], [%2];" ::"r"(dst),
      "l"(tm), "r"(bar), "r"(c0), "r"(c1)
      : "memory");
}
__device__ __forceinline__ void tma_load_2d_mc(uint32_t dst, const CUtensorMap* tm, uint32_t bar, int c0, int c1) {
  asm volatile(
      "cp.async.bulk.tensor.2d.shared::cluster.global.mbarrier::complete_tx::bytes.multicast::cluster [%0], [%1, {%3, %4}], [%2], %5;" ::"r"(dst),
      "l"(tm), "r"(bar), "r"(c0), "r"(c1), "h"((uint16_t)3)
      : "memory");
}
__device__ __forceinline__ void mbar_arrive_cluster(uint32_t bar, uint32_t cta) {
  asm volatile("{\n.reg .b32 ra;\nmapa.shared::cluster.u32 ra, %0, %1;\nmbarrier.arrive.shared::cluster.b64 _, [ra];\n}" ::"r"(bar), "r"(cta) : "memory");
}
__device__ __forceinline__ void prefetch_tmap(const CUtensorMap* tm) {
  asm volatile("prefetch.tensormap [%0];" ::"l"(tm) : "memory");
}
__device__ __forceinline__ void wgmma_fence() { asm volatile("wgmma.fence.sync.aligned;" ::: "memory"); }
__device__ __forceinline__ void wgmma_commit() { asm volatile("wgmma.commit_group.sync.aligned;" ::: "memory"); }
template <int N>
__device__ __forceinline__ void wgmma_wait() { asm volatile("wgmma.wait_group.sync.aligned %0;" ::"n"(N) : "memory"); }
__device__ __forceinline__ void bar_sync(int id, int n) { asm volatile("bar.sync %0, %1;" ::"r"(id), "r"(n) : "memory"); }
__device__ __forceinline__ void bar_arrive(int id, int n) { asm volatile("bar.arrive %0, %1;" ::"r"(id), "r"(n) : "memory"); }
__device__ __forceinline__ void fence_proxy_async() { asm volatile("fence.proxy.async.shared::cta;" ::: "memory"); }

__device__ __forceinline__ uint32_t ld_acquire(const uint32_t* p) {
  uint32_t v;
  asm volatile("ld.acquire.gpu.global.u32 %0, [%1];" : "=r"(v) : "l"(p) : "memory");
  return v;
}
__device__ __forceinline__ uint32_t ld_relaxed(const uint32_t* p) {
  uint32_t v;
  asm volatile("ld.relaxed.gpu.global.u32 %0, [%1];" : "=r"(v) : "l"(p));
  return v;
}
__device__ __forceinline__ void cluster_wait() { asm volatile("barrier.cluster.wait.aligned;" ::: "memory"); }
__device__ __forceinline__ void st_relaxed(uint32_t* p, uint32_t v) {
  asm volatile("st.relaxed.gpu.global.u32 [%0], %1;" ::"l"(p), "r"(v) : "memory");
}
__device__ __forceinline__ void wait_flag_eq(const uint32_t* p, uint32_t val) {
  uint32_t it = 0;
  while (ld_acquire(p) != val) {
    if (++it > kSpinLimit) break;
  }
}
__device__ __forceinline__ void wait_count_ge(const uint32_t* p, uint32_t val) {
  uint32_t it = 0;
  while ((int32_t)(ld_acquire(p) - val) < 0) {
    __nanosleep(64);
    if (++it > kSpinLimit) break;
  }
}
__device__ __forceinline__ void ldg_poll_u4(const void* p, uint32_t& a, uint32_t& b, uint32_t& c, uint32_t& d) {
  asm volatile("ld.relaxed.gpu.global.v4.u32 {%0,%1,%2,%3}, [%4];" : "=r"(a), "=r"(b), "=r"(c), "=r"(d) : "l"(p) : "memory");
}
template <int N>
__device__ __forceinline__ void recv_group(const uint4* p, uint32_t* r, uint32_t tag) {
  uint32_t it = 0;
  while (true) {
    uint32_t bad = 0u;
#pragma unroll
    for (int i = 0; i < 4 * N; i++) bad |= r[i] ^ tag;
    if (!__any_sync(0xffffffffu, (bad & 1u) != 0u) || ++it > kSpinLimit) break;
#pragma unroll
    for (int q = 0; q < N; q++) ldg_poll_u4(p + q * 128, r[q * 4], r[q * 4 + 1], r[q * 4 + 2], r[q * 4 + 3]);
  }
}
__device__ __forceinline__ uint32_t tagged(uint32_t v, uint32_t tag) { return (v & ~1u) | tag; }
__device__ __forceinline__ float4 ldg_cg_f4(const void* p) {
  float4 v;
  asm volatile("ld.global.cg.v4.f32 {%0,%1,%2,%3}, [%4];" : "=f"(v.x), "=f"(v.y), "=f"(v.z), "=f"(v.w) : "l"(p) : "memory");
  return v;
}
__device__ __forceinline__ void stg_u4(void* p, uint32_t a, uint32_t b, uint32_t c, uint32_t d) {
  asm volatile("st.global.v4.u32 [%0], {%1,%2,%3,%4};" ::"l"(p), "r"(a), "r"(b), "r"(c), "r"(d) : "memory");
}
__device__ __forceinline__ void stg_f4(void* p, float a, float b, float c, float d) {
  asm volatile("st.global.v4.f32 [%0], {%1,%2,%3,%4};" ::"l"(p), "f"(a), "f"(b), "f"(c), "f"(d) : "memory");
}
__device__ __forceinline__ void sts_u4(uint32_t addr, uint32_t a, uint32_t b, uint32_t c, uint32_t d) {
  asm volatile("st.shared.v4.u32 [%0], {%1,%2,%3,%4};" ::"r"(addr), "r"(a), "r"(b), "r"(c), "r"(d) : "memory");
}
__device__ __forceinline__ void lds_u4(uint32_t addr, uint32_t& a, uint32_t& b, uint32_t& c, uint32_t& d) {
  asm volatile("ld.shared.v4.u32 {%0,%1,%2,%3}, [%4];" : "=r"(a), "=r"(b), "=r"(c), "=r"(d) : "r"(addr) : "memory");
}
__device__ __forceinline__ uint32_t lds_u32(uint32_t addr) {
  uint32_t v;
  asm volatile("ld.shared.u32 %0, [%1];" : "=r"(v) : "r"(addr) : "memory");
  return v;
}
__device__ __forceinline__ void ldmatrix_x4(uint32_t addr, uint32_t& a, uint32_t& b, uint32_t& c, uint32_t& d) {
  asm volatile("ldmatrix.sync.aligned.m8n8.x4.shared.b16 {%0,%1,%2,%3}, [%4];" : "=r"(a), "=r"(b), "=r"(c), "=r"(d) : "r"(addr) : "memory");
}
__device__ __forceinline__ void ldmatrix_x4_trans(uint32_t addr, uint32_t& a, uint32_t& b, uint32_t& c, uint32_t& d) {
  asm volatile("ldmatrix.sync.aligned.m8n8.x4.trans.shared.b16 {%0,%1,%2,%3}, [%4];" : "=r"(a), "=r"(b), "=r"(c), "=r"(d) : "r"(addr) : "memory");
}
__device__ __forceinline__ void stmatrix_x4(uint32_t addr, uint32_t a, uint32_t b, uint32_t c, uint32_t d) {
  asm volatile("stmatrix.sync.aligned.m8n8.x4.shared.b16 [%0], {%1,%2,%3,%4};" ::"r"(addr), "r"(a), "r"(b), "r"(c), "r"(d) : "memory");
}
__device__ __forceinline__ void mma_16816(float (&c)[4], uint32_t a0, uint32_t a1, uint32_t a2, uint32_t a3, uint32_t b0, uint32_t b1) {
  asm volatile(
      "mma.sync.aligned.m16n8k16.row.col.f32.bf16.bf16.f32 {%0,%1,%2,%3}, {%4,%5,%6,%7}, {%8,%9}, {%0,%1,%2,%3};"
      : "+f"(c[0]), "+f"(c[1]), "+f"(c[2]), "+f"(c[3])
      : "r"(a0), "r"(a1), "r"(a2), "r"(a3), "r"(b0), "r"(b1));
}
__device__ __forceinline__ uint32_t pack_bf16(float lo, float hi) {
  uint32_t r;
  asm("cvt.rn.bf16x2.f32 %0, %1, %2;" : "=r"(r) : "f"(hi), "f"(lo));
  return r;
}
__device__ __forceinline__ uint32_t hsub2_bf16(uint32_t a, uint32_t b) {
  uint32_t r;
  asm("sub.rn.bf16x2 %0, %1, %2;" : "=r"(r) : "r"(a), "r"(b));
  return r;
}
__device__ __forceinline__ float ex2f(float x) {
  float r;
  asm("ex2.approx.ftz.f32 %0, %1;" : "=f"(r) : "f"(x));
  return r;
}
__device__ __forceinline__ float rcpf(float x) {
  float r;
  asm("rcp.approx.ftz.f32 %0, %1;" : "=f"(r) : "f"(x));
  return r;
}
__device__ __forceinline__ void red_add_v2(float* p, float a, float b) {
  asm volatile("red.relaxed.gpu.global.add.v2.f32 [%0], {%1,%2};" ::"l"(p), "f"(a), "f"(b) : "memory");
}
__device__ __forceinline__ void red_add(float* p, float a) {
  asm volatile("red.relaxed.gpu.global.add.f32 [%0], %1;" ::"l"(p), "f"(a) : "memory");
}
__device__ __forceinline__ float phi_f(float t) {
  float e = ex2f(t * 1.4426950408889634f);
  return (t > 0.f ? t + 1.f : e) + 1e-6f;
}

#define R8(a, o) "+f"(a[o + 0]), "+f"(a[o + 1]), "+f"(a[o + 2]), "+f"(a[o + 3]), "+f"(a[o + 4]), "+f"(a[o + 5]), "+f"(a[o + 6]), "+f"(a[o + 7])

#define W8(a, o) "=f"(a[o + 0]), "=f"(a[o + 1]), "=f"(a[o + 2]), "=f"(a[o + 3]), "=f"(a[o + 4]), "=f"(a[o + 5]), "=f"(a[o + 6]), "=f"(a[o + 7])
#define D32 "{%0,%1,%2,%3,%4,%5,%6,%7,%8,%9,%10,%11,%12,%13,%14,%15,%16,%17,%18,%19,%20,%21,%22,%23,%24,%25,%26,%27,%28,%29,%30,%31}"
#define D36 "{%0,%1,%2,%3,%4,%5,%6,%7,%8,%9,%10,%11,%12,%13,%14,%15,%16,%17,%18,%19,%20,%21,%22,%23,%24,%25,%26,%27,%28,%29,%30,%31,%32,%33,%34,%35}"

constexpr uint32_t kHi128 = (1024u >> 4) | (1u << 30);
constexpr uint32_t kHi64 = (512u >> 4) | (2u << 30);
__host__ __device__ constexpr uint32_t desc_lo(uint32_t off, uint32_t lbo) { return (off >> 4) | ((lbo >> 4) << 16); }

template <bool ACC, uint32_t LO, uint32_t HI>
__device__ __forceinline__ void wgmma_n64_rs(float (&d)[32], uint32_t a0, uint32_t a1, uint32_t a2, uint32_t a3, uint32_t base) {
  if (ACC) {
    asm volatile(
        "{\n.reg .pred p;\n.reg .b32 lo;\n.reg .b64 dd;\nsetp.eq.b32 p, 0, 0;\nadd.u32 lo, %36, %37;\nmov.b64 dd, {lo, %38};\n"
        "wgmma.mma_async.sync.aligned.m64n64k16.f32.bf16.bf16 " D32 ", {%32,%33,%34,%35}, dd, p, 1, 1, 1;\n}"
        : R8(d, 0), R8(d, 8), R8(d, 16), R8(d, 24)
        : "r"(a0), "r"(a1), "r"(a2), "r"(a3), "r"(base), "n"(LO), "n"(HI));
  } else {
    asm volatile(
        "{\n.reg .pred p;\n.reg .b32 lo;\n.reg .b64 dd;\nsetp.ne.b32 p, 0, 0;\nadd.u32 lo, %36, %37;\nmov.b64 dd, {lo, %38};\n"
        "wgmma.mma_async.sync.aligned.m64n64k16.f32.bf16.bf16 " D32 ", {%32,%33,%34,%35}, dd, p, 1, 1, 1;\n}"
        : W8(d, 0), W8(d, 8), W8(d, 16), W8(d, 24)
        : "r"(a0), "r"(a1), "r"(a2), "r"(a3), "r"(base), "n"(LO), "n"(HI));
  }
}
template <bool ACC, uint32_t LOA, uint32_t LOB>
__device__ __forceinline__ void wgmma_n72_ss_tt(float (&d)[36], uint32_t base) {
  if (ACC) {
    asm volatile(
        "{\n.reg .pred p;\n.reg .b32 lo;\n.reg .b64 da, db;\nsetp.eq.b32 p, 0, 0;\n"
        "add.u32 lo, %36, %37;\nmov.b64 da, {lo, %39};\nadd.u32 lo, %36, %38;\nmov.b64 db, {lo, %39};\n"
        "wgmma.mma_async.sync.aligned.m64n72k16.f32.bf16.bf16 " D36 ", da, db, p, 1, 1, 1, 1;\n}"
        : R8(d, 0), R8(d, 8), R8(d, 16), R8(d, 24), "+f"(d[32]), "+f"(d[33]), "+f"(d[34]), "+f"(d[35])
        : "r"(base), "n"(LOA), "n"(LOB), "n"(kHi128));
  } else {
    asm volatile(
        "{\n.reg .pred p;\n.reg .b32 lo;\n.reg .b64 da, db;\nsetp.ne.b32 p, 0, 0;\n"
        "add.u32 lo, %36, %37;\nmov.b64 da, {lo, %39};\nadd.u32 lo, %36, %38;\nmov.b64 db, {lo, %39};\n"
        "wgmma.mma_async.sync.aligned.m64n72k16.f32.bf16.bf16 " D36 ", da, db, p, 1, 1, 1, 1;\n}"
        : W8(d, 0), W8(d, 8), W8(d, 16), W8(d, 24), "=f"(d[32]), "=f"(d[33]), "=f"(d[34]), "=f"(d[35])
        : "r"(base), "n"(LOA), "n"(LOB), "n"(kHi128));
  }
}

#define INL __attribute__((always_inline))
template <int V> struct IC { static constexpr int value = V; };
template <int N, int I = 0, typename F>
__device__ __forceinline__ void static_for(F&& f) {
  if constexpr (I < N) { f(IC<I>{}); static_for<N, I + 1>(f); }
}

__host__ __device__ constexpr uint32_t stage_off(int st) {
  return st < 6 ? 131072u + (uint32_t)st * 16384u : (uint32_t)(st - 6) * 65536u + 49152u;
}

constexpr int B_FULL = 0, B_EMPTY = 8, B_XFULL = 16, B_XDONE = 32, B_KVREADY = 33, B_EV = 34, B_COUNT = 38;
constexpr uint32_t kBarOff = 229376;
constexpr int kSmemBytes = 229376 + 1024;

__host__ __device__ constexpr int p2_bi(int i) { return i < 7 ? 0 : i < 14 ? 1 : i < 16 ? 0 : i < 18 ? 1 : i / 9; }
__host__ __device__ constexpr int p2_kb(int i) { return i < 7 ? i : i < 14 ? i - 7 : i < 16 ? i - 7 : i < 18 ? i - 9 : i % 9; }

enum { K_NONE = 0, K_GU = 1, K_KV = 2, K_Q = 3 };

__global__ void __cluster_dims__(2, 1, 1) __launch_bounds__(384, 1)
fused_kernel(const __grid_constant__ CUtensorMap tm_x, const __grid_constant__ CUtensorMap tm_wqkv,
             const __grid_constant__ CUtensorMap tm_w1, const __grid_constant__ CUtensorMap tm_w3,
             const __grid_constant__ CUtensorMap tm_w2, const __grid_constant__ CUtensorMap tm_wo,
             const __nv_bfloat16* __restrict__ x, __nv_bfloat16* __restrict__ out) {
  extern __shared__ __align__(1024) uint8_t smem_raw[];
  const uint32_t sbase = smem_u32(smem_raw);
  const uint32_t bars = sbase + kBarOff;
  const int tid = threadIdx.x, lane = tid & 31;
  const int warp = __shfl_sync(0xffffffffu, tid >> 5, 0);
  const int cr = blockIdx.x & 1;
  const int r = (blockIdx.x >> 1) & 7, m = ((blockIdx.x >> 4) << 1) | cr, p = r >> 1, odd = r & 1;
#define BAR(i) (bars + 8u * (uint32_t)(i))
  if (tid == 256) {
    if (sbase & 1023u) __trap();
#pragma unroll
    for (int i = 0; i < 16; i++) mbar_init(BAR(B_XFULL + i), 1);
    fence_proxy_async();
#pragma unroll
    for (int b = 0; b < 16; b++) {
      mbar_expect_tx(BAR(B_XFULL + b), 8192);
      tma_load_2d(sbase + (b >> 3) * 65536 + (b & 7) * 8192, &tm_x, BAR(B_XFULL + b), (b & 7) * 64, m * 128 + (b >> 3) * 64);
    }
#pragma unroll
    for (int i = 0; i < 8; i++) { mbar_init(BAR(B_FULL + i), 1); mbar_init(BAR(B_EMPTY + i), 4); }
#pragma unroll
    for (int i = 0; i < 4; i++) mbar_init(BAR(B_EV + i), 4);
    mbar_init(BAR(B_XDONE), 2);
    mbar_init(BAR(B_KVREADY), 1);
    asm volatile("fence.mbarrier_init.release.cluster;" ::: "memory");
    fence_proxy_async();
  } else if (tid == 288) {
    prefetch_tmap(odd ? &tm_wqkv : (cr ? &tm_w3 : &tm_w1));
  }
  __syncwarp();
  asm volatile("barrier.cluster.arrive.relaxed.aligned;" ::: "memory");
  PROF((tid >> 7), 21);
  __syncthreads();

  if (warp >= 8) {
    asm volatile("setmaxnreg.dec.sync.aligned.u32 24;");
    PROF(2, 3);
    cluster_wait();
    PROF(2, 2);
    const uint32_t epoch = warp == 8 ? 0u : ld_relaxed(&g_epoch);
    const uint32_t tag = epoch + 1u;
    const int par = epoch & 1;
    if (warp == 8) {
      if (lane == 0) {
        for (int j = 0; j < 10; j++) {
          const CUtensorMap* tm;
          int col;
          if (!odd) {
            if (j < 8) { tm = cr ? &tm_w3 : &tm_w1; col = 7 * p * 64 + j * 32; }
            else { tm = &tm_wqkv; col = 128 * p + (j - 8) * 64 + cr * 32; }
          } else {
            if (j < 4) { tm = &tm_wqkv; col = 512 + cr * 512 + 128 * p + j * 32; }
            else { tm = cr ? &tm_w3 : &tm_w1; col = (7 * p + 4) * 64 + (j - 4) * 32; }
          }
          const int t = j >> 1;
          for (int kq = 0; kq < 4; kq++) {
            const int k = (j & 1) * 4 + kq;
            mbar_wait(BAR(B_EMPTY + k), k < 6 ? ((t & 1) ^ 1) : (t & 1));
            mbar_expect_tx(BAR(B_FULL + k), 16384);
            tma_load_2d_mc(sbase + stage_off(k) + cr * 8192, tm, BAR(B_FULL + k), col, kq * 128);
          }
        }
        for (int j = 0; j < 18; j++) {
          const int st = j & 7, n = 5 + (j >> 3);
          const int i = 2 * j + cr;
          const int bi = p2_bi(i), kb = p2_kb(i);
          const int col = odd * 256 + ((p + 1 + bi) & 3) * 64;
          const CUtensorMap* tmk;
          int row;
          if (!odd) {
            if (kb < 4) { tmk = &tm_w2; row = (7 * p + kb) * 64; }
            else if (kb < 6) { tmk = &tm_wo; row = (2 * p + kb - 4) * 64; }
            else { tmk = &tm_w2; row = (7 * p + 4 + kb - 6) * 64; }
          } else {
            if (kb < 3) { tmk = &tm_w2; row = (7 * p + 4 + kb) * 64; }
            else if (kb < 7) { tmk = &tm_w2; row = (7 * p + kb - 3) * 64; }
            else { tmk = &tm_wo; row = (2 * p + kb - 7) * 64; }
          }
          mbar_wait(BAR(B_EMPTY + st), st < 6 ? ((n & 1) ^ 1) : (n & 1));
          mbar_expect_tx(BAR(B_FULL + st), 16384);
          tma_load_2d_mc(sbase + stage_off(st) + cr * 8192, tmk, BAR(B_FULL + st), col, row);
        }
      }
    } else if (warp <= 10) {
      if (lane == 0 && odd) {
        const int w = warp - 9;
        for (int e = 0; e < 2; e++) {
          mbar_wait(BAR(B_EV + w * 2 + e), 0);
          __threadfence();
          atomicAdd(&g_kvcnt[p][0], 1u);
        }
      }
    } else {
      if (!odd) {
        {
          const int ce = m * 4 + p;
          float* kvn = &g_kv[par ^ 1][0][0][0];
          for (int i = lane; i < 128; i += 32) kvn[ce * 128 + i] = 0.f;
          if (lane < 8) (&g_z[par ^ 1][0][0])[ce * 8 + lane] = 0.f;
        }
        mbar_wait(BAR(B_XDONE), 0);
        wait_count_ge(&g_kvcnt[p][0], 64u * tag);
        const float* kvp = &g_kv[par][8 * p][0][0];
        const uint32_t dst0 = sbase + 5 * 8192, dst1 = dst0 + 65536;
#pragma unroll 4
        for (int i = 0; i < 16; i++) {
          float4 v = ldg_cg_f4(kvp + (i * 32 + lane) * 4);
          uint32_t lo = pack_bf16(v.x, v.y), hi = pack_bf16(v.z, v.w);
          uint32_t off = (uint32_t)(i * 32 + lane) * 8u;
          asm volatile("st.shared.v2.u32 [%0], {%1,%2};" ::"r"(dst0 + off), "r"(lo), "r"(hi) : "memory");
          asm volatile("st.shared.v2.u32 [%0], {%1,%2};" ::"r"(dst1 + off), "r"(lo), "r"(hi) : "memory");
        }
        {
          float4 v = ldg_cg_f4(&g_z[par][8 * p][0] + lane * 4);
          uint32_t lo = pack_bf16(v.x, v.y), hi = pack_bf16(v.z, v.w);
          uint32_t off = 4096u + (uint32_t)lane * 8u;
          asm volatile("st.shared.v2.u32 [%0], {%1,%2};" ::"r"(dst0 + off), "r"(lo), "r"(hi) : "memory");
          asm volatile("st.shared.v2.u32 [%0], {%1,%2};" ::"r"(dst1 + off), "r"(lo), "r"(hi) : "memory");
        }
        __syncwarp();
        if (lane == 0) mbar_arrive(BAR(B_KVREADY));
      }
    }
  } else {
    asm volatile("setmaxnreg.inc.sync.aligned.u32 240;");
    const int w = warp >> 2, wq = warp & 3, t128 = tid & 127;
    const int g = lane >> 2, tq = lane & 3;
    const uint32_t area = sbase + (uint32_t)w * 65536u;
    const bool elect = (t128 == 0);
    PROF(w, 22);
    const uint32_t dbase = (sbase & 0x3FFFFu) >> 4;
    uint32_t xoff = (uint32_t)((m * 4 + p) * 18 + w) * 8192u + (uint32_t)t128 * 16u;
    uint32_t stash = area + (uint32_t)t128 * 16u;
    const uint32_t epoch_c = ld_relaxed(&g_epoch);
    auto xptr = [&](int slot, int jj) INL { return (uint4*)((char*)g_xbuf + ((xoff & ~1u) + (uint32_t)slot * 16384u + (uint32_t)jj * 2048u)); };
    uint32_t A[144];
    float rs0, rs1;
    auto release = [&](int st) INL {
      if (elect) { mbar_arrive_cluster(BAR(B_EMPTY + st), 0); mbar_arrive_cluster(BAR(B_EMPTY + st), 1); }
    };

    {
      const int row = wq * 16 + (lane & 7) + ((lane >> 3) & 1) * 8;
      const uint32_t rbase = area + row * 128;
      float s0[2][4] = {}, q0[2][4] = {}, q1[2][4] = {};
      const uint32_t ones = 0x3F803F80u;
#pragma unroll
      for (int b = 0; b < 8; b++) {
        mbar_wait(BAR(B_XFULL + w * 8 + b), 0);
        if (b == 0) PROF(w, 23);
        if (b == 7) PROF(w, 24);
#pragma unroll
        for (int kk = 0; kk < 4; kk++) {
          const int i = (b * 4 + kk) * 4;
          ldmatrix_x4(rbase + b * 8192 + (((kk * 2 + (lane >> 4)) ^ (row & 7)) << 4), A[i], A[i + 1], A[i + 2], A[i + 3]);
        }
#pragma unroll
        for (int kk = 0; kk < 4; kk++) {
          const int i = (b * 4 + kk) * 4;
          mma_16816(s0[kk & 1], A[i], A[i + 1], A[i + 2], A[i + 3], ones, ones);
          mma_16816(q0[kk & 1], A[i], A[i + 1], A[i + 2], A[i + 3], A[i], A[i + 2]);
          mma_16816(q1[kk & 1], A[i], A[i + 1], A[i + 2], A[i + 3], A[i + 1], A[i + 3]);
        }
      }
      const float mean0 = (s0[0][0] + s0[1][0]) * (1.f / 512.f), mean1 = (s0[0][2] + s0[1][2]) * (1.f / 512.f);
      const uint32_t m0 = pack_bf16(mean0, mean0), m1 = pack_bf16(mean1, mean1);
#pragma unroll
      for (int i = 0; i < 128; i += 2) {
        A[i] = hsub2_bf16(A[i], m0);
        A[i + 1] = hsub2_bf16(A[i + 1], m1);
      }
      float v0 = (g & 1) ? q0[0][1] + q0[1][1] : q0[0][0] + q0[1][0];
      float v1 = (g & 1) ? q1[0][3] + q1[1][3] : q1[0][2] + q1[1][2];
      const int src = 4 * g + (g >> 1);
      v0 = __shfl_sync(0xffffffffu, v0, src);
      v1 = __shfl_sync(0xffffffffu, v1, src);
      v0 = fmaxf(v0 * (1.f / 512.f) - mean0 * mean0, 0.f);
      v1 = fmaxf(v1 * (1.f / 512.f) - mean1 * mean1, 0.f);
      rs0 = rsqrtf(v0 + 1e-5f);
      rs1 = rsqrtf(v1 + 1e-5f);
      bar_sync(1 + w, 128);
      cluster_wait();
      xoff |= (epoch_c & 1u) ^ 1u;
      asm volatile("" : "+r"(xoff), "+r"(stash));
      PROF(w, 0);
      release(6); release(7);
      if (elect) mbar_arrive(BAR(B_XDONE));
    }

    auto gu_chunk = [&](float (&acc)[32], int f, int slot, int xslot, int hb) INL {
      const float c0 = rs0 * -1.4426950408889634f, c1 = rs1 * -1.4426950408889634f;
      const float q0 = rs0 * rs0, q1 = rs1 * rs1;
      uint32_t h[4];
#pragma unroll
      for (int i = 0; i < 4; i++) {
        const float ga = acc[f * 8 + 2 * i], gb = acc[f * 8 + 2 * i + 1];
        const float ua = acc[16 + f * 8 + 2 * i], ub = acc[16 + f * 8 + 2 * i + 1];
        const float c = (i & 1) ? c1 : c0, q = (i & 1) ? q1 : q0;
        const float da = 1.f + ex2f(fminf(ga * c, 60.f)), db = 1.f + ex2f(fminf(gb * c, 60.f));
        const float rq = rcpf(da * db) * q;
        h[i] = tagged(pack_bf16(ga * ua * (db * rq), gb * ub * (da * rq)), xoff & 1u);
      }
      const int jj = hb * 2 + f;
      sts_u4(stash + slot * 8192 + jj * 2048, h[0], h[1], h[2], h[3]);
      stg_u4(xptr(xslot, jj), h[0], h[1], h[2], h[3]);
    };
    auto kv_stage = [&](float (&acc)[32], int c, int hb) INL {
      const int srow = wq * 16 + (lane & 7) + ((lane >> 3) & 1) * 8;
      const uint32_t base = area + (3 + c) * 8192 + srow * 128;
#pragma unroll
      for (int jj = 0; jj < 2; jj++) {
        const int a = c * 16 + jj * 8;
        uint32_t r0, r1, r2, r3;
        if (c == 0) {
          r0 = pack_bf16(phi_f(acc[a] * rs0), phi_f(acc[a + 1] * rs0));
          r1 = pack_bf16(phi_f(acc[a + 2] * rs1), phi_f(acc[a + 3] * rs1));
          r2 = pack_bf16(phi_f(acc[a + 4] * rs0), phi_f(acc[a + 5] * rs0));
          r3 = pack_bf16(phi_f(acc[a + 6] * rs1), phi_f(acc[a + 7] * rs1));
        } else {
          r0 = pack_bf16(acc[a] * rs0, acc[a + 1] * rs0);
          r1 = pack_bf16(acc[a + 2] * rs1, acc[a + 3] * rs1);
          r2 = pack_bf16(acc[a + 4] * rs0, acc[a + 5] * rs0);
          r3 = pack_bf16(acc[a + 6] * rs1, acc[a + 7] * rs1);
        }
        stmatrix_x4(base + (((hb * 4 + jj * 2 + (lane >> 4)) ^ (srow & 7)) << 4), r0, r1, r2, r3);
      }
    };
    auto q_head = [&](float (&acc)[32], int c, int slot, uint32_t b0, uint32_t b1, uint32_t b2, uint32_t b3, uint32_t z0, uint32_t z1) INL {
      const int a = c * 8;
      const uint32_t a0 = pack_bf16(phi_f(acc[a] * rs0), phi_f(acc[a + 1] * rs0));
      const uint32_t a1 = pack_bf16(phi_f(acc[a + 2] * rs1), phi_f(acc[a + 3] * rs1));
      const uint32_t a2 = pack_bf16(phi_f(acc[a + 4] * rs0), phi_f(acc[a + 5] * rs0));
      const uint32_t a3 = pack_bf16(phi_f(acc[a + 6] * rs1), phi_f(acc[a + 7] * rs1));
      float n0[4] = {0.f, 0.f, 0.f, 0.f}, n1[4] = {0.f, 0.f, 0.f, 0.f}, dn[4] = {0.f, 0.f, 0.f, 0.f};
      mma_16816(n0, a0, a1, a2, a3, b0, b1);
      mma_16816(n1, a0, a1, a2, a3, b2, b3);
      mma_16816(dn, a0, a1, a2, a3, z0, z1);
      const float i0 = __fdividef(1.f, dn[0] + 1e-6f), i1 = __fdividef(1.f, dn[2] + 1e-6f);
      const uint32_t tg = xoff & 1u;
      const uint32_t o0 = tagged(pack_bf16(n0[0] * i0, n0[1] * i0), tg), o1 = tagged(pack_bf16(n0[2] * i1, n0[3] * i1), tg);
      const uint32_t o2 = tagged(pack_bf16(n1[0] * i0, n1[1] * i0), tg), o3 = tagged(pack_bf16(n1[2] * i1, n1[3] * i1), tg);
      sts_u4(stash + slot * 8192 + c * 2048, o0, o1, o2, o3);
      stg_u4(xptr(slot, c), o0, o1, o2, o3);
    };
    const uint32_t kvb = area + 5 * 8192;
    const uint32_t kvfrag = kvb + ((lane & 7) + ((lane >> 3) & 1) * 8) * 32 + (lane >> 4) * 16;
    auto signal = [&](int e) INL {
      __syncwarp();
      if (lane == 0) mbar_arrive(BAR(B_EV + w * 2 + e));
    };

    float accB[32];
    int tw1 = 0, tw2 = 0, tw3 = 0;
#pragma unroll 1
    for (int t = 0; t < 5; t++) {
      float accA[32];
      const uint32_t ph = t & 1;
      const int kindP = t == 0 ? K_NONE : ((odd && t <= 2) ? K_KV : K_GU);
      const int kindC = odd ? (t < 2 ? K_KV : K_GU) : (t < 4 ? K_GU : K_Q);
      const int slotP = odd ? t - 3 : t - 1, xslotP = odd ? t + 3 : t - 1;
      const int slotC = odd ? t - 2 : t, xslotC = odd ? t + 4 : t;
      static_for<8>([&](auto kc) INL {
        constexpr int k = decltype(kc)::value;
        TWAIT(tw1, mbar_wait(BAR(B_FULL + k), ph));
        wgmma_fence();
        static_for<8>([&](auto kkc) INL {
          constexpr int kk = decltype(kkc)::value;
          constexpr int i = ((k & 3) * 8 + kk) * 4;
          constexpr uint32_t lo = desc_lo(stage_off(k) + kk * 1024, 8192);
          if constexpr (k < 4) wgmma_n64_rs<((k & 3) | kk) != 0, lo, kHi64>(accA, A[i], A[i + 1], A[i + 2], A[i + 3], dbase);
          else wgmma_n64_rs<((k & 3) | kk) != 0, lo, kHi64>(accB, A[i], A[i + 1], A[i + 2], A[i + 3], dbase);
        });
        wgmma_commit();
        if (k > 0) {
          TWAIT(tw3, wgmma_wait<1>());
          release(k - 1);
        }
        if constexpr (k == 1 || k == 3) {
          if (w == (k >> 1)) {
            if (kindP == K_GU) {
              gu_chunk(accB, 0, slotP, xslotP, 1);
              gu_chunk(accB, 1, slotP, xslotP, 1);
            } else if (kindP == K_KV) {
              kv_stage(accB, 0, 1);
              kv_stage(accB, 1, 1);
              float kvacc[36];
              const int par = (xoff & 1u) ^ 1u;
              fence_proxy_async();
              bar_sync(1 + w, 128);
              wgmma_fence();
              static_for<4>([&](auto kkc) INL {
                constexpr int kk = decltype(kkc)::value;
                wgmma_n72_ss_tt<kk != 0, desc_lo(3 * 8192 + kk * 2048, 0), desc_lo(4 * 8192 + kk * 2048, 8192 - kk * 2048)>(kvacc, dbase + w * 4096);
              });
              wgmma_commit();
              wgmma_wait<0>();
              float c[8];
#pragma unroll
              for (int i = 0; i < 8; i++)
                c[i] = wq == 0 ? kvacc[i] : (wq == 1 ? kvacc[8 + i] : (wq == 2 ? kvacc[16 + i] : kvacc[24 + i]));
              const int head = (2 * p + t - 1) * 4 + wq;
              float* kvp = &g_kv[par][head][0][0];
              red_add_v2(kvp + g * 16 + 2 * tq, c[0], c[1]);
              red_add_v2(kvp + (g + 8) * 16 + 2 * tq, c[2], c[3]);
              red_add_v2(kvp + g * 16 + 8 + 2 * tq, c[4], c[5]);
              red_add_v2(kvp + (g + 8) * 16 + 8 + 2 * tq, c[6], c[7]);
              if (tq == 0) {
                red_add(&g_z[par][head][g], kvacc[32]);
                red_add(&g_z[par][head][g + 8], kvacc[34]);
              }
              signal(t - 1);
            }
          }
        } else if constexpr (k == 5 || k == 7) {
          if (w == ((k - 4) >> 1)) {
            if (kindC == K_GU) {
              gu_chunk(accA, 0, slotC, xslotC, 0);
              gu_chunk(accA, 1, slotC, xslotC, 0);
            } else if (kindC == K_KV) {
              if (kindP == K_NONE) sts_u4(stash + 5 * 8192, 0x3F803F80u, 0x3F803F80u, 0x3F803F80u, 0x3F803F80u);
              kv_stage(accA, 0, 0);
              kv_stage(accA, 1, 0);
            } else {
              mbar_wait(BAR(B_KVREADY), 0);
#pragma unroll
              for (int c = 0; c < 4; c++) {
                uint32_t b0, b1, b2, b3;
                ldmatrix_x4_trans(kvfrag + c * 512, b0, b1, b2, b3);
                const uint32_t z0 = lds_u32(kvb + 4096 + c * 32 + tq * 4), z1 = lds_u32(kvb + 4096 + c * 32 + 16 + tq * 4);
                q_head(accA, c, 4, b0, b1, b2, b3, z0, z1);
              }
            }
          }
        }
      });
      wgmma_wait<0>();
      release(7);
      PROF(w, 1 + 2 * t);
    }
    if (odd) {
      gu_chunk(accB, 0, 2, 8, 1);
      gu_chunk(accB, 1, 2, 8, 1);
    } else {
      uint32_t Bf[4][6];
#pragma unroll
      for (int c = 0; c < 4; c++) {
        ldmatrix_x4_trans(kvfrag + (4 + c) * 512, Bf[c][0], Bf[c][1], Bf[c][2], Bf[c][3]);
        Bf[c][4] = lds_u32(kvb + 4096 + (4 + c) * 32 + tq * 4);
        Bf[c][5] = lds_u32(kvb + 4096 + (4 + c) * 32 + 16 + tq * 4);
      }
      bar_sync(1 + w, 128);
#pragma unroll
      for (int c = 0; c < 4; c++) q_head(accB, c, 5, Bf[c][0], Bf[c][1], Bf[c][2], Bf[c][3], Bf[c][4], Bf[c][5]);
    }
    PROF(w, 10);

    const int n_own = odd ? 3 : 6;
    auto load_a = [&](int kb) INL {
      if (kb < n_own) {
#pragma unroll
        for (int jj = 0; jj < 4; jj++) {
          const int i = (kb * 4 + jj) * 4;
          lds_u4(stash + kb * 8192 + jj * 2048, A[i], A[i + 1], A[i + 2], A[i + 3]);
        }
      } else {
        const int xs = odd ? kb - 3 : kb;
#pragma unroll
        for (int jj = 0; jj < 4; jj++) {
          const int i = (kb * 4 + jj) * 4;
          ldg_poll_u4(xptr(xs, jj), A[i], A[i + 1], A[i + 2], A[i + 3]);
        }
      }
    };
    auto fix_a = [&](int kb) INL {
      if (kb >= n_own) {
        const int xs = odd ? kb - 3 : kb;
        recv_group<4>(xptr(xs, 0), &A[kb * 16], xoff & 1u);
      }
    };
#pragma unroll
    for (int kb = 0; kb < 7; kb++) load_a(kb);
    PROF(w, 11);

    const int orow = m * 128 + w * 64 + wq * 16 + g;
    const int ocol = odd * 256 + p * 64 + 2 * tq;
    float acc2[2][32];
    uint32_t poff = (uint32_t)((m * 2 + odd) * 24 + w) * 8192u + (uint32_t)t128 * 16u;
    asm volatile("" : "+r"(poff));
    auto pptr = [&](int dest, int sl) INL { return (uint4*)((char*)g_pbuf + (poff + (uint32_t)(dest * 3 + sl) * 16384u)); };
    uint32_t P[3][16];
    uint32_t xr[16];
    auto send = [&](float (&acc)[32], int bi) INL {
      uint4* dst = pptr((p + 1 + bi) & 3, bi);
#pragma unroll
      for (int q = 0; q < 4; q++)
        stg_u4(dst + q * 128, tagged(pack_bf16(acc[q * 8], acc[q * 8 + 1]), xoff & 1u), tagged(pack_bf16(acc[q * 8 + 2], acc[q * 8 + 3]), xoff & 1u),
               tagged(pack_bf16(acc[q * 8 + 4], acc[q * 8 + 5]), xoff & 1u), tagged(pack_bf16(acc[q * 8 + 6], acc[q * 8 + 7]), xoff & 1u));
      PROF(w, 12 + 2 * bi);
    };
    auto fetch = [&](int sl) INL {
#pragma unroll
      for (int q = 0; q < 4; q++) ldg_poll_u4(pptr(p, sl) + q * 128, P[sl][q * 4], P[sl][q * 4 + 1], P[sl][q * 4 + 2], P[sl][q * 4 + 3]);
    };
    static_for<36>([&](auto ic) INL {
      constexpr int i = decltype(ic)::value, bi = p2_bi(i), kb = p2_kb(i), j = i >> 1, st = j & 7;
      if (i == 9) { load_a(7); load_a(8); }
      if (i == 14) PROF(w, 2);
      if (bi == 0 && kb >= 3) fix_a(kb);
      if (i == 15) PROF(w, 4);
      if (i == 7) PROF(w, 6);
      if ((i & 1) == 0) TWAIT(tw2, mbar_wait(BAR(B_FULL + st), (5 + (j >> 3)) & 1));
      wgmma_fence();
      static_for<4>([&](auto kkc) INL {
        constexpr int kk = decltype(kkc)::value, a = (kb * 4 + kk) * 4;
        wgmma_n64_rs<(kb | kk) != 0, desc_lo(stage_off(st) + (i & 1) * 8192 + kk * 2048, 0), kHi128>(acc2[bi & 1], A[a], A[a + 1], A[a + 2], A[a + 3], dbase);
      });
      wgmma_commit();
      if (i > 0) {
        wgmma_wait<1>();
        if ((i & 1) == 0 && j - 1 <= 9) release((j - 1) & 7);
      }
      if constexpr (i == 16) send(acc2[0], 0);
      if constexpr (i == 18) send(acc2[1], 1);
      if constexpr (i == 27) send(acc2[0], 2);
      if constexpr (i == 29) fetch(0);
      if constexpr (i == 30) fetch(1);
      if constexpr (i == 28) {
#pragma unroll
        for (int q = 0; q < 8; q++) {
          xr[2 * q] = __ldg((const uint32_t*)(x + (size_t)orow * kD + ocol + q * 8));
          xr[2 * q + 1] = __ldg((const uint32_t*)(x + (size_t)(orow + 8) * kD + ocol + q * 8));
        }
      }
      if constexpr (i == 32) fetch(2);
    });
#pragma unroll
    for (int sl = 0; sl < 3; sl++) { PROF(w, 13 + 2 * sl); recv_group<4>(pptr(p, sl), &P[sl][0], xoff & 1u); }
    wgmma_wait<0>();
    PROF(w, 18);
#pragma unroll
    for (int q = 0; q < 8; q++) {
      float rr[4];
      rr[0] = acc2[1][q * 4 + 0] + __uint_as_float(xr[2 * q] << 16);
      rr[1] = acc2[1][q * 4 + 1] + __uint_as_float(xr[2 * q] & 0xffff0000u);
      rr[2] = acc2[1][q * 4 + 2] + __uint_as_float(xr[2 * q + 1] << 16);
      rr[3] = acc2[1][q * 4 + 3] + __uint_as_float(xr[2 * q + 1] & 0xffff0000u);
#pragma unroll
      for (int sl = 0; sl < 3; sl++) {
        rr[0] += __uint_as_float(P[sl][2 * q] << 16);
        rr[1] += __uint_as_float(P[sl][2 * q] & 0xffff0000u);
        rr[2] += __uint_as_float(P[sl][2 * q + 1] << 16);
        rr[3] += __uint_as_float(P[sl][2 * q + 1] & 0xffff0000u);
      }
      *(uint32_t*)(out + (size_t)orow * kD + ocol + q * 8) = pack_bf16(rr[0], rr[1]);
      *(uint32_t*)(out + (size_t)(orow + 8) * kD + ocol + q * 8) = pack_bf16(rr[2], rr[3]);
    }
    PROF(w, 19);
    if (tid == 0) {
      const uint32_t old = atomicAdd(&g_done, 1u);
      if ((old & 127u) == 127u) st_relaxed(&g_epoch, ld_relaxed(&g_epoch) + 1u);
    }
  }
#undef BAR
}

typedef CUresult (*EncodeFn)(CUtensorMap*, CUtensorMapDataType, cuuint32_t, void*, const cuuint64_t*, const cuuint64_t*,
                             const cuuint32_t*, const cuuint32_t*, CUtensorMapInterleave, CUtensorMapSwizzle,
                             CUtensorMapL2promotion, CUtensorMapFloatOOBfill);

void make_map(EncodeFn enc, CUtensorMap* tm, const void* ptr, int rows, int cols, bool narrow) {
  cuuint64_t gd[2] = {(cuuint64_t)cols, (cuuint64_t)rows};
  cuuint64_t gs[1] = {(cuuint64_t)cols * 2};
  cuuint32_t bd[2] = {narrow ? 32u : 64u, narrow ? 128u : 64u};
  cuuint32_t es[2] = {1, 1};
  enc(tm, CU_TENSOR_MAP_DATA_TYPE_BFLOAT16, 2, const_cast<void*>(ptr), gd, gs, bd, es, CU_TENSOR_MAP_INTERLEAVE_NONE,
      narrow ? CU_TENSOR_MAP_SWIZZLE_64B : CU_TENSOR_MAP_SWIZZLE_128B, CU_TENSOR_MAP_L2_PROMOTION_L2_256B, CU_TENSOR_MAP_FLOAT_OOB_FILL_NONE);
}

}

extern "C" void kernel_launch(void* const* d_in, const int* in_sizes, int n_in, void* d_out, int out_size) {
  static EncodeFn enc = nullptr;
  if (!enc) {
    void* fn = nullptr;
    cudaDriverEntryPointQueryResult qr;
    cudaGetDriverEntryPoint("cuTensorMapEncodeTiled", &fn, cudaEnableDefault, &qr);
    enc = (EncodeFn)fn;
    cudaFuncSetAttribute(fused_kernel, cudaFuncAttributeMaxDynamicSharedMemorySize, kSmemBytes);
  }
  CUtensorMap tm_x, tm_wqkv, tm_w1, tm_w3, tm_w2, tm_wo;
  make_map(enc, &tm_x, d_in[0], kS, kD, false);
  make_map(enc, &tm_wqkv, d_in[1], kD, 3 * kD, true);
  make_map(enc, &tm_wo, d_in[2], kD, kD, false);
  make_map(enc, &tm_w1, d_in[4], kD, kF, true);
  make_map(enc, &tm_w3, d_in[5], kD, kF, true);
  make_map(enc, &tm_w2, d_in[6], kF, kD, false);
  fused_kernel<<<128, 384, kSmemBytes>>>(tm_x, tm_wqkv, tm_w1, tm_w3, tm_w2, tm_wo, (const __nv_bfloat16*)d_in[0],
                                         (__nv_bfloat16*)d_out);
}
```

```cpp
#include <cuda_runtime.h>
#include <cuda_bf16.h>
#include <cuda.h>
#include <stdint.h>

namespace {

constexpr int kS = 2048, kD = 512, kF = 1792;
constexpr uint32_t kSpinLimit = 1u << 22;

__device__ uint4    g_xbuf[16][4][9][2][4][128];
__device__ uint4    g_pbuf[16][2][4][3][2][4][128];
__device__ float    g_kv[2][32][16][16];
__device__ float    g_z[2][32][16];
__device__ uint32_t g_kvcnt[4][32];
__device__ uint32_t g_epoch;
__device__ uint32_t g_done;
#define PROF(wg, i) do {} while (0)
#define TWAIT(acc, stmt) do { stmt; } while (0)

__device__ __forceinline__ uint32_t smem_u32(const void* p) { return (uint32_t)__cvta_generic_to_shared(p); }
__device__ __forceinline__ void mbar_init(uint32_t bar, uint32_t cnt) {
  asm volatile("mbarrier.init.shared::cta.b64 [%0], %1;" ::"r"(bar), "r"(cnt) : "memory");
}
__device__ __forceinline__ void mbar_expect_tx(uint32_t bar, uint32_t bytes) {
  asm volatile("mbarrier.arrive.expect_tx.shared::cta.b64 _, [%0], %1;" ::"r"(bar), "r"(bytes) : "memory");
}
__device__ __forceinline__ void mbar_arrive(uint32_t bar) {
  asm volatile("mbarrier.arrive.shared::cta.b64 _, [%0];" ::"r"(bar) : "memory");
}
__device__ __forceinline__ void mbar_wait(uint32_t bar, uint32_t parity) {
  asm volatile(
      "{\n.reg .pred p;\n"
      "LAB_WAIT:\n"
      "mbarrier.try_wait.parity.shared::cta.b64 p, [%0], %1;\n"
      "@p bra DONE;\n"
      "bra LAB_WAIT;\n"
      "DONE:\n}" ::"r"(bar), "r"(parity) : "memory");
}
__device__ __forceinline__ void tma_load_2d(uint32_t dst, const CUtensorMap* tm, uint32_t bar, int c0, int c1) {
  asm volatile(
      "cp.async.bulk.tensor.2d.shared::cluster.global.mbarrier::complete_tx::bytes [%0], [%1, {%3, %4}], [%2];" ::"r"(dst),
      "l"(tm), "r"(bar), "r"(c0), "r"(c1)
      : "memory");
}
__device__ __forceinline__ void tma_load_2d_mc(uint32_t dst, const CUtensorMap* tm, uint32_t bar, int c0, int c1) {
  asm volatile(
      "cp.async.bulk.tensor.2d.shared::cluster.global.mbarrier::complete_tx::bytes.multicast::cluster [%0], [%1, {%3, %4}], [%2], %5;" ::"r"(dst),
      "l"(tm), "r"(bar), "r"(c0), "r"(c1), "h"((uint16_t)3)
      : "memory");
}
__device__ __forceinline__ void mbar_arrive_cluster(uint32_t bar, uint32_t cta) {
  asm volatile("{\n.reg .b32 ra;\nmapa.shared::cluster.u32 ra, %0, %1;\nmbarrier.arrive.shared::cluster.b64 _, [ra];\n}" ::"r"(bar), "r"(cta) : "memory");
}
__device__ __forceinline__ void prefetch_tmap(const CUtensorMap* tm) {
  asm volatile("prefetch.tensormap [%0];" ::"l"(tm) : "memory");
}
__device__ __forceinline__ void wgmma_fence() { asm volatile("wgmma.fence.sync.aligned;" ::: "memory"); }
__device__ __forceinline__ void wgmma_commit() { asm volatile("wgmma.commit_group.sync.aligned;" ::: "memory"); }
template <int N>
__device__ __forceinline__ void wgmma_wait() { asm volatile("wgmma.wait_group.sync.aligned %0;" ::"n"(N) : "memory"); }
__device__ __forceinline__ void bar_sync(int id, int n) { asm volatile("bar.sync %0, %1;" ::"r"(id), "r"(n) : "memory"); }
__device__ __forceinline__ void bar_arrive(int id, int n) { asm volatile("bar.arrive %0, %1;" ::"r"(id), "r"(n) : "memory"); }
__device__ __forceinline__ void fence_proxy_async() { asm volatile("fence.proxy.async.shared::cta;" ::: "memory"); }

__device__ __forceinline__ uint32_t ld_acquire(const uint32_t* p) {
  uint32_t v;
  asm volatile("ld.acquire.gpu.global.u32 %0, [%1];" : "=r"(v) : "l"(p) : "memory");
  return v;
}
__device__ __forceinline__ uint32_t ld_relaxed(const uint32_t* p) {
  uint32_t v;
  asm volatile("ld.relaxed.gpu.global.u32 %0, [%1];" : "=r"(v) : "l"(p));
  return v;
}
__device__ __forceinline__ void cluster_wait() { asm volatile("barrier.cluster.wait.aligned;" ::: "memory"); }
__device__ __forceinline__ void st_relaxed(uint32_t* p, uint32_t v) {
  asm volatile("st.relaxed.gpu.global.u32 [%0], %1;" ::"l"(p), "r"(v) : "memory");
}
__device__ __forceinline__ void wait_flag_eq(const uint32_t* p, uint32_t val) {
  uint32_t it = 0;
  while (ld_acquire(p) != val) {
    if (++it > kSpinLimit) break;
  }
}
__device__ __forceinline__ void wait_count_ge(const uint32_t* p, uint32_t val) {
  uint32_t it = 0;
  while ((int32_t)(ld_acquire(p) - val) < 0) {
    __nanosleep(64);
    if (++it > kSpinLimit) break;
  }
}
__device__ __forceinline__ void ldg_poll_u4(const void* p, uint32_t& a, uint32_t& b, uint32_t& c, uint32_t& d) {
  asm volatile("ld.relaxed.gpu.global.v4.u32 {%0,%1,%2,%3}, [%4];" : "=r"(a), "=r"(b), "=r"(c), "=r"(d) : "l"(p) : "memory");
}
template <int N>
__device__ __forceinline__ void recv_group(const uint4* p, uint32_t* r, uint32_t tag) {
  uint32_t it = 0;
  while (true) {
    uint32_t bad = 0u;
#pragma unroll
    for (int i = 0; i < 4 * N; i++) bad |= r[i] ^ tag;
    if (!__any_sync(0xffffffffu, (bad & 1u) != 0u) || ++it > kSpinLimit) break;
#pragma unroll
    for (int q = 0; q < N; q++) ldg_poll_u4(p + q * 128, r[q * 4], r[q * 4 + 1], r[q * 4 + 2], r[q * 4 + 3]);
  }
}
__device__ __forceinline__ uint32_t tagged(uint32_t v, uint32_t tag) { return (v & ~1u) | tag; }
__device__ __forceinline__ float4 ldg_cg_f4(const void* p) {
  float4 v;
  asm volatile("ld.global.cg.v4.f32 {%0,%1,%2,%3}, [%4];" : "=f"(v.x), "=f"(v.y), "=f"(v.z), "=f"(v.w) : "l"(p) : "memory");
  return v;
}
__device__ __forceinline__ void stg_u4(void* p, uint32_t a, uint32_t b, uint32_t c, uint32_t d) {
  asm volatile("st.global.v4.u32 [%0], {%1,%2,%3,%4};" ::"l"(p), "r"(a), "r"(b), "r"(c), "r"(d) : "memory");
}
__device__ __forceinline__ void stg_f4(void* p, float a, float b, float c, float d) {
  asm volatile("st.global.v4.f32 [%0], {%1,%2,%3,%4};" ::"l"(p), "f"(a), "f"(b), "f"(c), "f"(d) : "memory");
}
__device__ __forceinline__ void sts_u4(uint32_t addr, uint32_t a, uint32_t b, uint32_t c, uint32_t d) {
  asm volatile("st.shared.v4.u32 [%0], {%1,%2,%3,%4};" ::"r"(addr), "r"(a), "r"(b), "r"(c), "r"(d) : "memory");
}
__device__ __forceinline__ void lds_u4(uint32_t addr, uint32_t& a, uint32_t& b, uint32_t& c, uint32_t& d) {
  asm volatile("ld.shared.v4.u32 {%0,%1,%2,%3}, [%4];" : "=r"(a), "=r"(b), "=r"(c), "=r"(d) : "r"(addr) : "memory");
}
__device__ __forceinline__ uint32_t lds_u32(uint32_t addr) {
  uint32_t v;
  asm volatile("ld.shared.u32 %0, [%1];" : "=r"(v) : "r"(addr) : "memory");
  return v;
}
__device__ __forceinline__ void ldmatrix_x4(uint32_t addr, uint32_t& a, uint32_t& b, uint32_t& c, uint32_t& d) {
  asm volatile("ldmatrix.sync.aligned.m8n8.x4.shared.b16 {%0,%1,%2,%3}, [%4];" : "=r"(a), "=r"(b), "=r"(c), "=r"(d) : "r"(addr) : "memory");
}
__device__ __forceinline__ void ldmatrix_x4_trans(uint32_t addr, uint32_t& a, uint32_t& b, uint32_t& c, uint32_t& d) {
  asm volatile("ldmatrix.sync.aligned.m8n8.x4.trans.shared.b16 {%0,%1,%2,%3}, [%4];" : "=r"(a), "=r"(b), "=r"(c), "=r"(d) : "r"(addr) : "memory");
}
__device__ __forceinline__ void stmatrix_x4(uint32_t addr, uint32_t a, uint32_t b, uint32_t c, uint32_t d) {
  asm volatile("stmatrix.sync.aligned.m8n8.x4.shared.b16 [%0], {%1,%2,%3,%4};" ::"r"(addr), "r"(a), "r"(b), "r"(c), "r"(d) : "memory");
}
__device__ __forceinline__ void mma_16816(float (&c)[4], uint32_t a0, uint32_t a1, uint32_t a2, uint32_t a3, uint32_t b0, uint32_t b1) {
  asm(
      "mma.sync.aligned.m16n8k16.row.col.f32.bf16.bf16.f32 {%0,%1,%2,%3}, {%4,%5,%6,%7}, {%8,%9}, {%0,%1,%2,%3};"
      : "+f"(c[0]), "+f"(c[1]), "+f"(c[2]), "+f"(c[3])
      : "r"(a0), "r"(a1), "r"(a2), "r"(a3), "r"(b0), "r"(b1));
}
__device__ __forceinline__ uint32_t pack_bf16(float lo, float hi) {
  uint32_t r;
  asm("cvt.rn.bf16x2.f32 %0, %1, %2;" : "=r"(r) : "f"(hi), "f"(lo));
  return r;
}
__device__ __forceinline__ uint32_t hsub2_bf16(uint32_t a, uint32_t b) {
  uint32_t r;
  asm("sub.rn.bf16x2 %0, %1, %2;" : "=r"(r) : "r"(a), "r"(b));
  return r;
}
__device__ __forceinline__ float ex2f(float x) {
  float r;
  asm("ex2.approx.ftz.f32 %0, %1;" : "=f"(r) : "f"(x));
  return r;
}
__device__ __forceinline__ float rcpf(float x) {
  float r;
  asm("rcp.approx.ftz.f32 %0, %1;" : "=f"(r) : "f"(x));
  return r;
}
__device__ __forceinline__ void red_add_v2(float* p, float a, float b) {
  asm volatile("red.relaxed.gpu.global.add.v2.f32 [%0], {%1,%2};" ::"l"(p), "f"(a), "f"(b) : "memory");
}
__device__ __forceinline__ void red_add(float* p, float a) {
  asm volatile("red.relaxed.gpu.global.add.f32 [%0], %1;" ::"l"(p), "f"(a) : "memory");
}
__device__ __forceinline__ float phi_f(float t) {
  float e = ex2f(t * 1.4426950408889634f);
  return (t > 0.f ? t + 1.f : e) + 1e-6f;
}

#define R8(a, o) "+f"(a[o + 0]), "+f"(a[o + 1]), "+f"(a[o + 2]), "+f"(a[o + 3]), "+f"(a[o + 4]), "+f"(a[o + 5]), "+f"(a[o + 6]), "+f"(a[o + 7])

#define W8(a, o) "=f"(a[o + 0]), "=f"(a[o + 1]), "=f"(a[o + 2]), "=f"(a[o + 3]), "=f"(a[o + 4]), "=f"(a[o + 5]), "=f"(a[o + 6]), "=f"(a[o + 7])
#define D32 "{%0,%1,%2,%3,%4,%5,%6,%7,%8,%9,%10,%11,%12,%13,%14,%15,%16,%17,%18,%19,%20,%21,%22,%23,%24,%25,%26,%27,%28,%29,%30,%31}"
#define D36 "{%0,%1,%2,%3,%4,%5,%6,%7,%8,%9,%10,%11,%12,%13,%14,%15,%16,%17,%18,%19,%20,%21,%22,%23,%24,%25,%26,%27,%28,%29,%30,%31,%32,%33,%34,%35}"

constexpr uint32_t kHi128 = (1024u >> 4) | (1u << 30);
constexpr uint32_t kHi64 = (512u >> 4) | (2u << 30);
__host__ __device__ constexpr uint32_t desc_lo(uint32_t off, uint32_t lbo) { return (off >> 4) | ((lbo >> 4) << 16); }

template <bool ACC, uint32_t LO, uint32_t HI>
__device__ __forceinline__ void wgmma_n64_rs(float (&d)[32], uint32_t a0, uint32_t a1, uint32_t a2, uint32_t a3, uint32_t base) {
  if (ACC) {
    asm volatile(
        "{\n.reg .pred p;\n.reg .b32 lo;\n.reg .b64 dd;\nsetp.eq.b32 p, 0, 0;\nadd.u32 lo, %36, %37;\nmov.b64 dd, {lo, %38};\n"
        "wgmma.mma_async.sync.aligned.m64n64k16.f32.bf16.bf16 " D32 ", {%32,%33,%34,%35}, dd, p, 1, 1, 1;\n}"
        : R8(d, 0), R8(d, 8), R8(d, 16), R8(d, 24)
        : "r"(a0), "r"(a1), "r"(a2), "r"(a3), "r"(base), "n"(LO), "n"(HI));
  } else {
    asm volatile(
        "{\n.reg .pred p;\n.reg .b32 lo;\n.reg .b64 dd;\nsetp.ne.b32 p, 0, 0;\nadd.u32 lo, %36, %37;\nmov.b64 dd, {lo, %38};\n"
        "wgmma.mma_async.sync.aligned.m64n64k16.f32.bf16.bf16 " D32 ", {%32,%33,%34,%35}, dd, p, 1, 1, 1;\n}"
        : W8(d, 0), W8(d, 8), W8(d, 16), W8(d, 24)
        : "r"(a0), "r"(a1), "r"(a2), "r"(a3), "r"(base), "n"(LO), "n"(HI));
  }
}
template <bool ACC, uint32_t LOA, uint32_t LOB>
__device__ __forceinline__ void wgmma_n72_ss_tt(float (&d)[36], uint32_t base) {
  if (ACC) {
    asm volatile(
        "{\n.reg .pred p;\n.reg .b32 lo;\n.reg .b64 da, db;\nsetp.eq.b32 p, 0, 0;\n"
        "add.u32 lo, %36, %37;\nmov.b64 da, {lo, %39};\nadd.u32 lo, %36, %38;\nmov.b64 db, {lo, %39};\n"
        "wgmma.mma_async.sync.aligned.m64n72k16.f32.bf16.bf16 " D36 ", da, db, p, 1, 1, 1, 1;\n}"
        : R8(d, 0), R8(d, 8), R8(d, 16), R8(d, 24), "+f"(d[32]), "+f"(d[33]), "+f"(d[34]), "+f"(d[35])
        : "r"(base), "n"(LOA), "n"(LOB), "n"(kHi128));
  } else {
    asm volatile(
        "{\n.reg .pred p;\n.reg .b32 lo;\n.reg .b64 da, db;\nsetp.ne.b32 p, 0, 0;\n"
        "add.u32 lo, %36, %37;\nmov.b64 da, {lo, %39};\nadd.u32 lo, %36, %38;\nmov.b64 db, {lo, %39};\n"
        "wgmma.mma_async.sync.aligned.m64n72k16.f32.bf16.bf16 " D36 ", da, db, p, 1, 1, 1, 1;\n}"
        : W8(d, 0), W8(d, 8), W8(d, 16), W8(d, 24), "=f"(d[32]), "=f"(d[33]), "=f"(d[34]), "=f"(d[35])
        : "r"(base), "n"(LOA), "n"(LOB), "n"(kHi128));
  }
}

#define INL __attribute__((always_inline))
template <int V> struct IC { static constexpr int value = V; };
template <int N, int I = 0, typename F>
__device__ __forceinline__ void static_for(F&& f) {
  if constexpr (I < N) { f(IC<I>{}); static_for<N, I + 1>(f); }
}

__host__ __device__ constexpr uint32_t stage_off(int st) {
  return st < 6 ? 131072u + (uint32_t)st * 16384u : (uint32_t)(st - 6) * 65536u + 49152u;
}

constexpr int B_FULL = 0, B_EMPTY = 8, B_XFULL = 16, B_XDONE = 32, B_KVREADY = 33, B_EV = 34, B_COUNT = 38;
constexpr uint32_t kBarOff = 229376;
constexpr int kSmemBytes = 229376 + 1024;

__host__ __device__ constexpr int p2_bi(int i) { return i < 7 ? 0 : i < 14 ? 1 : i < 16 ? 0 : i < 18 ? 1 : i / 9; }
__host__ __device__ constexpr int p2_kb(int i) { return i < 7 ? i : i < 14 ? i - 7 : i < 16 ? i - 7 : i < 18 ? i - 9 : i % 9; }

enum { K_NONE = 0, K_GU = 1, K_KV = 2, K_Q = 3 };

__global__ void __cluster_dims__(2, 1, 1) __launch_bounds__(384, 1)
fused_kernel(const __grid_constant__ CUtensorMap tm_x, const __grid_constant__ CUtensorMap tm_wqkv,
             const __grid_constant__ CUtensorMap tm_w1, const __grid_constant__ CUtensorMap tm_w3,
             const __grid_constant__ CUtensorMap tm_w2, const __grid_constant__ CUtensorMap tm_wo,
             const __nv_bfloat16* __restrict__ x, __nv_bfloat16* __restrict__ out) {
  extern __shared__ __align__(1024) uint8_t smem_raw[];
  const uint32_t sbase = smem_u32(smem_raw);
  const uint32_t bars = sbase + kBarOff;
  const int tid = threadIdx.x, lane = tid & 31;
  const int warp = __shfl_sync(0xffffffffu, tid >> 5, 0);
  const int cr = blockIdx.x & 1;
  const int r = (blockIdx.x >> 1) & 7, m = ((blockIdx.x >> 4) << 1) | cr, p = r >> 1, odd = r & 1;
#define BAR(i) (bars + 8u * (uint32_t)(i))
  if (tid == 256) {
    if (sbase & 1023u) __trap();
#pragma unroll
    for (int i = 0; i < 16; i++) mbar_init(BAR(B_XFULL + i), 1);
    fence_proxy_async();
#pragma unroll
    for (int b = 0; b < 16; b++) {
      mbar_expect_tx(BAR(B_XFULL + b), 8192);
      tma_load_2d(sbase + (b >> 3) * 65536 + (b & 7) * 8192, &tm_x, BAR(B_XFULL + b), (b & 7) * 64, m * 128 + (b >> 3) * 64);
    }
#pragma unroll
    for (int i = 0; i < 8; i++) { mbar_init(BAR(B_FULL + i), 1); mbar_init(BAR(B_EMPTY + i), 4); }
#pragma unroll
    for (int i = 0; i < 4; i++) mbar_init(BAR(B_EV + i), 4);
    mbar_init(BAR(B_XDONE), 2);
    mbar_init(BAR(B_KVREADY), 1);
    asm volatile("fence.mbarrier_init.release.cluster;" ::: "memory");
    fence_proxy_async();
  } else if (tid == 288) {
    prefetch_tmap(odd ? &tm_wqkv : (cr ? &tm_w3 : &tm_w1));
  }
  __syncwarp();
  asm volatile("barrier.cluster.arrive.relaxed.aligned;" ::: "memory");
  PROF((tid >> 7), 21);
  __syncthreads();

  if (warp >= 8) {
    asm volatile("setmaxnreg.dec.sync.aligned.u32 24;");
    PROF(2, 3);
    cluster_wait();
    PROF(2, 2);
    const uint32_t epoch = warp == 8 ? 0u : ld_relaxed(&g_epoch);
    const uint32_t tag = epoch + 1u;
    const int par = epoch & 1;
    if (warp == 8) {
      if (lane == 0) {
        for (int j = 0; j < 10; j++) {
          const CUtensorMap* tm;
          int col;
          if (!odd) {
            if (j < 8) { tm = cr ? &tm_w3 : &tm_w1; col = 7 * p * 64 + j * 32; }
            else { tm = &tm_wqkv; col = 128 * p + (j - 8) * 64 + cr * 32; }
          } else {
            if (j < 4) { tm = &tm_wqkv; col = 512 + cr * 512 + 128 * p + j * 32; }
            else { tm = cr ? &tm_w3 : &tm_w1; col = (7 * p + 4) * 64 + (j - 4) * 32; }
          }
          const int t = j >> 1;
          for (int kq = 0; kq < 4; kq++) {
            const int k = (j & 1) * 4 + kq;
            mbar_wait(BAR(B_EMPTY + k), k < 6 ? ((t & 1) ^ 1) : (t & 1));
            mbar_expect_tx(BAR(B_FULL + k), 16384);
            tma_load_2d_mc(sbase + stage_off(k) + cr * 8192, tm, BAR(B_FULL + k), col, kq * 128);
          }
        }
        for (int j = 0; j < 18; j++) {
          const int st = j & 7, n = 5 + (j >> 3);
          const int i = 2 * j + cr;
          const int bi = p2_bi(i), kb = p2_kb(i);
          const int col = odd * 256 + ((p + 1 + bi) & 3) * 64;
          const CUtensorMap* tmk;
          int row;
          if (!odd) {
            if (kb < 4) { tmk = &tm_w2; row = (7 * p + kb) * 64; }
            else if (kb < 6) { tmk = &tm_wo; row = (2 * p + kb - 4) * 64; }
            else { tmk = &tm_w2; row = (7 * p + 4 + kb - 6) * 64; }
          } else {
            if (kb < 3) { tmk = &tm_w2; row = (7 * p + 4 + kb) * 64; }
            else if (kb < 7) { tmk = &tm_w2; row = (7 * p + kb - 3) * 64; }
            else { tmk = &tm_wo; row = (2 * p + kb - 7) * 64; }
          }
          mbar_wait(BAR(B_EMPTY + st), st < 6 ? ((n & 1) ^ 1) : (n & 1));
          mbar_expect_tx(BAR(B_FULL + st), 16384);
          tma_load_2d_mc(sbase + stage_off(st) + cr * 8192, tmk, BAR(B_FULL + st), col, row);
        }
      }
    } else if (warp <= 10) {
      if (lane == 0 && odd) {
        const int w = warp - 9;
        for (int e = 0; e < 2; e++) {
          mbar_wait(BAR(B_EV + w * 2 + e), 0);
          __threadfence();
          atomicAdd(&g_kvcnt[p][0], 1u);
        }
      }
    } else {
      if (!odd) {
        {
          const int ce = m * 4 + p;
          float* kvn = &g_kv[par ^ 1][0][0][0];
          for (int i = lane; i < 128; i += 32) kvn[ce * 128 + i] = 0.f;
          if (lane < 8) (&g_z[par ^ 1][0][0])[ce * 8 + lane] = 0.f;
        }
        mbar_wait(BAR(B_XDONE), 0);
        wait_count_ge(&g_kvcnt[p][0], 64u * tag);
        const float* kvp = &g_kv[par][8 * p][0][0];
        const uint32_t dst0 = sbase + 5 * 8192, dst1 = dst0 + 65536;
#pragma unroll 4
        for (int i = 0; i < 16; i++) {
          float4 v = ldg_cg_f4(kvp + (i * 32 + lane) * 4);
          uint32_t lo = pack_bf16(v.x, v.y), hi = pack_bf16(v.z, v.w);
          uint32_t off = (uint32_t)(i * 32 + lane) * 8u;
          asm volatile("st.shared.v2.u32 [%0], {%1,%2};" ::"r"(dst0 + off), "r"(lo), "r"(hi) : "memory");
          asm volatile("st.shared.v2.u32 [%0], {%1,%2};" ::"r"(dst1 + off), "r"(lo), "r"(hi) : "memory");
        }
        {
          float4 v = ldg_cg_f4(&g_z[par][8 * p][0] + lane * 4);
          uint32_t lo = pack_bf16(v.x, v.y), hi = pack_bf16(v.z, v.w);
          uint32_t off = 4096u + (uint32_t)lane * 8u;
          asm volatile("st.shared.v2.u32 [%0], {%1,%2};" ::"r"(dst0 + off), "r"(lo), "r"(hi) : "memory");
          asm volatile("st.shared.v2.u32 [%0], {%1,%2};" ::"r"(dst1 + off), "r"(lo), "r"(hi) : "memory");
        }
        __syncwarp();
        if (lane == 0) mbar_arrive(BAR(B_KVREADY));
      }
    }
  } else {
    asm volatile("setmaxnreg.inc.sync.aligned.u32 240;");
    const int w = warp >> 2, wq = warp & 3, t128 = tid & 127;
    const int g = lane >> 2, tq = lane & 3;
    const uint32_t area = sbase + (uint32_t)w * 65536u;
    const bool elect = (t128 == 0);
    PROF(w, 22);
    const uint32_t dbase = (sbase & 0x3FFFFu) >> 4;
    uint32_t xoff = (uint32_t)((m * 4 + p) * 18 + w) * 8192u + (uint32_t)t128 * 16u;
    uint32_t stash = area + (uint32_t)t128 * 16u;
    const uint32_t epoch_c = ld_relaxed(&g_epoch);
    auto xptr = [&](int slot, int jj) INL { return (uint4*)((char*)g_xbuf + ((xoff & ~1u) + (uint32_t)slot * 16384u + (uint32_t)jj * 2048u)); };
    uint32_t A[144];
    float rs0, rs1;
    auto release = [&](int st) INL {
      if (elect) { mbar_arrive_cluster(BAR(B_EMPTY + st), 0); mbar_arrive_cluster(BAR(B_EMPTY + st), 1); }
    };

    {
      const int row = wq * 16 + (lane & 7) + ((lane >> 3) & 1) * 8;
      const uint32_t rbase = area + row * 128;
      float s0[2][4] = {}, q0[2][4] = {}, q1[2][4] = {};
      const uint32_t ones = 0x3F803F80u;
#pragma unroll
      for (int b = 0; b < 8; b++) {
        mbar_wait(BAR(B_XFULL + w * 8 + b), 0);
        if (b == 0) PROF(w, 23);
        if (b == 7) PROF(w, 24);
#pragma unroll
        for (int kk = 0; kk < 4; kk++) {
          const int i = (b * 4 + kk) * 4;
          ldmatrix_x4(rbase + b * 8192 + (((kk * 2 + (lane >> 4)) ^ (row & 7)) << 4), A[i], A[i + 1], A[i + 2], A[i + 3]);
        }
#pragma unroll
        for (int kk = 0; kk < 4; kk++) {
          const int i = (b * 4 + kk) * 4;
          mma_16816(s0[kk & 1], A[i], A[i + 1], A[i + 2], A[i + 3], ones, ones);
          mma_16816(q0[kk & 1], A[i], A[i + 1], A[i + 2], A[i + 3], A[i], A[i + 2]);
          mma_16816(q1[kk & 1], A[i], A[i + 1], A[i + 2], A[i + 3], A[i + 1], A[i + 3]);
        }
      }
      const float mean0 = (s0[0][0] + s0[1][0]) * (1.f / 512.f), mean1 = (s0[0][2] + s0[1][2]) * (1.f / 512.f);
      const uint32_t m0 = pack_bf16(mean0, mean0), m1 = pack_bf16(mean1, mean1);
#pragma unroll
      for (int i = 0; i < 128; i += 2) {
        A[i] = hsub2_bf16(A[i], m0);
        A[i + 1] = hsub2_bf16(A[i + 1], m1);
      }
      float v0 = (g & 1) ? q0[0][1] + q0[1][1] : q0[0][0] + q0[1][0];
      float v1 = (g & 1) ? q1[0][3] + q1[1][3] : q1[0][2] + q1[1][2];
      const int src = 4 * g + (g >> 1);
      v0 = __shfl_sync(0xffffffffu, v0, src);
      v1 = __shfl_sync(0xffffffffu, v1, src);
      v0 = fmaxf(v0 * (1.f / 512.f) - mean0 * mean0, 0.f);
      v1 = fmaxf(v1 * (1.f / 512.f) - mean1 * mean1, 0.f);
      rs0 = rsqrtf(v0 + 1e-5f);
      rs1 = rsqrtf(v1 + 1e-5f);
      bar_sync(1 + w, 128);
      cluster_wait();
      xoff |= (epoch_c & 1u) ^ 1u;
      asm volatile("" : "+r"(xoff), "+r"(stash));
      PROF(w, 0);
      release(6); release(7);
      if (elect) mbar_arrive(BAR(B_XDONE));
    }

    auto gu_chunk = [&](float (&acc)[32], int f, int slot, int xslot, int hb) INL {
      const float c0 = rs0 * -1.4426950408889634f, c1 = rs1 * -1.4426950408889634f;
      const float q0 = rs0 * rs0, q1 = rs1 * rs1;
      uint32_t h[4];
#pragma unroll
      for (int i = 0; i < 4; i++) {
        const float ga = acc[f * 8 + 2 * i], gb = acc[f * 8 + 2 * i + 1];
        const float ua = acc[16 + f * 8 + 2 * i], ub = acc[16 + f * 8 + 2 * i + 1];
        const float c = (i & 1) ? c1 : c0, q = (i & 1) ? q1 : q0;
        const float da = 1.f + ex2f(fminf(ga * c, 60.f)), db = 1.f + ex2f(fminf(gb * c, 60.f));
        const float rq = rcpf(da * db) * q;
        h[i] = tagged(pack_bf16(ga * ua * (db * rq), gb * ub * (da * rq)), xoff & 1u);
      }
      const int jj = hb * 2 + f;
      sts_u4(stash + slot * 8192 + jj * 2048, h[0], h[1], h[2], h[3]);
      stg_u4(xptr(xslot, jj), h[0], h[1], h[2], h[3]);
    };
    auto kv_stage = [&](float (&acc)[32], int c, int hb) INL {
      const int srow = wq * 16 + (lane & 7) + ((lane >> 3) & 1) * 8;
      const uint32_t base = area + (3 + c) * 8192 + srow * 128;
#pragma unroll
      for (int jj = 0; jj < 2; jj++) {
        const int a = c * 16 + jj * 8;
        uint32_t r0, r1, r2, r3;
        if (c == 0) {
          r0 = pack_bf16(phi_f(acc[a] * rs0), phi_f(acc[a + 1] * rs0));
          r1 = pack_bf16(phi_f(acc[a + 2] * rs1), phi_f(acc[a + 3] * rs1));
          r2 = pack_bf16(phi_f(acc[a + 4] * rs0), phi_f(acc[a + 5] * rs0));
          r3 = pack_bf16(phi_f(acc[a + 6] * rs1), phi_f(acc[a + 7] * rs1));
        } else {
          r0 = pack_bf16(acc[a] * rs0, acc[a + 1] * rs0);
          r1 = pack_bf16(acc[a + 2] * rs1, acc[a + 3] * rs1);
          r2 = pack_bf16(acc[a + 4] * rs0, acc[a + 5] * rs0);
          r3 = pack_bf16(acc[a + 6] * rs1, acc[a + 7] * rs1);
        }
        stmatrix_x4(base + (((hb * 4 + jj * 2 + (lane >> 4)) ^ (srow & 7)) << 4), r0, r1, r2, r3);
      }
    };
    auto q_head = [&](float (&acc)[32], int c, int slot, uint32_t b0, uint32_t b1, uint32_t b2, uint32_t b3, uint32_t z0, uint32_t z1) INL {
      const int a = c * 8;
      const uint32_t a0 = pack_bf16(phi_f(acc[a] * rs0), phi_f(acc[a + 1] * rs0));
      const uint32_t a1 = pack_bf16(phi_f(acc[a + 2] * rs1), phi_f(acc[a + 3] * rs1));
      const uint32_t a2 = pack_bf16(phi_f(acc[a + 4] * rs0), phi_f(acc[a + 5] * rs0));
      const uint32_t a3 = pack_bf16(phi_f(acc[a + 6] * rs1), phi_f(acc[a + 7] * rs1));
      float n0[4] = {0.f, 0.f, 0.f, 0.f}, n1[4] = {0.f, 0.f, 0.f, 0.f}, dn[4] = {0.f, 0.f, 0.f, 0.f};
      mma_16816(n0, a0, a1, a2, a3, b0, b1);
      mma_16816(n1, a0, a1, a2, a3, b2, b3);
      mma_16816(dn, a0, a1, a2, a3, z0, z1);
      const float i0 = __fdividef(1.f, dn[0] + 1e-6f), i1 = __fdividef(1.f, dn[2] + 1e-6f);
      const uint32_t tg = xoff & 1u;
      const uint32_t o0 = tagged(pack_bf16(n0[0] * i0, n0[1] * i0), tg), o1 = tagged(pack_bf16(n0[2] * i1, n0[3] * i1), tg);
      const uint32_t o2 = tagged(pack_bf16(n1[0] * i0, n1[1] * i0), tg), o3 = tagged(pack_bf16(n1[2] * i1, n1[3] * i1), tg);
      sts_u4(stash + slot * 8192 + c * 2048, o0, o1, o2, o3);
      stg_u4(xptr(slot, c), o0, o1, o2, o3);
    };
    const uint32_t kvb = area + 5 * 8192;
    const uint32_t kvfrag = kvb + ((lane & 7) + ((lane >> 3) & 1) * 8) * 32 + (lane >> 4) * 16;
    auto signal = [&](int e) INL {
      __syncwarp();
      if (lane == 0) mbar_arrive(BAR(B_EV + w * 2 + e));
    };

    auto pp_wait = [&]() INL { bar_sync(3 + w, 256); };
    auto pp_pass = [&]() INL { bar_arrive(3 + (w ^ 1), 256); };
    if (w == 1) pp_pass();
#pragma unroll 1
    for (int t = 0; t < 5; t++) {
      const uint32_t ph = t & 1;
      const int kind = odd ? (t < 2 ? K_KV : K_GU) : (t < 4 ? K_GU : K_Q);
      const int slot = odd ? t - 2 : t, xslot = odd ? t + 4 : t;
      static_for<2>([&](auto hc) INL {
        constexpr int hb = decltype(hc)::value;
        float acc[32];
        pp_wait();
        static_for<4>([&](auto kc) INL {
          constexpr int kq = decltype(kc)::value, k = hb * 4 + kq;
          mbar_wait(BAR(B_FULL + k), ph);
          wgmma_fence();
          static_for<8>([&](auto kkc) INL {
            constexpr int kk = decltype(kkc)::value, i = (kq * 8 + kk) * 4;
            wgmma_n64_rs<(kq | kk) != 0, desc_lo(stage_off(k) + kk * 1024, 8192), kHi64>(acc, A[i], A[i + 1], A[i + 2], A[i + 3], dbase);
          });
          wgmma_commit();
          if (kq == 2) pp_pass();
          if (kq > 0) {
            wgmma_wait<1>();
            release(k - 1);
          }
        });
        wgmma_wait<0>();
        release(hb * 4 + 3);
        if (kind == K_GU) {
          gu_chunk(acc, 0, slot, xslot, hb);
          gu_chunk(acc, 1, slot, xslot, hb);
        } else if (kind == K_KV) {
          if (hb == 0 && t == 0) sts_u4(stash + 5 * 8192, 0x3F803F80u, 0x3F803F80u, 0x3F803F80u, 0x3F803F80u);
          kv_stage(acc, 0, hb);
          kv_stage(acc, 1, hb);
          if (hb == 1) {
            float kvacc[36];
            const int par = (xoff & 1u) ^ 1u;
            fence_proxy_async();
            bar_sync(1 + w, 128);
            wgmma_fence();
            static_for<4>([&](auto kkc) INL {
              constexpr int kk = decltype(kkc)::value;
              wgmma_n72_ss_tt<kk != 0, desc_lo(3 * 8192 + kk * 2048, 0), desc_lo(4 * 8192 + kk * 2048, 8192 - kk * 2048)>(kvacc, dbase + w * 4096);
            });
            wgmma_commit();
            wgmma_wait<0>();
            float c[8];
#pragma unroll
            for (int i = 0; i < 8; i++)
              c[i] = wq == 0 ? kvacc[i] : (wq == 1 ? kvacc[8 + i] : (wq == 2 ? kvacc[16 + i] : kvacc[24 + i]));
            const int head = (2 * p + t) * 4 + wq;
            float* kvp = &g_kv[par][head][0][0];
            red_add_v2(kvp + g * 16 + 2 * tq, c[0], c[1]);
            red_add_v2(kvp + (g + 8) * 16 + 2 * tq, c[2], c[3]);
            red_add_v2(kvp + g * 16 + 8 + 2 * tq, c[4], c[5]);
            red_add_v2(kvp + (g + 8) * 16 + 8 + 2 * tq, c[6], c[7]);
            if (tq == 0) {
              red_add(&g_z[par][head][g], kvacc[32]);
              red_add(&g_z[par][head][g + 8], kvacc[34]);
            }
            signal(t);
          }
        } else {
          if (hb == 0) mbar_wait(BAR(B_KVREADY), 0);
          uint32_t Bf[4][6];
#pragma unroll
          for (int c = 0; c < 4; c++) {
            ldmatrix_x4_trans(kvfrag + (hb * 4 + c) * 512, Bf[c][0], Bf[c][1], Bf[c][2], Bf[c][3]);
            Bf[c][4] = lds_u32(kvb + 4096 + (hb * 4 + c) * 32 + tq * 4);
            Bf[c][5] = lds_u32(kvb + 4096 + (hb * 4 + c) * 32 + 16 + tq * 4);
          }
          if (hb == 1) bar_sync(1 + w, 128);
#pragma unroll
          for (int c = 0; c < 4; c++) q_head(acc, c, 4 + hb, Bf[c][0], Bf[c][1], Bf[c][2], Bf[c][3], Bf[c][4], Bf[c][5]);
        }
      });
      PROF(w, 1 + 2 * t);
    }
    PROF(w, 10);

    const int n_own = odd ? 3 : 6;
    auto load_a = [&](int kb) INL {
      if (kb < n_own) {
#pragma unroll
        for (int jj = 0; jj < 4; jj++) {
          const int i = (kb * 4 + jj) * 4;
          lds_u4(stash + kb * 8192 + jj * 2048, A[i], A[i + 1], A[i + 2], A[i + 3]);
        }
      } else {
        const int xs = odd ? kb - 3 : kb;
#pragma unroll
        for (int jj = 0; jj < 4; jj++) {
          const int i = (kb * 4 + jj) * 4;
          ldg_poll_u4(xptr(xs, jj), A[i], A[i + 1], A[i + 2], A[i + 3]);
        }
      }
    };
    auto fix_a = [&](int kb) INL {
      if (kb >= n_own) {
        const int xs = odd ? kb - 3 : kb;
        recv_group<4>(xptr(xs, 0), &A[kb * 16], xoff & 1u);
      }
    };
#pragma unroll
    for (int kb = 0; kb < 7; kb++) load_a(kb);
    PROF(w, 11);

    const int orow = m * 128 + w * 64 + wq * 16 + g;
    const int ocol = odd * 256 + p * 64 + 2 * tq;
    float acc2[2][32];
    uint32_t poff = (uint32_t)((m * 2 + odd) * 24 + w) * 8192u + (uint32_t)t128 * 16u;
    asm volatile("" : "+r"(poff));
    auto pptr = [&](int dest, int sl) INL { return (uint4*)((char*)g_pbuf + (poff + (uint32_t)(dest * 3 + sl) * 16384u)); };
    uint32_t P[3][16];
    uint32_t xr[16];
    auto send = [&](float (&acc)[32], int bi) INL {
      uint4* dst = pptr((p + 1 + bi) & 3, bi);
#pragma unroll
      for (int q = 0; q < 4; q++)
        stg_u4(dst + q * 128, tagged(pack_bf16(acc[q * 8], acc[q * 8 + 1]), xoff & 1u), tagged(pack_bf16(acc[q * 8 + 2], acc[q * 8 + 3]), xoff & 1u),
               tagged(pack_bf16(acc[q * 8 + 4], acc[q * 8 + 5]), xoff & 1u), tagged(pack_bf16(acc[q * 8 + 6], acc[q * 8 + 7]), xoff & 1u));
      PROF(w, 12 + 2 * bi);
    };
    auto fetch = [&](int sl) INL {
#pragma unroll
      for (int q = 0; q < 4; q++) ldg_poll_u4(pptr(p, sl) + q * 128, P[sl][q * 4], P[sl][q * 4 + 1], P[sl][q * 4 + 2], P[sl][q * 4 + 3]);
    };
    static_for<36>([&](auto ic) INL {
      constexpr int i = decltype(ic)::value, bi = p2_bi(i), kb = p2_kb(i), j = i >> 1, st = j & 7;
      if (i == 9) { load_a(7); load_a(8); }
      if (i == 14) PROF(w, 2);
      if (bi == 0 && kb >= 3) fix_a(kb);
      if (i == 15) PROF(w, 4);
      if (i == 7) PROF(w, 6);
      if (i == 0 || i == 7 || i == 14 || i == 18 || i == 27) pp_wait();
      if ((i & 1) == 0) mbar_wait(BAR(B_FULL + st), (5 + (j >> 3)) & 1);
      wgmma_fence();
      static_for<4>([&](auto kkc) INL {
        constexpr int kk = decltype(kkc)::value, a = (kb * 4 + kk) * 4;
        wgmma_n64_rs<(kb | kk) != 0, desc_lo(stage_off(st) + (i & 1) * 8192 + kk * 2048, 0), kHi128>(acc2[bi & 1], A[a], A[a + 1], A[a + 2], A[a + 3], dbase);
      });
      wgmma_commit();
      if (i == 4 || i == 11 || i == 15 || i == 24 || (i == 33 && w == 0)) pp_pass();
      if (i > 0) {
        wgmma_wait<1>();
        if ((i & 1) == 0 && j - 1 <= 9) release((j - 1) & 7);
      }
      if constexpr (i == 17) { send(acc2[0], 0); wgmma_wait<0>(); send(acc2[1], 1); }
      if constexpr (i == 26) { wgmma_wait<0>(); send(acc2[0], 2); }
      if constexpr (i == 29) fetch(0);
      if constexpr (i == 30) fetch(1);
      if constexpr (i == 28) {
#pragma unroll
        for (int q = 0; q < 8; q++) {
          xr[2 * q] = __ldg((const uint32_t*)(x + (size_t)orow * kD + ocol + q * 8));
          xr[2 * q + 1] = __ldg((const uint32_t*)(x + (size_t)(orow + 8) * kD + ocol + q * 8));
        }
      }
      if constexpr (i == 32) fetch(2);
    });
#pragma unroll
    for (int sl = 0; sl < 3; sl++) { PROF(w, 13 + 2 * sl); recv_group<4>(pptr(p, sl), &P[sl][0], xoff & 1u); }
    wgmma_wait<0>();
    PROF(w, 18);
#pragma unroll
    for (int q = 0; q < 8; q++) {
      float rr[4];
      rr[0] = acc2[1][q * 4 + 0] + __uint_as_float(xr[2 * q] << 16);
      rr[1] = acc2[1][q * 4 + 1] + __uint_as_float(xr[2 * q] & 0xffff0000u);
      rr[2] = acc2[1][q * 4 + 2] + __uint_as_float(xr[2 * q + 1] << 16);
      rr[3] = acc2[1][q * 4 + 3] + __uint_as_float(xr[2 * q + 1] & 0xffff0000u);
#pragma unroll
      for (int sl = 0; sl < 3; sl++) {
        rr[0] += __uint_as_float(P[sl][2 * q] << 16);
        rr[1] += __uint_as_float(P[sl][2 * q] & 0xffff0000u);
        rr[2] += __uint_as_float(P[sl][2 * q + 1] << 16);
        rr[3] += __uint_as_float(P[sl][2 * q + 1] & 0xffff0000u);
      }
      *(uint32_t*)(out + (size_t)orow * kD + ocol + q * 8) = pack_bf16(rr[0], rr[1]);
      *(uint32_t*)(out + (size_t)(orow + 8) * kD + ocol + q * 8) = pack_bf16(rr[2], rr[3]);
    }
    PROF(w, 19);
    if (tid == 0) {
      const uint32_t old = atomicAdd(&g_done, 1u);
      if ((old & 127u) == 127u) st_relaxed(&g_epoch, ld_relaxed(&g_epoch) + 1u);
    }
  }
#undef BAR
}

typedef CUresult (*EncodeFn)(CUtensorMap*, CUtensorMapDataType, cuuint32_t, void*, const cuuint64_t*, const cuuint64_t*,
                             const cuuint32_t*, const cuuint32_t*, CUtensorMapInterleave, CUtensorMapSwizzle,
                             CUtensorMapL2promotion, CUtensorMapFloatOOBfill);

void make_map(EncodeFn enc, CUtensorMap* tm, const void* ptr, int rows, int cols, bool narrow) {
  cuuint64_t gd[2] = {(cuuint64_t)cols, (cuuint64_t)rows};
  cuuint64_t gs[1] = {(cuuint64_t)cols * 2};
  cuuint32_t bd[2] = {narrow ? 32u : 64u, narrow ? 128u : 64u};
  cuuint32_t es[2] = {1, 1};
  enc(tm, CU_TENSOR_MAP_DATA_TYPE_BFLOAT16, 2, const_cast<void*>(ptr), gd, gs, bd, es, CU_TENSOR_MAP_INTERLEAVE_NONE,
      narrow ? CU_TENSOR_MAP_SWIZZLE_64B : CU_TENSOR_MAP_SWIZZLE_128B, CU_TENSOR_MAP_L2_PROMOTION_L2_256B, CU_TENSOR_MAP_FLOAT_OOB_FILL_NONE);
}

}

extern "C" void kernel_launch(void* const* d_in, const int* in_sizes, int n_in, void* d_out, int out_size) {
  static EncodeFn enc = nullptr;
  if (!enc) {
    void* fn = nullptr;
    cudaDriverEntryPointQueryResult qr;
    cudaGetDriverEntryPoint("cuTensorMapEncodeTiled", &fn, cudaEnableDefault, &qr);
    enc = (EncodeFn)fn;
    cudaFuncSetAttribute(fused_kernel, cudaFuncAttributeMaxDynamicSharedMemorySize, kSmemBytes);
  }
  CUtensorMap tm_x, tm_wqkv, tm_w1, tm_w3, tm_w2, tm_wo;
  make_map(enc, &tm_x, d_in[0], kS, kD, false);
  make_map(enc, &tm_wqkv, d_in[1], kD, 3 * kD, true);
  make_map(enc, &tm_wo, d_in[2], kD, kD, false);
  make_map(enc, &tm_w1, d_in[4], kD, kF, true);
  make_map(enc, &tm_w3, d_in[5], kD, kF, true);
  make_map(enc, &tm_w2, d_in[6], kF, kD, false);
  fused_kernel<<<128, 384, kSmemBytes>>>(tm_x, tm_wqkv, tm_w1, tm_w3, tm_w2, tm_wo, (const __nv_bfloat16*)d_in[0],
                                         (__nv_bfloat16*)d_out);
}
```

```cpp
#include <cuda_runtime.h>
#include <cuda_bf16.h>
#include <cuda.h>
#include <stdint.h>

extern __shared__ __align__(1024) uint8_t smem_raw[];

namespace {

constexpr int kS = 2048, kD = 512, kF = 1792;
constexpr uint32_t kSpinLimit = 1u << 22;

__device__ uint4    g_xbuf[16][4][9][2][4][128];
__device__ uint4    g_pbuf[16][2][4][3][2][4][128];
__device__ float    g_kv[2][32][16][16];
__device__ float    g_z[2][32][16];
__device__ uint32_t g_kvcnt[4][32];
__device__ uint32_t g_epoch;
__device__ uint32_t g_done;
#define PROF(wg, i) do {} while (0)
#define TWAIT(acc, stmt) do { stmt; } while (0)

__device__ __forceinline__ uint32_t smem_u32(const void* p) { return (uint32_t)__cvta_generic_to_shared(p); }
__device__ __forceinline__ void mbar_init(uint32_t bar, uint32_t cnt) {
  asm volatile("mbarrier.init.shared::cta.b64 [%0], %1;" ::"r"(bar), "r"(cnt) : "memory");
}
__device__ __forceinline__ void mbar_expect_tx(uint32_t bar, uint32_t bytes) {
  asm volatile("mbarrier.arrive.expect_tx.shared::cta.b64 _, [%0], %1;" ::"r"(bar), "r"(bytes) : "memory");
}
__device__ __forceinline__ void mbar_arrive(uint32_t bar) {
  asm volatile("mbarrier.arrive.shared::cta.b64 _, [%0];" ::"r"(bar) : "memory");
}
__device__ __forceinline__ void mbar_wait(uint32_t bar, uint32_t parity) {
  asm volatile(
      "{\n.reg .pred p;\n"
      "LAB_WAIT:\n"
      "mbarrier.try_wait.parity.shared::cta.b64 p, [%0], %1;\n"
      "@p bra DONE;\n"
      "bra LAB_WAIT;\n"
      "DONE:\n}" ::"r"(bar), "r"(parity) : "memory");
}
__device__ __forceinline__ void tma_load_2d(uint32_t dst, const CUtensorMap* tm, uint32_t bar, int c0, int c1) {
  asm volatile(
      "cp.async.bulk.tensor.2d.shared::cluster.global.mbarrier::complete_tx::bytes [%0], [%1, {%3, %4}], [%2];" ::"r"(dst),
      "l"(tm), "r"(bar), "r"(c0), "r"(c1)
      : "memory");
}
__device__ __forceinline__ void tma_load_2d_mc(uint32_t dst, const CUtensorMap* tm, uint32_t bar, int c0, int c1) {
  asm volatile(
      "cp.async.bulk.tensor.2d.shared::cluster.global.mbarrier::complete_tx::bytes.multicast::cluster [%0], [%1, {%3, %4}], [%2], %5;" ::"r"(dst),
      "l"(tm), "r"(bar), "r"(c0), "r"(c1), "h"((uint16_t)3)
      : "memory");
}
__device__ __forceinline__ void mbar_arrive_cluster(uint32_t bar, uint32_t cta) {
  asm volatile("{\n.reg .b32 ra;\nmapa.shared::cluster.u32 ra, %0, %1;\nmbarrier.arrive.shared::cluster.b64 _, [ra];\n}" ::"r"(bar), "r"(cta) : "memory");
}
__device__ __forceinline__ void prefetch_tmap(const CUtensorMap* tm) {
  asm volatile("prefetch.tensormap [%0];" ::"l"(tm) : "memory");
}
__device__ __forceinline__ void wgmma_fence() { asm volatile("wgmma.fence.sync.aligned;" ::: "memory"); }
__device__ __forceinline__ void wgmma_commit() { asm volatile("wgmma.commit_group.sync.aligned;" ::: "memory"); }
template <int N>
__device__ __forceinline__ void wgmma_wait() { asm volatile("wgmma.wait_group.sync.aligned %0;" ::"n"(N) : "memory"); }
__device__ __forceinline__ void bar_sync(int id, int n) { asm volatile("bar.sync %0, %1;" ::"r"(id), "r"(n) : "memory"); }
__device__ __forceinline__ void bar_arrive(int id, int n) { asm volatile("bar.arrive %0, %1;" ::"r"(id), "r"(n) : "memory"); }
__device__ __forceinline__ void fence_proxy_async() { asm volatile("fence.proxy.async.shared::cta;" ::: "memory"); }

__device__ __forceinline__ uint32_t ld_acquire(const uint32_t* p) {
  uint32_t v;
  asm volatile("ld.acquire.gpu.global.u32 %0, [%1];" : "=r"(v) : "l"(p) : "memory");
  return v;
}
__device__ __forceinline__ uint32_t ld_relaxed(const uint32_t* p) {
  uint32_t v;
  asm volatile("ld.relaxed.gpu.global.u32 %0, [%1];" : "=r"(v) : "l"(p));
  return v;
}
__device__ __forceinline__ void cluster_wait() { asm volatile("barrier.cluster.wait.aligned;" ::: "memory"); }
__device__ __forceinline__ void st_relaxed(uint32_t* p, uint32_t v) {
  asm volatile("st.relaxed.gpu.global.u32 [%0], %1;" ::"l"(p), "r"(v) : "memory");
}
__device__ __forceinline__ void wait_flag_eq(const uint32_t* p, uint32_t val) {
  uint32_t it = 0;
  while (ld_acquire(p) != val) {
    if (++it > kSpinLimit) break;
  }
}
__device__ __forceinline__ void wait_count_ge(const uint32_t* p, uint32_t val) {
  uint32_t it = 0;
  while ((int32_t)(ld_acquire(p) - val) < 0) {
    __nanosleep(64);
    if (++it > kSpinLimit) break;
  }
}
__device__ __forceinline__ void ldg_poll_u4(const void* p, uint32_t& a, uint32_t& b, uint32_t& c, uint32_t& d) {
  asm volatile("ld.relaxed.gpu.global.v4.u32 {%0,%1,%2,%3}, [%4];" : "=r"(a), "=r"(b), "=r"(c), "=r"(d) : "l"(p) : "memory");
}
template <int N>
__device__ __forceinline__ void recv_group(const uint4* p, uint32_t* r, uint32_t tag) {
  uint32_t it = 0;
  while (true) {
    uint32_t bad = 0u;
#pragma unroll
    for (int i = 0; i < 4 * N; i++) bad |= r[i] ^ tag;
    if (!__any_sync(0xffffffffu, (bad & 1u) != 0u) || ++it > kSpinLimit) break;
#pragma unroll
    for (int q = 0; q < N; q++) ldg_poll_u4(p + q * 128, r[q * 4], r[q * 4 + 1], r[q * 4 + 2], r[q * 4 + 3]);
  }
}
__device__ __forceinline__ uint32_t tagged(uint32_t v, uint32_t tag) { return (v & ~1u) | tag; }
__device__ __forceinline__ float4 ldg_cg_f4(const void* p) {
  float4 v;
  asm volatile("ld.global.cg.v4.f32 {%0,%1,%2,%3}, [%4];" : "=f"(v.x), "=f"(v.y), "=f"(v.z), "=f"(v.w) : "l"(p) : "memory");
  return v;
}
__device__ __forceinline__ void stg_u4(void* p, uint32_t a, uint32_t b, uint32_t c, uint32_t d) {
  asm volatile("st.global.v4.u32 [%0], {%1,%2,%3,%4};" ::"l"(p), "r"(a), "r"(b), "r"(c), "r"(d) : "memory");
}
__device__ __forceinline__ void stg_f4(void* p, float a, float b, float c, float d) {
  asm volatile("st.global.v4.f32 [%0], {%1,%2,%3,%4};" ::"l"(p), "f"(a), "f"(b), "f"(c), "f"(d) : "memory");
}
__device__ __forceinline__ void sts_u4(uint32_t addr, uint32_t a, uint32_t b, uint32_t c, uint32_t d) {
  asm volatile("st.shared.v4.u32 [%0], {%1,%2,%3,%4};" ::"r"(addr), "r"(a), "r"(b), "r"(c), "r"(d) : "memory");
}
__device__ __forceinline__ void lds_u4(uint32_t addr, uint32_t& a, uint32_t& b, uint32_t& c, uint32_t& d) {
  asm volatile("ld.shared.v4.u32 {%0,%1,%2,%3}, [%4];" : "=r"(a), "=r"(b), "=r"(c), "=r"(d) : "r"(addr) : "memory");
}
__device__ __forceinline__ uint32_t lds_u32(uint32_t addr) {
  uint32_t v;
  asm volatile("ld.shared.u32 %0, [%1];" : "=r"(v) : "r"(addr) : "memory");
  return v;
}
__device__ __forceinline__ void ldmatrix_x4(uint32_t addr, uint32_t& a, uint32_t& b, uint32_t& c, uint32_t& d) {
  asm volatile("ldmatrix.sync.aligned.m8n8.x4.shared.b16 {%0,%1,%2,%3}, [%4];" : "=r"(a), "=r"(b), "=r"(c), "=r"(d) : "r"(addr) : "memory");
}
__device__ __forceinline__ void ldmatrix_x4_trans(uint32_t addr, uint32_t& a, uint32_t& b, uint32_t& c, uint32_t& d) {
  asm volatile("ldmatrix.sync.aligned.m8n8.x4.trans.shared.b16 {%0,%1,%2,%3}, [%4];" : "=r"(a), "=r"(b), "=r"(c), "=r"(d) : "r"(addr) : "memory");
}
__device__ __forceinline__ void stmatrix_x4(uint32_t addr, uint32_t a, uint32_t b, uint32_t c, uint32_t d) {
  asm volatile("stmatrix.sync.aligned.m8n8.x4.shared.b16 [%0], {%1,%2,%3,%4};" ::"r"(addr), "r"(a), "r"(b), "r"(c), "r"(d) : "memory");
}
__device__ __forceinline__ void mma_16816(float (&c)[4], uint32_t a0, uint32_t a1, uint32_t a2, uint32_t a3, uint32_t b0, uint32_t b1) {
  asm(
      "mma.sync.aligned.m16n8k16.row.col.f32.bf16.bf16.f32 {%0,%1,%2,%3}, {%4,%5,%6,%7}, {%8,%9}, {%0,%1,%2,%3};"
      : "+f"(c[0]), "+f"(c[1]), "+f"(c[2]), "+f"(c[3])
      : "r"(a0), "r"(a1), "r"(a2), "r"(a3), "r"(b0), "r"(b1));
}
__device__ __forceinline__ uint32_t pack_bf16(float lo, float hi) {
  uint32_t r;
  asm("cvt.rn.bf16x2.f32 %0, %1, %2;" : "=r"(r) : "f"(hi), "f"(lo));
  return r;
}
__device__ __forceinline__ uint32_t hsub2_bf16(uint32_t a, uint32_t b) {
  uint32_t r;
  asm("sub.rn.bf16x2 %0, %1, %2;" : "=r"(r) : "r"(a), "r"(b));
  return r;
}
__device__ __forceinline__ float ex2f(float x) {
  float r;
  asm("ex2.approx.ftz.f32 %0, %1;" : "=f"(r) : "f"(x));
  return r;
}
__device__ __forceinline__ float rcpf(float x) {
  float r;
  asm("rcp.approx.ftz.f32 %0, %1;" : "=f"(r) : "f"(x));
  return r;
}
__device__ __forceinline__ void red_add_v2(float* p, float a, float b) {
  asm volatile("red.relaxed.gpu.global.add.v2.f32 [%0], {%1,%2};" ::"l"(p), "f"(a), "f"(b) : "memory");
}
__device__ __forceinline__ void red_add(float* p, float a) {
  asm volatile("red.relaxed.gpu.global.add.f32 [%0], %1;" ::"l"(p), "f"(a) : "memory");
}
__device__ __forceinline__ float phi_f(float t) {
  float e = ex2f(t * 1.4426950408889634f);
  return (t > 0.f ? t + 1.f : e) + 1e-6f;
}

#define R8(a, o) "+f"(a[o + 0]), "+f"(a[o + 1]), "+f"(a[o + 2]), "+f"(a[o + 3]), "+f"(a[o + 4]), "+f"(a[o + 5]), "+f"(a[o + 6]), "+f"(a[o + 7])

#define W8(a, o) "=f"(a[o + 0]), "=f"(a[o + 1]), "=f"(a[o + 2]), "=f"(a[o + 3]), "=f"(a[o + 4]), "=f"(a[o + 5]), "=f"(a[o + 6]), "=f"(a[o + 7])
#define D32 "{%0,%1,%2,%3,%4,%5,%6,%7,%8,%9,%10,%11,%12,%13,%14,%15,%16,%17,%18,%19,%20,%21,%22,%23,%24,%25,%26,%27,%28,%29,%30,%31}"
#define D36 "{%0,%1,%2,%3,%4,%5,%6,%7,%8,%9,%10,%11,%12,%13,%14,%15,%16,%17,%18,%19,%20,%21,%22,%23,%24,%25,%26,%27,%28,%29,%30,%31,%32,%33,%34,%35}"

constexpr uint32_t kHi128 = (1024u >> 4) | (1u << 30);
constexpr uint32_t kHi64 = (512u >> 4) | (2u << 30);
__host__ __device__ constexpr uint32_t desc_lo(uint32_t off, uint32_t lbo) { return (off >> 4) | ((lbo >> 4) << 16); }

template <bool ACC, uint32_t LO, uint32_t HI>
__device__ __forceinline__ void wgmma_n64_rs(float (&d)[32], uint32_t a0, uint32_t a1, uint32_t a2, uint32_t a3) {
  if (ACC) {
    asm volatile(
        "{\n.reg .pred p;\n.reg .b32 lo;\n.reg .b64 dd;\nsetp.eq.b32 p, 0, 0;\nmov.u32 lo, 64;\nadd.u32 lo, lo, %36;\nmov.b64 dd, {lo, %37};\n"
        "wgmma.mma_async.sync.aligned.m64n64k16.f32.bf16.bf16 " D32 ", {%32,%33,%34,%35}, dd, p, 1, 1, 1;\n}"
        : R8(d, 0), R8(d, 8), R8(d, 16), R8(d, 24)
        : "r"(a0), "r"(a1), "r"(a2), "r"(a3), "n"(LO), "n"(HI));
  } else {
    asm volatile(
        "{\n.reg .pred p;\n.reg .b32 lo;\n.reg .b64 dd;\nsetp.ne.b32 p, 0, 0;\nmov.u32 lo, 64;\nadd.u32 lo, lo, %36;\nmov.b64 dd, {lo, %37};\n"
        "wgmma.mma_async.sync.aligned.m64n64k16.f32.bf16.bf16 " D32 ", {%32,%33,%34,%35}, dd, p, 1, 1, 1;\n}"
        : W8(d, 0), W8(d, 8), W8(d, 16), W8(d, 24)
        : "r"(a0), "r"(a1), "r"(a2), "r"(a3), "n"(LO), "n"(HI));
  }
}
template <bool ACC, uint32_t LOA, uint32_t LOB>
__device__ __forceinline__ void wgmma_n72_ss_tt(float (&d)[36], uint32_t base) {
  if (ACC) {
    asm volatile(
        "{\n.reg .pred p;\n.reg .b32 lo;\n.reg .b64 da, db;\nsetp.eq.b32 p, 0, 0;\n"
        "add.u32 lo, %36, %37;\nmov.b64 da, {lo, %39};\nadd.u32 lo, %36, %38;\nmov.b64 db, {lo, %39};\n"
        "wgmma.mma_async.sync.aligned.m64n72k16.f32.bf16.bf16 " D36 ", da, db, p, 1, 1, 1, 1;\n}"
        : R8(d, 0), R8(d, 8), R8(d, 16), R8(d, 24), "+f"(d[32]), "+f"(d[33]), "+f"(d[34]), "+f"(d[35])
        : "r"(base), "n"(LOA), "n"(LOB), "n"(kHi128));
  } else {
    asm volatile(
        "{\n.reg .pred p;\n.reg .b32 lo;\n.reg .b64 da, db;\nsetp.ne.b32 p, 0, 0;\n"
        "add.u32 lo, %36, %37;\nmov.b64 da, {lo, %39};\nadd.u32 lo, %36, %38;\nmov.b64 db, {lo, %39};\n"
        "wgmma.mma_async.sync.aligned.m64n72k16.f32.bf16.bf16 " D36 ", da, db, p, 1, 1, 1, 1;\n}"
        : W8(d, 0), W8(d, 8), W8(d, 16), W8(d, 24), "=f"(d[32]), "=f"(d[33]), "=f"(d[34]), "=f"(d[35])
        : "r"(base), "n"(LOA), "n"(LOB), "n"(kHi128));
  }
}

#define INL __attribute__((always_inline))
template <int V> struct IC { static constexpr int value = V; };
template <int N, int I = 0, typename F>
__device__ __forceinline__ void static_for(F&& f) {
  if constexpr (I < N) { f(IC<I>{}); static_for<N, I + 1>(f); }
}

__host__ __device__ constexpr uint32_t stage_off(int st) {
  return st < 6 ? 131072u + (uint32_t)st * 16384u : (uint32_t)(st - 6) * 65536u + 49152u;
}

constexpr int B_FULL = 0, B_EMPTY = 8, B_XFULL = 16, B_XDONE = 32, B_KVREADY = 33, B_EV = 34, B_COUNT = 38;
constexpr uint32_t kBarOff = 229376;
constexpr int kSmemBytes = 229376 + 1024;

__host__ __device__ constexpr int p2_bi(int i) { return i < 7 ? 0 : i < 14 ? 1 : i < 16 ? 0 : i < 18 ? 1 : i / 9; }
__host__ __device__ constexpr int p2_kb(int i) { return i < 7 ? i : i < 14 ? i - 7 : i < 16 ? i - 7 : i < 18 ? i - 9 : i % 9; }

enum { K_NONE = 0, K_GU = 1, K_KV = 2, K_Q = 3 };

__global__ void __cluster_dims__(2, 1, 1) __launch_bounds__(384, 1)
fused_kernel(const __grid_constant__ CUtensorMap tm_x, const __grid_constant__ CUtensorMap tm_wqkv,
             const __grid_constant__ CUtensorMap tm_w1, const __grid_constant__ CUtensorMap tm_w3,
             const __grid_constant__ CUtensorMap tm_w2, const __grid_constant__ CUtensorMap tm_wo,
             const __nv_bfloat16* __restrict__ x, __nv_bfloat16* __restrict__ out) {
  const uint32_t sbase = smem_u32(smem_raw);
  const uint32_t bars = sbase + kBarOff;
  const int tid = threadIdx.x, lane = tid & 31;
  const int warp = __shfl_sync(0xffffffffu, tid >> 5, 0);
  const int cr = blockIdx.x & 1;
  const int r = (blockIdx.x >> 1) & 7, m = ((blockIdx.x >> 4) << 1) | cr, p = r >> 1, odd = r & 1;
#define BAR(i) (bars + 8u * (uint32_t)(i))
  if (tid == 256) {
    if ((sbase & 0x3FFFFu) != 1024u) __trap();
#pragma unroll
    for (int i = 0; i < 16; i++) mbar_init(BAR(B_XFULL + i), 1);
    fence_proxy_async();
#pragma unroll
    for (int b = 0; b < 16; b++) {
      mbar_expect_tx(BAR(B_XFULL + b), 8192);
      tma_load_2d(sbase + (b >> 3) * 65536 + (b & 7) * 8192, &tm_x, BAR(B_XFULL + b), (b & 7) * 64, m * 128 + (b >> 3) * 64);
    }
#pragma unroll
    for (int i = 0; i < 8; i++) { mbar_init(BAR(B_FULL + i), 1); mbar_init(BAR(B_EMPTY + i), 4); }
#pragma unroll
    for (int i = 0; i < 4; i++) mbar_init(BAR(B_EV + i), 4);
    mbar_init(BAR(B_XDONE), 2);
    mbar_init(BAR(B_KVREADY), 1);
    asm volatile("fence.mbarrier_init.release.cluster;" ::: "memory");
    fence_proxy_async();
  } else if (tid == 288) {
    prefetch_tmap(odd ? &tm_wqkv : (cr ? &tm_w3 : &tm_w1));
  }
  __syncwarp();
  asm volatile("barrier.cluster.arrive.relaxed.aligned;" ::: "memory");
  PROF((tid >> 7), 21);
  __syncthreads();

  if (warp >= 8) {
    asm volatile("setmaxnreg.dec.sync.aligned.u32 24;");
    PROF(2, 3);
    cluster_wait();
    PROF(2, 2);
    const uint32_t epoch = warp == 8 ? 0u : ld_relaxed(&g_epoch);
    const uint32_t tag = epoch + 1u;
    const int par = epoch & 1;
    if (warp == 8) {
      if (lane == 0) {
        int twp = 0;
        for (int j = 0; j < 10; j++) {
          const CUtensorMap* tm;
          int col;
          if (!odd) {
            if (j < 8) { tm = cr ? &tm_w3 : &tm_w1; col = 7 * p * 64 + j * 32; }
            else { tm = &tm_wqkv; col = 128 * p + (j - 8) * 64 + cr * 32; }
          } else {
            if (j < 4) { tm = &tm_wqkv; col = 512 + cr * 512 + 128 * p + j * 32; }
            else { tm = cr ? &tm_w3 : &tm_w1; col = (7 * p + 4) * 64 + (j - 4) * 32; }
          }
          const int t = j >> 1;
          for (int kq = 0; kq < 4; kq++) {
            const int k = (j & 1) * 4 + kq;
            TWAIT(twp, mbar_wait(BAR(B_EMPTY + k), k < 6 ? ((t & 1) ^ 1) : (t & 1)));
            mbar_expect_tx(BAR(B_FULL + k), 16384);
            tma_load_2d_mc(sbase + stage_off(k) + cr * 8192, tm, BAR(B_FULL + k), col, kq * 128);
          }
        }
        for (int j = 0; j < 18; j++) {
          const int st = j & 7, n = 5 + (j >> 3);
          const int i = 2 * j + cr;
          const int bi = p2_bi(i), kb = p2_kb(i);
          const int col = odd * 256 + ((p + 1 + bi) & 3) * 64;
          const CUtensorMap* tmk;
          int row;
          if (!odd) {
            if (kb < 4) { tmk = &tm_w2; row = (7 * p + kb) * 64; }
            else if (kb < 6) { tmk = &tm_wo; row = (2 * p + kb - 4) * 64; }
            else { tmk = &tm_w2; row = (7 * p + 4 + kb - 6) * 64; }
          } else {
            if (kb < 3) { tmk = &tm_w2; row = (7 * p + 4 + kb) * 64; }
            else if (kb < 7) { tmk = &tm_w2; row = (7 * p + kb - 3) * 64; }
            else { tmk = &tm_wo; row = (2 * p + kb - 7) * 64; }
          }
          mbar_wait(BAR(B_EMPTY + st), st < 6 ? ((n & 1) ^ 1) : (n & 1));
          mbar_expect_tx(BAR(B_FULL + st), 16384);
          tma_load_2d_mc(sbase + stage_off(st) + cr * 8192, tmk, BAR(B_FULL + st), col, row);
        }
      }
    } else if (warp <= 10) {
      if (lane == 0 && odd) {
        const int w = warp - 9;
        for (int e = 0; e < 2; e++) {
          mbar_wait(BAR(B_EV + w * 2 + e), 0);
          __threadfence();
          atomicAdd(&g_kvcnt[p][0], 1u);
        }
      }
    } else {
      if (!odd) {
        {
          const int ce = m * 4 + p;
          float* kvn = &g_kv[par ^ 1][0][0][0];
          for (int i = lane; i < 128; i += 32) kvn[ce * 128 + i] = 0.f;
          if (lane < 8) (&g_z[par ^ 1][0][0])[ce * 8 + lane] = 0.f;
        }
        mbar_wait(BAR(B_XDONE), 0);
        wait_count_ge(&g_kvcnt[p][0], 64u * tag);
        const float* kvp = &g_kv[par][8 * p][0][0];
        const uint32_t dst0 = sbase + 5 * 8192, dst1 = dst0 + 65536;
#pragma unroll 4
        for (int i = 0; i < 16; i++) {
          float4 v = ldg_cg_f4(kvp + (i * 32 + lane) * 4);
          uint32_t lo = pack_bf16(v.x, v.y), hi = pack_bf16(v.z, v.w);
          uint32_t off = (uint32_t)(i * 32 + lane) * 8u;
          asm volatile("st.shared.v2.u32 [%0], {%1,%2};" ::"r"(dst0 + off), "r"(lo), "r"(hi) : "memory");
          asm volatile("st.shared.v2.u32 [%0], {%1,%2};" ::"r"(dst1 + off), "r"(lo), "r"(hi) : "memory");
        }
        {
          float4 v = ldg_cg_f4(&g_z[par][8 * p][0] + lane * 4);
          uint32_t lo = pack_bf16(v.x, v.y), hi = pack_bf16(v.z, v.w);
          uint32_t off = 4096u + (uint32_t)lane * 8u;
          asm volatile("st.shared.v2.u32 [%0], {%1,%2};" ::"r"(dst0 + off), "r"(lo), "r"(hi) : "memory");
          asm volatile("st.shared.v2.u32 [%0], {%1,%2};" ::"r"(dst1 + off), "r"(lo), "r"(hi) : "memory");
        }
        __syncwarp();
        if (lane == 0) mbar_arrive(BAR(B_KVREADY));
      }
    }
  } else {
    asm volatile("setmaxnreg.inc.sync.aligned.u32 240;");
    const int w = warp >> 2, wq = warp & 3, t128 = tid & 127;
    const int g = lane >> 2, tq = lane & 3;
    const uint32_t area = sbase + (uint32_t)w * 65536u;
    const bool elect = (t128 == 0);
    PROF(w, 22);
    const uint32_t dbase = (sbase & 0x3FFFFu) >> 4;
    uint32_t xoff = (uint32_t)((m * 4 + p) * 18 + w) * 8192u + (uint32_t)t128 * 16u;
    uint32_t stash = area + (uint32_t)t128 * 16u;
    const uint32_t epoch_c = ld_relaxed(&g_epoch);
    auto xptr = [&](int slot, int jj) INL { return (uint4*)((char*)g_xbuf + ((xoff & ~1u) + (uint32_t)slot * 16384u + (uint32_t)jj * 2048u)); };
    uint32_t A[144];
    float rs0, rs1;
    auto release = [&](int st) INL {
      if (elect) { mbar_arrive_cluster(BAR(B_EMPTY + st), 0); mbar_arrive_cluster(BAR(B_EMPTY + st), 1); }
    };

    {
      const int row = wq * 16 + (lane & 7) + ((lane >> 3) & 1) * 8;
      const uint32_t rbase = area + row * 128;
      float s0[2][4] = {}, q0[2][4] = {}, q1[2][4] = {};
      const uint32_t ones = 0x3F803F80u;
#pragma unroll
      for (int b = 0; b < 8; b++) {
        mbar_wait(BAR(B_XFULL + w * 8 + b), 0);
        if (b == 0) PROF(w, 23);
        if (b == 7) PROF(w, 24);
#pragma unroll
        for (int kk = 0; kk < 4; kk++) {
          const int i = (b * 4 + kk) * 4;
          ldmatrix_x4(rbase + b * 8192 + (((kk * 2 + (lane >> 4)) ^ (row & 7)) << 4), A[i], A[i + 1], A[i + 2], A[i + 3]);
        }
#pragma unroll
        for (int kk = 0; kk < 4; kk++) {
          const int i = (b * 4 + kk) * 4;
          mma_16816(s0[kk & 1], A[i], A[i + 1], A[i + 2], A[i + 3], ones, ones);
          mma_16816(q0[kk & 1], A[i], A[i + 1], A[i + 2], A[i + 3], A[i], A[i + 2]);
          mma_16816(q1[kk & 1], A[i], A[i + 1], A[i + 2], A[i + 3], A[i + 1], A[i + 3]);
        }
      }
      const float mean0 = (s0[0][0] + s0[1][0]) * (1.f / 512.f), mean1 = (s0[0][2] + s0[1][2]) * (1.f / 512.f);
      const uint32_t m0 = pack_bf16(mean0, mean0), m1 = pack_bf16(mean1, mean1);
#pragma unroll
      for (int i = 0; i < 128; i += 2) {
        A[i] = hsub2_bf16(A[i], m0);
        A[i + 1] = hsub2_bf16(A[i + 1], m1);
      }
      float v0 = (g & 1) ? q0[0][1] + q0[1][1] : q0[0][0] + q0[1][0];
      float v1 = (g & 1) ? q1[0][3] + q1[1][3] : q1[0][2] + q1[1][2];
      const int src = 4 * g + (g >> 1);
      v0 = __shfl_sync(0xffffffffu, v0, src);
      v1 = __shfl_sync(0xffffffffu, v1, src);
      v0 = fmaxf(v0 * (1.f / 512.f) - mean0 * mean0, 0.f);
      v1 = fmaxf(v1 * (1.f / 512.f) - mean1 * mean1, 0.f);
      rs0 = rsqrtf(v0 + 1e-5f);
      rs1 = rsqrtf(v1 + 1e-5f);
      bar_sync(1 + w, 128);
      cluster_wait();
      xoff |= (epoch_c & 1u) ^ 1u;
      asm volatile("" : "+r"(xoff), "+r"(stash));
      PROF(w, 0);
      release(6); release(7);
      if (elect) mbar_arrive(BAR(B_XDONE));
    }

    auto gu_chunk = [&](float (&acc)[32], int f, int slot, int xslot, int hb) INL {
      const float c0 = rs0 * -1.4426950408889634f, c1 = rs1 * -1.4426950408889634f;
      const float q0 = rs0 * rs0, q1 = rs1 * rs1;
      uint32_t h[4];
#pragma unroll
      for (int i = 0; i < 4; i++) {
        const float ga = acc[f * 8 + 2 * i], gb = acc[f * 8 + 2 * i + 1];
        const float ua = acc[16 + f * 8 + 2 * i], ub = acc[16 + f * 8 + 2 * i + 1];
        const float c = (i & 1) ? c1 : c0, q = (i & 1) ? q1 : q0;
        const float da = 1.f + ex2f(fminf(ga * c, 60.f)), db = 1.f + ex2f(fminf(gb * c, 60.f));
        const float rq = rcpf(da * db) * q;
        h[i] = tagged(pack_bf16(ga * ua * (db * rq), gb * ub * (da * rq)), xoff & 1u);
      }
      const int jj = hb * 2 + f;
      sts_u4(stash + slot * 8192 + jj * 2048, h[0], h[1], h[2], h[3]);
      stg_u4(xptr(xslot, jj), h[0], h[1], h[2], h[3]);
    };
    auto kv_stage = [&](float (&acc)[32], int c, int hb) INL {
      const int srow = wq * 16 + (lane & 7) + ((lane >> 3) & 1) * 8;
      const uint32_t base = area + (3 + c) * 8192 + srow * 128;
#pragma unroll
      for (int jj = 0; jj < 2; jj++) {
        const int a = c * 16 + jj * 8;
        uint32_t r0, r1, r2, r3;
        if (c == 0) {
          r0 = pack_bf16(phi_f(acc[a] * rs0), phi_f(acc[a + 1] * rs0));
          r1 = pack_bf16(phi_f(acc[a + 2] * rs1), phi_f(acc[a + 3] * rs1));
          r2 = pack_bf16(phi_f(acc[a + 4] * rs0), phi_f(acc[a + 5] * rs0));
          r3 = pack_bf16(phi_f(acc[a + 6] * rs1), phi_f(acc[a + 7] * rs1));
        } else {
          r0 = pack_bf16(acc[a] * rs0, acc[a + 1] * rs0);
          r1 = pack_bf16(acc[a + 2] * rs1, acc[a + 3] * rs1);
          r2 = pack_bf16(acc[a + 4] * rs0, acc[a + 5] * rs0);
          r3 = pack_bf16(acc[a + 6] * rs1, acc[a + 7] * rs1);
        }
        stmatrix_x4(base + (((hb * 4 + jj * 2 + (lane >> 4)) ^ (srow & 7)) << 4), r0, r1, r2, r3);
      }
    };
    auto q_head = [&](float (&acc)[32], int c, int slot, uint32_t b0, uint32_t b1, uint32_t b2, uint32_t b3, uint32_t z0, uint32_t z1) INL {
      const int a = c * 8;
      const uint32_t a0 = pack_bf16(phi_f(acc[a] * rs0), phi_f(acc[a + 1] * rs0));
      const uint32_t a1 = pack_bf16(phi_f(acc[a + 2] * rs1), phi_f(acc[a + 3] * rs1));
      const uint32_t a2 = pack_bf16(phi_f(acc[a + 4] * rs0), phi_f(acc[a + 5] * rs0));
      const uint32_t a3 = pack_bf16(phi_f(acc[a + 6] * rs1), phi_f(acc[a + 7] * rs1));
      float n0[4] = {0.f, 0.f, 0.f, 0.f}, n1[4] = {0.f, 0.f, 0.f, 0.f}, dn[4] = {0.f, 0.f, 0.f, 0.f};
      mma_16816(n0, a0, a1, a2, a3, b0, b1);
      mma_16816(n1, a0, a1, a2, a3, b2, b3);
      mma_16816(dn, a0, a1, a2, a3, z0, z1);
      const float i0 = __fdividef(1.f, dn[0] + 1e-6f), i1 = __fdividef(1.f, dn[2] + 1e-6f);
      const uint32_t tg = xoff & 1u;
      const uint32_t o0 = tagged(pack_bf16(n0[0] * i0, n0[1] * i0), tg), o1 = tagged(pack_bf16(n0[2] * i1, n0[3] * i1), tg);
      const uint32_t o2 = tagged(pack_bf16(n1[0] * i0, n1[1] * i0), tg), o3 = tagged(pack_bf16(n1[2] * i1, n1[3] * i1), tg);
      sts_u4(stash + slot * 8192 + c * 2048, o0, o1, o2, o3);
      stg_u4(xptr(slot, c), o0, o1, o2, o3);
    };
    const uint32_t kvb = area + 5 * 8192;
    const uint32_t kvfrag = kvb + ((lane & 7) + ((lane >> 3) & 1) * 8) * 32 + (lane >> 4) * 16;
    auto signal = [&](int e) INL {
      __syncwarp();
      if (lane == 0) mbar_arrive(BAR(B_EV + w * 2 + e));
    };

    auto pp_wait = [&]() INL { bar_sync(3 + w, 256); };
    auto pp_pass = [&]() INL { bar_arrive(3 + (w ^ 1), 256); };
    if (w == 1) pp_pass();
    int tw1 = 0, tw2 = 0, tw3 = 0;
#pragma unroll 1
    for (int t = 0; t < 5; t++) {
      const uint32_t ph = t & 1;
      const int kind = odd ? (t < 2 ? K_KV : K_GU) : (t < 4 ? K_GU : K_Q);
      const int slot = odd ? t - 2 : t, xslot = odd ? t + 4 : t;
      static_for<2>([&](auto hc) INL {
        constexpr int hb = decltype(hc)::value;
        float acc[32];
        TWAIT(tw2, pp_wait());
        static_for<4>([&](auto kc) INL {
          constexpr int kq = decltype(kc)::value, k = hb * 4 + kq;
          TWAIT(tw1, mbar_wait(BAR(B_FULL + k), ph));
          wgmma_fence();
          static_for<8>([&](auto kkc) INL {
            constexpr int kk = decltype(kkc)::value, i = (kq * 8 + kk) * 4;
            wgmma_n64_rs<(kq | kk) != 0, desc_lo(stage_off(k) + kk * 1024, 8192), kHi64>(acc, A[i], A[i + 1], A[i + 2], A[i + 3]);
          });
          wgmma_commit();
          if (kq == 2) pp_pass();
          if (kq > 0) {
            wgmma_wait<1>();
            release(k - 1);
          }
        });
        TWAIT(tw3, wgmma_wait<0>());
        release(hb * 4 + 3);
        if (kind == K_GU) {
          gu_chunk(acc, 0, slot, xslot, hb);
          gu_chunk(acc, 1, slot, xslot, hb);
        } else if (kind == K_KV) {
          if (hb == 0 && t == 0) sts_u4(stash + 5 * 8192, 0x3F803F80u, 0x3F803F80u, 0x3F803F80u, 0x3F803F80u);
          kv_stage(acc, 0, hb);
          kv_stage(acc, 1, hb);
          if (hb == 1) {
            float kvacc[36];
            const int par = (xoff & 1u) ^ 1u;
            fence_proxy_async();
            bar_sync(1 + w, 128);
            wgmma_fence();
            static_for<4>([&](auto kkc) INL {
              constexpr int kk = decltype(kkc)::value;
              wgmma_n72_ss_tt<kk != 0, desc_lo(3 * 8192 + kk * 2048, 0), desc_lo(4 * 8192 + kk * 2048, 8192 - kk * 2048)>(kvacc, dbase + w * 4096);
            });
            wgmma_commit();
            wgmma_wait<0>();
            float c[8];
#pragma unroll
            for (int i = 0; i < 8; i++)
              c[i] = wq == 0 ? kvacc[i] : (wq == 1 ? kvacc[8 + i] : (wq == 2 ? kvacc[16 + i] : kvacc[24 + i]));
            const int head = (2 * p + t) * 4 + wq;
            float* kvp = &g_kv[par][head][0][0];
            red_add_v2(kvp + g * 16 + 2 * tq, c[0], c[1]);
            red_add_v2(kvp + (g + 8) * 16 + 2 * tq, c[2], c[3]);
            red_add_v2(kvp + g * 16 + 8 + 2 * tq, c[4], c[5]);
            red_add_v2(kvp + (g + 8) * 16 + 8 + 2 * tq, c[6], c[7]);
            if (tq == 0) {
              red_add(&g_z[par][head][g], kvacc[32]);
              red_add(&g_z[par][head][g + 8], kvacc[34]);
            }
            signal(t);
          }
        } else {
          if (hb == 0) mbar_wait(BAR(B_KVREADY), 0);
          uint32_t Bf[4][6];
#pragma unroll
          for (int c = 0; c < 4; c++) {
            ldmatrix_x4_trans(kvfrag + (hb * 4 + c) * 512, Bf[c][0], Bf[c][1], Bf[c][2], Bf[c][3]);
            Bf[c][4] = lds_u32(kvb + 4096 + (hb * 4 + c) * 32 + tq * 4);
            Bf[c][5] = lds_u32(kvb + 4096 + (hb * 4 + c) * 32 + 16 + tq * 4);
          }
          if (hb == 1) bar_sync(1 + w, 128);
#pragma unroll
          for (int c = 0; c < 4; c++) q_head(acc, c, 4 + hb, Bf[c][0], Bf[c][1], Bf[c][2], Bf[c][3], Bf[c][4], Bf[c][5]);
        }
      });
      PROF(w, 1 + 2 * t);
    }
    PROF(w, 10);

    const int n_own = odd ? 3 : 6;
    auto load_a = [&](int kb) INL {
      if (kb < n_own) {
#pragma unroll
        for (int jj = 0; jj < 4; jj++) {
          const int i = (kb * 4 + jj) * 4;
          lds_u4(stash + kb * 8192 + jj * 2048, A[i], A[i + 1], A[i + 2], A[i + 3]);
        }
      } else {
        const int xs = odd ? kb - 3 : kb;
#pragma unroll
        for (int jj = 0; jj < 4; jj++) {
          const int i = (kb * 4 + jj) * 4;
          ldg_poll_u4(xptr(xs, jj), A[i], A[i + 1], A[i + 2], A[i + 3]);
        }
      }
    };
    auto fix_a = [&](int kb) INL {
      if (kb >= n_own) {
        const int xs = odd ? kb - 3 : kb;
        recv_group<4>(xptr(xs, 0), &A[kb * 16], xoff & 1u);
      }
    };
#pragma unroll
    for (int kb = 0; kb < 7; kb++) load_a(kb);
    PROF(w, 11);

    const int orow = m * 128 + w * 64 + wq * 16 + g;
    const int ocol = odd * 256 + p * 64 + 2 * tq;
    float acc2[2][32];
    uint32_t poff = (uint32_t)((m * 2 + odd) * 24 + w) * 8192u + (uint32_t)t128 * 16u;
    asm volatile("" : "+r"(poff));
    auto pptr = [&](int dest, int sl) INL { return (uint4*)((char*)g_pbuf + (poff + (uint32_t)(dest * 3 + sl) * 16384u)); };
    uint32_t P[3][16];
    uint32_t xr[16];
    auto send = [&](float (&acc)[32], int bi) INL {
      uint4* dst = pptr((p + 1 + bi) & 3, bi);
#pragma unroll
      for (int q = 0; q < 4; q++)
        stg_u4(dst + q * 128, tagged(pack_bf16(acc[q * 8], acc[q * 8 + 1]), xoff & 1u), tagged(pack_bf16(acc[q * 8 + 2], acc[q * 8 + 3]), xoff & 1u),
               tagged(pack_bf16(acc[q * 8 + 4], acc[q * 8 + 5]), xoff & 1u), tagged(pack_bf16(acc[q * 8 + 6], acc[q * 8 + 7]), xoff & 1u));
      PROF(w, 12 + 2 * bi);
    };
    auto fetch = [&](int sl) INL {
#pragma unroll
      for (int q = 0; q < 4; q++) ldg_poll_u4(pptr(p, sl) + q * 128, P[sl][q * 4], P[sl][q * 4 + 1], P[sl][q * 4 + 2], P[sl][q * 4 + 3]);
    };
    static_for<36>([&](auto ic) INL {
      constexpr int i = decltype(ic)::value, bi = p2_bi(i), kb = p2_kb(i), j = i >> 1, st = j & 7;
      if (i == 9) { load_a(7); load_a(8); }
      if (i == 14) PROF(w, 2);
      if (bi == 0 && kb >= 3) fix_a(kb);
      if (i == 15) PROF(w, 4);
      if (i == 7) PROF(w, 6);
      if (i == 0 || i == 7 || i == 14 || i == 18 || i == 27) pp_wait();
      if ((i & 1) == 0) mbar_wait(BAR(B_FULL + st), (5 + (j >> 3)) & 1);
      wgmma_fence();
      static_for<4>([&](auto kkc) INL {
        constexpr int kk = decltype(kkc)::value, a = (kb * 4 + kk) * 4;
        wgmma_n64_rs<(kb | kk) != 0, desc_lo(stage_off(st) + (i & 1) * 8192 + kk * 2048, 0), kHi128>(acc2[bi & 1], A[a], A[a + 1], A[a + 2], A[a + 3]);
      });
      wgmma_commit();
      if (i == 4 || i == 11 || i == 15 || i == 24 || (i == 33 && w == 0)) pp_pass();
      if (i > 0) {
        wgmma_wait<1>();
        if ((i & 1) == 0 && j - 1 <= 9) release((j - 1) & 7);
      }
      if constexpr (i == 17) { send(acc2[0], 0); wgmma_wait<0>(); send(acc2[1], 1); }
      if constexpr (i == 26) { wgmma_wait<0>(); send(acc2[0], 2); }
      if constexpr (i == 29) fetch(0);
      if constexpr (i == 30) fetch(1);
      if constexpr (i == 28) {
#pragma unroll
        for (int q = 0; q < 8; q++) {
          xr[2 * q] = __ldg((const uint32_t*)(x + (size_t)orow * kD + ocol + q * 8));
          xr[2 * q + 1] = __ldg((const uint32_t*)(x + (size_t)(orow + 8) * kD + ocol + q * 8));
        }
      }
      if constexpr (i == 32) fetch(2);
    });
#pragma unroll
    for (int sl = 0; sl < 3; sl++) { PROF(w, 13 + 2 * sl); recv_group<4>(pptr(p, sl), &P[sl][0], xoff & 1u); }
    wgmma_wait<0>();
    PROF(w, 18);
#pragma unroll
    for (int q = 0; q < 8; q++) {
      float rr[4];
      rr[0] = acc2[1][q * 4 + 0] + __uint_as_float(xr[2 * q] << 16);
      rr[1] = acc2[1][q * 4 + 1] + __uint_as_float(xr[2 * q] & 0xffff0000u);
      rr[2] = acc2[1][q * 4 + 2] + __uint_as_float(xr[2 * q + 1] << 16);
      rr[3] = acc2[1][q * 4 + 3] + __uint_as_float(xr[2 * q + 1] & 0xffff0000u);
#pragma unroll
      for (int sl = 0; sl < 3; sl++) {
        rr[0] += __uint_as_float(P[sl][2 * q] << 16);
        rr[1] += __uint_as_float(P[sl][2 * q] & 0xffff0000u);
        rr[2] += __uint_as_float(P[sl][2 * q + 1] << 16);
        rr[3] += __uint_as_float(P[sl][2 * q + 1] & 0xffff0000u);
      }
      *(uint32_t*)(out + (size_t)orow * kD + ocol + q * 8) = pack_bf16(rr[0], rr[1]);
      *(uint32_t*)(out + (size_t)(orow + 8) * kD + ocol + q * 8) = pack_bf16(rr[2], rr[3]);
    }
    PROF(w, 19);
    if (tid == 0) {
      const uint32_t old = atomicAdd(&g_done, 1u);
      if ((old & 127u) == 127u) st_relaxed(&g_epoch, ld_relaxed(&g_epoch) + 1u);
    }
  }
#undef BAR
}

typedef CUresult (*EncodeFn)(CUtensorMap*, CUtensorMapDataType, cuuint32_t, void*, const cuuint64_t*, const cuuint64_t*,
                             const cuuint32_t*, const cuuint32_t*, CUtensorMapInterleave, CUtensorMapSwizzle,
                             CUtensorMapL2promotion, CUtensorMapFloatOOBfill);

void make_map(EncodeFn enc, CUtensorMap* tm, const void* ptr, int rows, int cols, bool narrow) {
  cuuint64_t gd[2] = {(cuuint64_t)cols, (cuuint64_t)rows};
  cuuint64_t gs[1] = {(cuuint64_t)cols * 2};
  cuuint32_t bd[2] = {narrow ? 32u : 64u, narrow ? 128u : 64u};
  cuuint32_t es[2] = {1, 1};
  enc(tm, CU_TENSOR_MAP_DATA_TYPE_BFLOAT16, 2, const_cast<void*>(ptr), gd, gs, bd, es, CU_TENSOR_MAP_INTERLEAVE_NONE,
      narrow ? CU_TENSOR_MAP_SWIZZLE_64B : CU_TENSOR_MAP_SWIZZLE_128B, CU_TENSOR_MAP_L2_PROMOTION_L2_256B, CU_TENSOR_MAP_FLOAT_OOB_FILL_NONE);
}

}

extern "C" void kernel_launch(void* const* d_in, const int* in_sizes, int n_in, void* d_out, int out_size) {
  static EncodeFn enc = nullptr;
  if (!enc) {
    void* fn = nullptr;
    cudaDriverEntryPointQueryResult qr;
    cudaGetDriverEntryPoint("cuTensorMapEncodeTiled", &fn, cudaEnableDefault, &qr);
    enc = (EncodeFn)fn;
    cudaFuncSetAttribute(fused_kernel, cudaFuncAttributeMaxDynamicSharedMemorySize, kSmemBytes);
  }
  CUtensorMap tm_x, tm_wqkv, tm_w1, tm_w3, tm_w2, tm_wo;
  make_map(enc, &tm_x, d_in[0], kS, kD, false);
  make_map(enc, &tm_wqkv, d_in[1], kD, 3 * kD, true);
  make_map(enc, &tm_wo, d_in[2], kD, kD, false);
  make_map(enc, &tm_w1, d_in[4], kD, kF, true);
  make_map(enc, &tm_w3, d_in[5], kD, kF, true);
  make_map(enc, &tm_w2, d_in[6], kF, kD, false);
  fused_kernel<<<128, 384, kSmemBytes>>>(tm_x, tm_wqkv, tm_w1, tm_w3, tm_w2, tm_wo, (const __nv_bfloat16*)d_in[0],
                                         (__nv_bfloat16*)d_out);
}
```

```cpp
#include <cuda_runtime.h>
#include <cuda_bf16.h>
#include <cuda.h>
#include <stdint.h>

extern __shared__ __align__(1024) uint8_t smem_raw[];

namespace {

constexpr int kS = 2048, kD = 512, kF = 1792;
constexpr uint32_t kSpinLimit = 1u << 22;

__device__ uint4    g_xbuf[16][4][9][2][4][128];
__device__ uint4    g_pbuf[16][2][4][3][2][4][128];
__device__ float    g_kv[2][32][16][16];
__device__ float    g_z[2][32][16];
__device__ uint32_t g_kvcnt[4][32];
__device__ uint32_t g_epoch;
__device__ uint32_t g_done;
#define PROF(wg, i) do {} while (0)
#define TWAIT(acc, stmt) do { stmt; } while (0)

__device__ __forceinline__ uint32_t smem_u32(const void* p) { return (uint32_t)__cvta_generic_to_shared(p); }
__device__ __forceinline__ void mbar_init(uint32_t bar, uint32_t cnt) {
  asm volatile("mbarrier.init.shared::cta.b64 [%0], %1;" ::"r"(bar), "r"(cnt) : "memory");
}
__device__ __forceinline__ void mbar_expect_tx(uint32_t bar, uint32_t bytes) {
  asm volatile("mbarrier.arrive.expect_tx.shared::cta.b64 _, [%0], %1;" ::"r"(bar), "r"(bytes) : "memory");
}
__device__ __forceinline__ void mbar_arrive(uint32_t bar) {
  asm volatile("mbarrier.arrive.shared::cta.b64 _, [%0];" ::"r"(bar) : "memory");
}
__device__ __forceinline__ void mbar_wait(uint32_t bar, uint32_t parity) {
  asm volatile(
      "{\n.reg .pred p;\n"
      "LAB_WAIT:\n"
      "mbarrier.try_wait.parity.shared::cta.b64 p, [%0], %1;\n"
      "@p bra DONE;\n"
      "bra LAB_WAIT;\n"
      "DONE:\n}" ::"r"(bar), "r"(parity) : "memory");
}
__device__ __forceinline__ void tma_load_2d(uint32_t dst, const CUtensorMap* tm, uint32_t bar, int c0, int c1) {
  asm volatile(
      "cp.async.bulk.tensor.2d.shared::cluster.global.mbarrier::complete_tx::bytes [%0], [%1, {%3, %4}], [%2];" ::"r"(dst),
      "l"(tm), "r"(bar), "r"(c0), "r"(c1)
      : "memory");
}
__device__ __forceinline__ void tma_load_2d_mc(uint32_t dst, const CUtensorMap* tm, uint32_t bar, int c0, int c1) {
  asm volatile(
      "cp.async.bulk.tensor.2d.shared::cluster.global.mbarrier::complete_tx::bytes.multicast::cluster [%0], [%1, {%3, %4}], [%2], %5;" ::"r"(dst),
      "l"(tm), "r"(bar), "r"(c0), "r"(c1), "h"((uint16_t)3)
      : "memory");
}
__device__ __forceinline__ void mbar_arrive_cluster(uint32_t bar, uint32_t cta) {
  asm volatile("{\n.reg .b32 ra;\nmapa.shared::cluster.u32 ra, %0, %1;\nmbarrier.arrive.shared::cluster.b64 _, [ra];\n}" ::"r"(bar), "r"(cta) : "memory");
}
__device__ __forceinline__ void prefetch_tmap(const CUtensorMap* tm) {
  asm volatile("prefetch.tensormap [%0];" ::"l"(tm) : "memory");
}
__device__ __forceinline__ void wgmma_fence() { asm volatile("wgmma.fence.sync.aligned;" ::: "memory"); }
__device__ __forceinline__ void wgmma_commit() { asm volatile("wgmma.commit_group.sync.aligned;" ::: "memory"); }
template <int N>
__device__ __forceinline__ void wgmma_wait() { asm volatile("wgmma.wait_group.sync.aligned %0;" ::"n"(N) : "memory"); }
__device__ __forceinline__ void bar_sync(int id, int n) { asm volatile("bar.sync %0, %1;" ::"r"(id), "r"(n) : "memory"); }
__device__ __forceinline__ void bar_arrive(int id, int n) { asm volatile("bar.arrive %0, %1;" ::"r"(id), "r"(n) : "memory"); }
__device__ __forceinline__ void fence_proxy_async() { asm volatile("fence.proxy.async.shared::cta;" ::: "memory"); }

__device__ __forceinline__ uint32_t ld_acquire(const uint32_t* p) {
  uint32_t v;
  asm volatile("ld.acquire.gpu.global.u32 %0, [%1];" : "=r"(v) : "l"(p) : "memory");
  return v;
}
__device__ __forceinline__ uint32_t ld_relaxed(const uint32_t* p) {
  uint32_t v;
  asm volatile("ld.relaxed.gpu.global.u32 %0, [%1];" : "=r"(v) : "l"(p));
  return v;
}
__device__ __forceinline__ void cluster_wait() { asm volatile("barrier.cluster.wait.aligned;" ::: "memory"); }
__device__ __forceinline__ void st_relaxed(uint32_t* p, uint32_t v) {
  asm volatile("st.relaxed.gpu.global.u32 [%0], %1;" ::"l"(p), "r"(v) : "memory");
}
__device__ __forceinline__ void wait_flag_eq(const uint32_t* p, uint32_t val) {
  uint32_t it = 0;
  while (ld_acquire(p) != val) {
    if (++it > kSpinLimit) break;
  }
}
__device__ __forceinline__ void wait_count_ge(const uint32_t* p, uint32_t val) {
  uint32_t it = 0;
  while ((int32_t)(ld_acquire(p) - val) < 0) {
    __nanosleep(64);
    if (++it > kSpinLimit) break;
  }
}
__device__ __forceinline__ void ldg_poll_u4(const void* p, uint32_t& a, uint32_t& b, uint32_t& c, uint32_t& d) {
  asm volatile("ld.relaxed.gpu.global.v4.u32 {%0,%1,%2,%3}, [%4];" : "=r"(a), "=r"(b), "=r"(c), "=r"(d) : "l"(p) : "memory");
}
template <int N>
__device__ __forceinline__ void recv_group(const uint4* p, uint32_t* r, uint32_t tag) {
  uint32_t it = 0;
  while (true) {
    uint32_t bad = 0u;
#pragma unroll
    for (int i = 0; i < 4 * N; i++) bad |= r[i] ^ tag;
    if (!__any_sync(0xffffffffu, (bad & 1u) != 0u) || ++it > kSpinLimit) break;
#pragma unroll
    for (int q = 0; q < N; q++) ldg_poll_u4(p + q * 128, r[q * 4], r[q * 4 + 1], r[q * 4 + 2], r[q * 4 + 3]);
  }
}
__device__ __forceinline__ uint32_t tagged(uint32_t v, uint32_t tag) { return (v & ~1u) | tag; }
__device__ __forceinline__ float4 ldg_cg_f4(const void* p) {
  float4 v;
  asm volatile("ld.global.cg.v4.f32 {%0,%1,%2,%3}, [%4];" : "=f"(v.x), "=f"(v.y), "=f"(v.z), "=f"(v.w) : "l"(p) : "memory");
  return v;
}
__device__ __forceinline__ void stg_u4(void* p, uint32_t a, uint32_t b, uint32_t c, uint32_t d) {
  asm volatile("st.global.v4.u32 [%0], {%1,%2,%3,%4};" ::"l"(p), "r"(a), "r"(b), "r"(c), "r"(d) : "memory");
}
__device__ __forceinline__ void stg_f4(void* p, float a, float b, float c, float d) {
  asm volatile("st.global.v4.f32 [%0], {%1,%2,%3,%4};" ::"l"(p), "f"(a), "f"(b), "f"(c), "f"(d) : "memory");
}
__device__ __forceinline__ void sts_u4(uint32_t addr, uint32_t a, uint32_t b, uint32_t c, uint32_t d) {
  asm volatile("st.shared.v4.u32 [%0], {%1,%2,%3,%4};" ::"r"(addr), "r"(a), "r"(b), "r"(c), "r"(d) : "memory");
}
__device__ __forceinline__ void lds_u4(uint32_t addr, uint32_t& a, uint32_t& b, uint32_t& c, uint32_t& d) {
  asm volatile("ld.shared.v4.u32 {%0,%1,%2,%3}, [%4];" : "=r"(a), "=r"(b), "=r"(c), "=r"(d) : "r"(addr) : "memory");
}
__device__ __forceinline__ uint32_t lds_u32(uint32_t addr) {
  uint32_t v;
  asm volatile("ld.shared.u32 %0, [%1];" : "=r"(v) : "r"(addr) : "memory");
  return v;
}
__device__ __forceinline__ void ldmatrix_x4(uint32_t addr, uint32_t& a, uint32_t& b, uint32_t& c, uint32_t& d) {
  asm volatile("ldmatrix.sync.aligned.m8n8.x4.shared.b16 {%0,%1,%2,%3}, [%4];" : "=r"(a), "=r"(b), "=r"(c), "=r"(d) : "r"(addr) : "memory");
}
__device__ __forceinline__ void ldmatrix_x4_trans(uint32_t addr, uint32_t& a, uint32_t& b, uint32_t& c, uint32_t& d) {
  asm volatile("ldmatrix.sync.aligned.m8n8.x4.trans.shared.b16 {%0,%1,%2,%3}, [%4];" : "=r"(a), "=r"(b), "=r"(c), "=r"(d) : "r"(addr) : "memory");
}
__device__ __forceinline__ void stmatrix_x4(uint32_t addr, uint32_t a, uint32_t b, uint32_t c, uint32_t d) {
  asm volatile("stmatrix.sync.aligned.m8n8.x4.shared.b16 [%0], {%1,%2,%3,%4};" ::"r"(addr), "r"(a), "r"(b), "r"(c), "r"(d) : "memory");
}
__device__ __forceinline__ void mma_16816(float (&c)[4], uint32_t a0, uint32_t a1, uint32_t a2, uint32_t a3, uint32_t b0, uint32_t b1) {
  asm(
      "mma.sync.aligned.m16n8k16.row.col.f32.bf16.bf16.f32 {%0,%1,%2,%3}, {%4,%5,%6,%7}, {%8,%9}, {%0,%1,%2,%3};"
      : "+f"(c[0]), "+f"(c[1]), "+f"(c[2]), "+f"(c[3])
      : "r"(a0), "r"(a1), "r"(a2), "r"(a3), "r"(b0), "r"(b1));
}
__device__ __forceinline__ uint32_t pack_bf16(float lo, float hi) {
  uint32_t r;
  asm("cvt.rn.bf16x2.f32 %0, %1, %2;" : "=r"(r) : "f"(hi), "f"(lo));
  return r;
}
__device__ __forceinline__ uint32_t hsub2_bf16(uint32_t a, uint32_t b) {
  uint32_t r;
  asm("sub.rn.bf16x2 %0, %1, %2;" : "=r"(r) : "r"(a), "r"(b));
  return r;
}
__device__ __forceinline__ float ex2f(float x) {
  float r;
  asm("ex2.approx.ftz.f32 %0, %1;" : "=f"(r) : "f"(x));
  return r;
}
__device__ __forceinline__ float rcpf(float x) {
  float r;
  asm("rcp.approx.ftz.f32 %0, %1;" : "=f"(r) : "f"(x));
  return r;
}
__device__ __forceinline__ void red_add_v2(float* p, float a, float b) {
  asm volatile("red.relaxed.gpu.global.add.v2.f32 [%0], {%1,%2};" ::"l"(p), "f"(a), "f"(b) : "memory");
}
__device__ __forceinline__ void red_add(float* p, float a) {
  asm volatile("red.relaxed.gpu.global.add.f32 [%0], %1;" ::"l"(p), "f"(a) : "memory");
}
__device__ __forceinline__ float phi_f(float t) {
  float e = ex2f(t * 1.4426950408889634f);
  return (t > 0.f ? t + 1.f : e) + 1e-6f;
}

#define R8(a, o) "+f"(a[o + 0]), "+f"(a[o + 1]), "+f"(a[o + 2]), "+f"(a[o + 3]), "+f"(a[o + 4]), "+f"(a[o + 5]), "+f"(a[o + 6]), "+f"(a[o + 7])

#define W8(a, o) "=f"(a[o + 0]), "=f"(a[o + 1]), "=f"(a[o + 2]), "=f"(a[o + 3]), "=f"(a[o + 4]), "=f"(a[o + 5]), "=f"(a[o + 6]), "=f"(a[o + 7])
#define D32 "{%0,%1,%2,%3,%4,%5,%6,%7,%8,%9,%10,%11,%12,%13,%14,%15,%16,%17,%18,%19,%20,%21,%22,%23,%24,%25,%26,%27,%28,%29,%30,%31}"
#define D36 "{%0,%1,%2,%3,%4,%5,%6,%7,%8,%9,%10,%11,%12,%13,%14,%15,%16,%17,%18,%19,%20,%21,%22,%23,%24,%25,%26,%27,%28,%29,%30,%31,%32,%33,%34,%35}"

constexpr uint32_t kHi128 = (1024u >> 4) | (1u << 30);
constexpr uint32_t kHi64 = (512u >> 4) | (2u << 30);
__host__ __device__ constexpr uint32_t desc_lo(uint32_t off, uint32_t lbo) { return (off >> 4) | ((lbo >> 4) << 16); }

template <bool ACC, uint32_t LO, uint32_t HI>
__device__ __forceinline__ void wgmma_n64_rs(float (&d)[32], uint32_t a0, uint32_t a1, uint32_t a2, uint32_t a3) {
  if (ACC) {
    asm volatile(
        "{\n.reg .pred p;\n.reg .b32 lo;\n.reg .b64 dd;\nsetp.eq.b32 p, 0, 0;\nmov.u32 lo, 64;\nadd.u32 lo, lo, %36;\nmov.b64 dd, {lo, %37};\n"
        "wgmma.mma_async.sync.aligned.m64n64k16.f32.bf16.bf16 " D32 ", {%32,%33,%34,%35}, dd, p, 1, 1, 1;\n}"
        : R8(d, 0), R8(d, 8), R8(d, 16), R8(d, 24)
        : "r"(a0), "r"(a1), "r"(a2), "r"(a3), "n"(LO), "n"(HI));
  } else {
    asm volatile(
        "{\n.reg .pred p;\n.reg .b32 lo;\n.reg .b64 dd;\nsetp.ne.b32 p, 0, 0;\nmov.u32 lo, 64;\nadd.u32 lo, lo, %36;\nmov.b64 dd, {lo, %37};\n"
        "wgmma.mma_async.sync.aligned.m64n64k16.f32.bf16.bf16 " D32 ", {%32,%33,%34,%35}, dd, p, 1, 1, 1;\n}"
        : W8(d, 0), W8(d, 8), W8(d, 16), W8(d, 24)
        : "r"(a0), "r"(a1), "r"(a2), "r"(a3), "n"(LO), "n"(HI));
  }
}
template <bool ACC, uint32_t LOA, uint32_t LOB>
__device__ __forceinline__ void wgmma_n72_ss_tt(float (&d)[36], uint32_t base) {
  if (ACC) {
    asm volatile(
        "{\n.reg .pred p;\n.reg .b32 lo;\n.reg .b64 da, db;\nsetp.eq.b32 p, 0, 0;\n"
        "add.u32 lo, %36, %37;\nmov.b64 da, {lo, %39};\nadd.u32 lo, %36, %38;\nmov.b64 db, {lo, %39};\n"
        "wgmma.mma_async.sync.aligned.m64n72k16.f32.bf16.bf16 " D36 ", da, db, p, 1, 1, 1, 1;\n}"
        : R8(d, 0), R8(d, 8), R8(d, 16), R8(d, 24), "+f"(d[32]), "+f"(d[33]), "+f"(d[34]), "+f"(d[35])
        : "r"(base), "n"(LOA), "n"(LOB), "n"(kHi128));
  } else {
    asm volatile(
        "{\n.reg .pred p;\n.reg .b32 lo;\n.reg .b64 da, db;\nsetp.ne.b32 p, 0, 0;\n"
        "add.u32 lo, %36, %37;\nmov.b64 da, {lo, %39};\nadd.u32 lo, %36, %38;\nmov.b64 db, {lo, %39};\n"
        "wgmma.mma_async.sync.aligned.m64n72k16.f32.bf16.bf16 " D36 ", da, db, p, 1, 1, 1, 1;\n}"
        : W8(d, 0), W8(d, 8), W8(d, 16), W8(d, 24), "=f"(d[32]), "=f"(d[33]), "=f"(d[34]), "=f"(d[35])
        : "r"(base), "n"(LOA), "n"(LOB), "n"(kHi128));
  }
}

#define INL __attribute__((always_inline))
template <int V> struct IC { static constexpr int value = V; };
template <int N, int I = 0, typename F>
__device__ __forceinline__ void static_for(F&& f) {
  if constexpr (I < N) { f(IC<I>{}); static_for<N, I + 1>(f); }
}

__host__ __device__ constexpr uint32_t stage_off(int st) {
  return st < 6 ? 131072u + (uint32_t)st * 16384u : (uint32_t)(st - 6) * 65536u + 49152u;
}

constexpr int B_FULL = 0, B_EMPTY = 8, B_XFULL = 16, B_XDONE = 32, B_KVREADY = 33, B_EV = 34, B_COUNT = 38;
constexpr uint32_t kBarOff = 229376;
constexpr int kSmemBytes = 229376 + 1024;

__host__ __device__ constexpr int p2_bi(int i) { return i < 7 ? 0 : i < 14 ? 1 : i < 16 ? 0 : i < 18 ? 1 : i / 9; }
__host__ __device__ constexpr int p2_kb(int i) { return i < 7 ? i : i < 14 ? i - 7 : i < 16 ? i - 7 : i < 18 ? i - 9 : i % 9; }

enum { K_NONE = 0, K_GU = 1, K_KV = 2, K_Q = 3 };

__global__ void __cluster_dims__(2, 1, 1) __launch_bounds__(384, 1)
fused_kernel(const __grid_constant__ CUtensorMap tm_x, const __grid_constant__ CUtensorMap tm_wqkv,
             const __grid_constant__ CUtensorMap tm_w1, const __grid_constant__ CUtensorMap tm_w3,
             const __grid_constant__ CUtensorMap tm_w2, const __grid_constant__ CUtensorMap tm_wo,
             const __nv_bfloat16* __restrict__ x, __nv_bfloat16* __restrict__ out) {
  const uint32_t sbase = smem_u32(smem_raw);
  const uint32_t bars = sbase + kBarOff;
  const int tid = threadIdx.x, lane = tid & 31;
  const int warp = __shfl_sync(0xffffffffu, tid >> 5, 0);
  const int cr = blockIdx.x & 1;
  const int r = (blockIdx.x >> 1) & 7, m = ((blockIdx.x >> 4) << 1) | cr, p = r >> 1, odd = r & 1;
#define BAR(i) (bars + 8u * (uint32_t)(i))
  if (tid == 256) {
    if ((sbase & 0x3FFFFu) != 1024u) __trap();
#pragma unroll
    for (int i = 0; i < 16; i++) mbar_init(BAR(B_XFULL + i), 1);
    fence_proxy_async();
#pragma unroll
    for (int b = 0; b < 8; b++) {
      mbar_expect_tx(BAR(B_XFULL + b), 8192);
      tma_load_2d(sbase + (b >> 3) * 65536 + (b & 7) * 8192, &tm_x, BAR(B_XFULL + b), (b & 7) * 64, m * 128 + (b >> 3) * 64);
    }
#pragma unroll
    for (int i = 0; i < 8; i++) { mbar_init(BAR(B_FULL + i), 1); mbar_init(BAR(B_EMPTY + i), 4); }
#pragma unroll
    for (int i = 0; i < 4; i++) mbar_init(BAR(B_EV + i), 4);
    mbar_init(BAR(B_XDONE), 2);
    mbar_init(BAR(B_KVREADY), 1);
    asm volatile("fence.mbarrier_init.release.cluster;" ::: "memory");
    fence_proxy_async();
  } else if (tid == 288) {
    prefetch_tmap(odd ? &tm_wqkv : (cr ? &tm_w3 : &tm_w1));
  }
  __syncwarp();
  asm volatile("barrier.cluster.arrive.relaxed.aligned;" ::: "memory");
  PROF((tid >> 7), 21);
  __syncthreads();

  if (warp >= 8) {
    asm volatile("setmaxnreg.dec.sync.aligned.u32 24;");
    PROF(2, 3);
    cluster_wait();
    PROF(2, 2);
    const uint32_t epoch = warp == 8 ? 0u : ld_relaxed(&g_epoch);
    const uint32_t tag = epoch + 1u;
    const int par = epoch & 1;
    if (warp == 8) {
      if (lane == 0) {
        int twp = 0;
        for (int j = 0; j < 10; j++) {
          const CUtensorMap* tm;
          int col;
          if (!odd) {
            if (j < 8) { tm = cr ? &tm_w3 : &tm_w1; col = 7 * p * 64 + j * 32; }
            else { tm = &tm_wqkv; col = 128 * p + (j - 8) * 64 + cr * 32; }
          } else {
            if (j < 4) { tm = &tm_wqkv; col = 512 + cr * 512 + 128 * p + j * 32; }
            else { tm = cr ? &tm_w3 : &tm_w1; col = (7 * p + 4) * 64 + (j - 4) * 32; }
          }
          const int t = j >> 1;
          if (j == 1) {
            for (int b = 8; b < 16; b++) {
              mbar_expect_tx(BAR(B_XFULL + b), 8192);
              tma_load_2d(sbase + 65536 + (b & 7) * 8192, &tm_x, BAR(B_XFULL + b), (b & 7) * 64, m * 128 + 64);
            }
          }
          for (int kq = 0; kq < 4; kq++) {
            const int k = (j & 1) * 4 + kq;
            TWAIT(twp, mbar_wait(BAR(B_EMPTY + k), k < 6 ? ((t & 1) ^ 1) : (t & 1)));
            mbar_expect_tx(BAR(B_FULL + k), 16384);
            tma_load_2d_mc(sbase + stage_off(k) + cr * 8192, tm, BAR(B_FULL + k), col, kq * 128);
          }
        }
        for (int j = 0; j < 18; j++) {
          const int st = j & 7, n = 5 + (j >> 3);
          const int i = 2 * j + cr;
          const int bi = p2_bi(i), kb = p2_kb(i);
          const int col = odd * 256 + ((p + 1 + bi) & 3) * 64;
          const CUtensorMap* tmk;
          int row;
          if (!odd) {
            if (kb < 4) { tmk = &tm_w2; row = (7 * p + kb) * 64; }
            else if (kb < 6) { tmk = &tm_wo; row = (2 * p + kb - 4) * 64; }
            else { tmk = &tm_w2; row = (7 * p + 4 + kb - 6) * 64; }
          } else {
            if (kb < 3) { tmk = &tm_w2; row = (7 * p + 4 + kb) * 64; }
            else if (kb < 7) { tmk = &tm_w2; row = (7 * p + kb - 3) * 64; }
            else { tmk = &tm_wo; row = (2 * p + kb - 7) * 64; }
          }
          mbar_wait(BAR(B_EMPTY + st), st < 6 ? ((n & 1) ^ 1) : (n & 1));
          mbar_expect_tx(BAR(B_FULL + st), 16384);
          tma_load_2d_mc(sbase + stage_off(st) + cr * 8192, tmk, BAR(B_FULL + st), col, row);
        }
      }
    } else if (warp <= 10) {
      if (lane == 0 && odd) {
        const int w = warp - 9;
        for (int e = 0; e < 2; e++) {
          mbar_wait(BAR(B_EV + w * 2 + e), 0);
          __threadfence();
          atomicAdd(&g_kvcnt[p][0], 1u);
        }
      }
    } else {
      if (!odd) {
        {
          const int ce = m * 4 + p;
          float* kvn = &g_kv[par ^ 1][0][0][0];
          for (int i = lane; i < 128; i += 32) kvn[ce * 128 + i] = 0.f;
          if (lane < 8) (&g_z[par ^ 1][0][0])[ce * 8 + lane] = 0.f;
        }
        mbar_wait(BAR(B_XDONE), 0);
        wait_count_ge(&g_kvcnt[p][0], 64u * tag);
        const float* kvp = &g_kv[par][8 * p][0][0];
        const uint32_t dst0 = sbase + 5 * 8192, dst1 = dst0 + 65536;
#pragma unroll 4
        for (int i = 0; i < 16; i++) {
          float4 v = ldg_cg_f4(kvp + (i * 32 + lane) * 4);
          uint32_t lo = pack_bf16(v.x, v.y), hi = pack_bf16(v.z, v.w);
          uint32_t off = (uint32_t)(i * 32 + lane) * 8u;
          asm volatile("st.shared.v2.u32 [%0], {%1,%2};" ::"r"(dst0 + off), "r"(lo), "r"(hi) : "memory");
          asm volatile("st.shared.v2.u32 [%0], {%1,%2};" ::"r"(dst1 + off), "r"(lo), "r"(hi) : "memory");
        }
        {
          float4 v = ldg_cg_f4(&g_z[par][8 * p][0] + lane * 4);
          uint32_t lo = pack_bf16(v.x, v.y), hi = pack_bf16(v.z, v.w);
          uint32_t off = 4096u + (uint32_t)lane * 8u;
          asm volatile("st.shared.v2.u32 [%0], {%1,%2};" ::"r"(dst0 + off), "r"(lo), "r"(hi) : "memory");
          asm volatile("st.shared.v2.u32 [%0], {%1,%2};" ::"r"(dst1 + off), "r"(lo), "r"(hi) : "memory");
        }
        __syncwarp();
        if (lane == 0) mbar_arrive(BAR(B_KVREADY));
      }
    }
  } else {
    asm volatile("setmaxnreg.inc.sync.aligned.u32 240;");
    const int w = warp >> 2, wq = warp & 3, t128 = tid & 127;
    const int g = lane >> 2, tq = lane & 3;
    const uint32_t area = sbase + (uint32_t)w * 65536u;
    const bool elect = (t128 == 0);
    PROF(w, 22);
    const uint32_t dbase = (sbase & 0x3FFFFu) >> 4;
    uint32_t xoff = (uint32_t)((m * 4 + p) * 18 + w) * 8192u + (uint32_t)t128 * 16u;
    uint32_t stash = area + (uint32_t)t128 * 16u;
    const uint32_t epoch_c = ld_relaxed(&g_epoch);
    auto xptr = [&](int slot, int jj) INL { return (uint4*)((char*)g_xbuf + ((xoff & ~1u) + (uint32_t)slot * 16384u + (uint32_t)jj * 2048u)); };
    uint32_t A[144];
    float rs0, rs1;
    auto release = [&](int st) INL {
      if (elect) { mbar_arrive_cluster(BAR(B_EMPTY + st), 0); mbar_arrive_cluster(BAR(B_EMPTY + st), 1); }
    };

    {
      const int row = wq * 16 + (lane & 7) + ((lane >> 3) & 1) * 8;
      const uint32_t rbase = area + row * 128;
      float s0[2][4] = {}, q0[2][4] = {}, q1[2][4] = {};
      const uint32_t ones = 0x3F803F80u;
#pragma unroll
      for (int b = 0; b < 8; b++) {
        mbar_wait(BAR(B_XFULL + w * 8 + b), 0);
        if (b == 0) PROF(w, 23);
        if (b == 7) PROF(w, 24);
#pragma unroll
        for (int kk = 0; kk < 4; kk++) {
          const int i = (b * 4 + kk) * 4;
          ldmatrix_x4(rbase + b * 8192 + (((kk * 2 + (lane >> 4)) ^ (row & 7)) << 4), A[i], A[i + 1], A[i + 2], A[i + 3]);
        }
#pragma unroll
        for (int kk = 0; kk < 4; kk++) {
          const int i = (b * 4 + kk) * 4;
          mma_16816(s0[kk & 1], A[i], A[i + 1], A[i + 2], A[i + 3], ones, ones);
          mma_16816(q0[kk & 1], A[i], A[i + 1], A[i + 2], A[i + 3], A[i], A[i + 2]);
          mma_16816(q1[kk & 1], A[i], A[i + 1], A[i + 2], A[i + 3], A[i + 1], A[i + 3]);
        }
      }
      const float mean0 = (s0[0][0] + s0[1][0]) * (1.f / 512.f), mean1 = (s0[0][2] + s0[1][2]) * (1.f / 512.f);
      const uint32_t m0 = pack_bf16(mean0, mean0), m1 = pack_bf16(mean1, mean1);
#pragma unroll
      for (int i = 0; i < 128; i += 2) {
        A[i] = hsub2_bf16(A[i], m0);
        A[i + 1] = hsub2_bf16(A[i + 1], m1);
      }
      float v0 = (g & 1) ? q0[0][1] + q0[1][1] : q0[0][0] + q0[1][0];
      float v1 = (g & 1) ? q1[0][3] + q1[1][3] : q1[0][2] + q1[1][2];
      const int src = 4 * g + (g >> 1);
      v0 = __shfl_sync(0xffffffffu, v0, src);
      v1 = __shfl_sync(0xffffffffu, v1, src);
      v0 = fmaxf(v0 * (1.f / 512.f) - mean0 * mean0, 0.f);
      v1 = fmaxf(v1 * (1.f / 512.f) - mean1 * mean1, 0.f);
      rs0 = rsqrtf(v0 + 1e-5f);
      rs1 = rsqrtf(v1 + 1e-5f);
      bar_sync(1 + w, 128);
      cluster_wait();
      asm volatile("" : "+r"(xoff), "+r"(stash));
      PROF(w, 0);
      release(6); release(7);
      if (elect) mbar_arrive(BAR(B_XDONE));
    }

    auto gu_chunk = [&](float (&acc)[32], int f, int slot, int xslot, int hb) INL {
      const float c0 = rs0 * -1.4426950408889634f, c1 = rs1 * -1.4426950408889634f;
      const float q0 = rs0 * rs0, q1 = rs1 * rs1;
      uint32_t h[4];
#pragma unroll
      for (int i = 0; i < 4; i++) {
        const float ga = acc[f * 8 + 2 * i], gb = acc[f * 8 + 2 * i + 1];
        const float ua = acc[16 + f * 8 + 2 * i], ub = acc[16 + f * 8 + 2 * i + 1];
        const float c = (i & 1) ? c1 : c0, q = (i & 1) ? q1 : q0;
        const float da = 1.f + ex2f(fminf(ga * c, 60.f)), db = 1.f + ex2f(fminf(gb * c, 60.f));
        const float rq = rcpf(da * db) * q;
        h[i] = tagged(pack_bf16(ga * ua * (db * rq), gb * ub * (da * rq)), xoff & 1u);
      }
      const int jj = hb * 2 + f;
      sts_u4(stash + slot * 8192 + jj * 2048, h[0], h[1], h[2], h[3]);
      stg_u4(xptr(xslot, jj), h[0], h[1], h[2], h[3]);
    };
    auto kv_stage = [&](float (&acc)[32], int c, int hb) INL {
      const int srow = wq * 16 + (lane & 7) + ((lane >> 3) & 1) * 8;
      const uint32_t base = area + (3 + c) * 8192 + srow * 128;
#pragma unroll
      for (int jj = 0; jj < 2; jj++) {
        const int a = c * 16 + jj * 8;
        uint32_t r0, r1, r2, r3;
        if (c == 0) {
          r0 = pack_bf16(phi_f(acc[a] * rs0), phi_f(acc[a + 1] * rs0));
          r1 = pack_bf16(phi_f(acc[a + 2] * rs1), phi_f(acc[a + 3] * rs1));
          r2 = pack_bf16(phi_f(acc[a + 4] * rs0), phi_f(acc[a + 5] * rs0));
          r3 = pack_bf16(phi_f(acc[a + 6] * rs1), phi_f(acc[a + 7] * rs1));
        } else {
          r0 = pack_bf16(acc[a] * rs0, acc[a + 1] * rs0);
          r1 = pack_bf16(acc[a + 2] * rs1, acc[a + 3] * rs1);
          r2 = pack_bf16(acc[a + 4] * rs0, acc[a + 5] * rs0);
          r3 = pack_bf16(acc[a + 6] * rs1, acc[a + 7] * rs1);
        }
        stmatrix_x4(base + (((hb * 4 + jj * 2 + (lane >> 4)) ^ (srow & 7)) << 4), r0, r1, r2, r3);
      }
    };
    auto q_head = [&](float (&acc)[32], int c, int slot, uint32_t b0, uint32_t b1, uint32_t b2, uint32_t b3, uint32_t z0, uint32_t z1) INL {
      const int a = c * 8;
      const uint32_t a0 = pack_bf16(phi_f(acc[a] * rs0), phi_f(acc[a + 1] * rs0));
      const uint32_t a1 = pack_bf16(phi_f(acc[a + 2] * rs1), phi_f(acc[a + 3] * rs1));
      const uint32_t a2 = pack_bf16(phi_f(acc[a + 4] * rs0), phi_f(acc[a + 5] * rs0));
      const uint32_t a3 = pack_bf16(phi_f(acc[a + 6] * rs1), phi_f(acc[a + 7] * rs1));
      float n0[4] = {0.f, 0.f, 0.f, 0.f}, n1[4] = {0.f, 0.f, 0.f, 0.f}, dn[4] = {0.f, 0.f, 0.f, 0.f};
      mma_16816(n0, a0, a1, a2, a3, b0, b1);
      mma_16816(n1, a0, a1, a2, a3, b2, b3);
      mma_16816(dn, a0, a1, a2, a3, z0, z1);
      const float i0 = __fdividef(1.f, dn[0] + 1e-6f), i1 = __fdividef(1.f, dn[2] + 1e-6f);
      const uint32_t tg = xoff & 1u;
      const uint32_t o0 = tagged(pack_bf16(n0[0] * i0, n0[1] * i0), tg), o1 = tagged(pack_bf16(n0[2] * i1, n0[3] * i1), tg);
      const uint32_t o2 = tagged(pack_bf16(n1[0] * i0, n1[1] * i0), tg), o3 = tagged(pack_bf16(n1[2] * i1, n1[3] * i1), tg);
      sts_u4(stash + slot * 8192 + c * 2048, o0, o1, o2, o3);
      stg_u4(xptr(slot, c), o0, o1, o2, o3);
    };
    const uint32_t kvb = area + 5 * 8192;
    const uint32_t kvfrag = kvb + ((lane & 7) + ((lane >> 3) & 1) * 8) * 32 + (lane >> 4) * 16;
    auto signal = [&](int e) INL {
      __syncwarp();
      if (lane == 0) mbar_arrive(BAR(B_EV + w * 2 + e));
    };

    auto pp_wait = [&]() INL { bar_sync(3 + w, 256); };
    auto pp_pass = [&]() INL { bar_arrive(3 + (w ^ 1), 256); };
    if (w == 1) pp_pass();
    int tw1 = 0, tw2 = 0, tw3 = 0;
#pragma unroll 1
    for (int t = 0; t < 5; t++) {
      const uint32_t ph = t & 1;
      const int kind = odd ? (t < 2 ? K_KV : K_GU) : (t < 4 ? K_GU : K_Q);
      const int slot = odd ? t - 2 : t, xslot = odd ? t + 4 : t;
      static_for<2>([&](auto hc) INL {
        constexpr int hb = decltype(hc)::value;
        float acc[32];
        TWAIT(tw2, pp_wait());
        static_for<4>([&](auto kc) INL {
          constexpr int kq = decltype(kc)::value, k = hb * 4 + kq;
          TWAIT(tw1, mbar_wait(BAR(B_FULL + k), ph));
          wgmma_fence();
          static_for<8>([&](auto kkc) INL {
            constexpr int kk = decltype(kkc)::value, i = (kq * 8 + kk) * 4;
            wgmma_n64_rs<(kq | kk) != 0, desc_lo(stage_off(k) + kk * 1024, 8192), kHi64>(acc, A[i], A[i + 1], A[i + 2], A[i + 3]);
          });
          wgmma_commit();
          if (kq == 2) pp_pass();
          if (kq > 0) {
            wgmma_wait<1>();
            release(k - 1);
          }
        });
        TWAIT(tw3, wgmma_wait<0>());
        release(hb * 4 + 3);
        if (hb == 0 && t == 0) xoff |= (epoch_c & 1u) ^ 1u;
        if (kind == K_GU) {
          gu_chunk(acc, 0, slot, xslot, hb);
          gu_chunk(acc, 1, slot, xslot, hb);
        } else if (kind == K_KV) {
          if (hb == 0 && t == 0) sts_u4(stash + 5 * 8192, 0x3F803F80u, 0x3F803F80u, 0x3F803F80u, 0x3F803F80u);
          kv_stage(acc, 0, hb);
          kv_stage(acc, 1, hb);
          if (hb == 1) {
            float kvacc[36];
            const int par = (xoff & 1u) ^ 1u;
            fence_proxy_async();
            bar_sync(1 + w, 128);
            wgmma_fence();
            static_for<4>([&](auto kkc) INL {
              constexpr int kk = decltype(kkc)::value;
              wgmma_n72_ss_tt<kk != 0, desc_lo(3 * 8192 + kk * 2048, 0), desc_lo(4 * 8192 + kk * 2048, 8192 - kk * 2048)>(kvacc, dbase + w * 4096);
            });
            wgmma_commit();
            wgmma_wait<0>();
            float c[8];
#pragma unroll
            for (int i = 0; i < 8; i++)
              c[i] = wq == 0 ? kvacc[i] : (wq == 1 ? kvacc[8 + i] : (wq == 2 ? kvacc[16 + i] : kvacc[24 + i]));
            const int head = (2 * p + t) * 4 + wq;
            float* kvp = &g_kv[par][head][0][0];
            red_add_v2(kvp + g * 16 + 2 * tq, c[0], c[1]);
            red_add_v2(kvp + (g + 8) * 16 + 2 * tq, c[2], c[3]);
            red_add_v2(kvp + g * 16 + 8 + 2 * tq, c[4], c[5]);
            red_add_v2(kvp + (g + 8) * 16 + 8 + 2 * tq, c[6], c[7]);
            if (tq == 0) {
              red_add(&g_z[par][head][g], kvacc[32]);
              red_add(&g_z[par][head][g + 8], kvacc[34]);
            }
            signal(t);
          }
        } else {
          if (hb == 0) mbar_wait(BAR(B_KVREADY), 0);
          uint32_t Bf[4][6];
#pragma unroll
          for (int c = 0; c < 4; c++) {
            ldmatrix_x4_trans(kvfrag + (hb * 4 + c) * 512, Bf[c][0], Bf[c][1], Bf[c][2], Bf[c][3]);
            Bf[c][4] = lds_u32(kvb + 4096 + (hb * 4 + c) * 32 + tq * 4);
            Bf[c][5] = lds_u32(kvb + 4096 + (hb * 4 + c) * 32 + 16 + tq * 4);
          }
          if (hb == 1) bar_sync(1 + w, 128);
#pragma unroll
          for (int c = 0; c < 4; c++) q_head(acc, c, 4 + hb, Bf[c][0], Bf[c][1], Bf[c][2], Bf[c][3], Bf[c][4], Bf[c][5]);
        }
      });
      PROF(w, 1 + 2 * t);
    }
    PROF(w, 10);

    const int n_own = odd ? 3 : 6;
    auto load_a = [&](int kb) INL {
      if (kb < n_own) {
#pragma unroll
        for (int jj = 0; jj < 4; jj++) {
          const int i = (kb * 4 + jj) * 4;
          lds_u4(stash + kb * 8192 + jj * 2048, A[i], A[i + 1], A[i + 2], A[i + 3]);
        }
      } else {
        const int xs = odd ? kb - 3 : kb;
#pragma unroll
        for (int jj = 0; jj < 4; jj++) {
          const int i = (kb * 4 + jj) * 4;
          ldg_poll_u4(xptr(xs, jj), A[i], A[i + 1], A[i + 2], A[i + 3]);
        }
      }
    };
    auto fix_a = [&](int kb) INL {
      if (kb >= n_own) {
        const int xs = odd ? kb - 3 : kb;
        recv_group<4>(xptr(xs, 0), &A[kb * 16], xoff & 1u);
      }
    };
#pragma unroll
    for (int kb = 0; kb < 7; kb++) load_a(kb);
    PROF(w, 11);

    const int orow = m * 128 + w * 64 + wq * 16 + g;
    const int ocol = odd * 256 + p * 64 + 2 * tq;
    float acc2[2][32];
    uint32_t poff = (uint32_t)((m * 2 + odd) * 24 + w) * 8192u + (uint32_t)t128 * 16u;
    asm volatile("" : "+r"(poff));
    auto pptr = [&](int dest, int sl) INL { return (uint4*)((char*)g_pbuf + (poff + (uint32_t)(dest * 3 + sl) * 16384u)); };
    uint32_t P[3][16];
    uint32_t xr[16];
    auto send = [&](float (&acc)[32], int bi) INL {
      uint4* dst = pptr((p + 1 + bi) & 3, bi);
#pragma unroll
      for (int q = 0; q < 4; q++)
        stg_u4(dst + q * 128, tagged(pack_bf16(acc[q * 8], acc[q * 8 + 1]), xoff & 1u), tagged(pack_bf16(acc[q * 8 + 2], acc[q * 8 + 3]), xoff & 1u),
               tagged(pack_bf16(acc[q * 8 + 4], acc[q * 8 + 5]), xoff & 1u), tagged(pack_bf16(acc[q * 8 + 6], acc[q * 8 + 7]), xoff & 1u));
      PROF(w, 12 + 2 * bi);
    };
    auto fetch = [&](int sl) INL {
#pragma unroll
      for (int q = 0; q < 4; q++) ldg_poll_u4(pptr(p, sl) + q * 128, P[sl][q * 4], P[sl][q * 4 + 1], P[sl][q * 4 + 2], P[sl][q * 4 + 3]);
    };
    static_for<36>([&](auto ic) INL {
      constexpr int i = decltype(ic)::value, bi = p2_bi(i), kb = p2_kb(i), j = i >> 1, st = j & 7;
      if (i == 9) { load_a(7); load_a(8); }
      if (i == 14) PROF(w, 2);
      if (bi == 0 && kb >= 3) fix_a(kb);
      if (i == 15) PROF(w, 4);
      if (i == 7) PROF(w, 6);
      if (i == 0 || i == 7 || i == 14 || i == 18 || i == 27) pp_wait();
      if ((i & 1) == 0) mbar_wait(BAR(B_FULL + st), (5 + (j >> 3)) & 1);
      wgmma_fence();
      static_for<4>([&](auto kkc) INL {
        constexpr int kk = decltype(kkc)::value, a = (kb * 4 + kk) * 4;
        wgmma_n64_rs<(kb | kk) != 0, desc_lo(stage_off(st) + (i & 1) * 8192 + kk * 2048, 0), kHi128>(acc2[bi & 1], A[a], A[a + 1], A[a + 2], A[a + 3]);
      });
      wgmma_commit();
      if (i == 4 || i == 11 || i == 15 || i == 24 || (i == 33 && w == 0)) pp_pass();
      if (i > 0) {
        wgmma_wait<1>();
        if ((i & 1) == 0 && j - 1 <= 9) release((j - 1) & 7);
      }
      if constexpr (i == 17) { send(acc2[0], 0); wgmma_wait<0>(); send(acc2[1], 1); }
      if constexpr (i == 26) { wgmma_wait<0>(); send(acc2[0], 2); }
      if constexpr (i == 29) fetch(0);
      if constexpr (i == 30) fetch(1);
      if constexpr (i == 28) {
#pragma unroll
        for (int q = 0; q < 8; q++) {
          xr[2 * q] = __ldg((const uint32_t*)(x + (size_t)orow * kD + ocol + q * 8));
          xr[2 * q + 1] = __ldg((const uint32_t*)(x + (size_t)(orow + 8) * kD + ocol + q * 8));
        }
      }
      if constexpr (i == 32) fetch(2);
    });
#pragma unroll
    for (int sl = 0; sl < 3; sl++) { PROF(w, 13 + 2 * sl); recv_group<4>(pptr(p, sl), &P[sl][0], xoff & 1u); }
    wgmma_wait<0>();
    PROF(w, 18);
#pragma unroll
    for (int q = 0; q < 8; q++) {
      float rr[4];
      rr[0] = acc2[1][q * 4 + 0] + __uint_as_float(xr[2 * q] << 16);
      rr[1] = acc2[1][q * 4 + 1] + __uint_as_float(xr[2 * q] & 0xffff0000u);
      rr[2] = acc2[1][q * 4 + 2] + __uint_as_float(xr[2 * q + 1] << 16);
      rr[3] = acc2[1][q * 4 + 3] + __uint_as_float(xr[2 * q + 1] & 0xffff0000u);
#pragma unroll
      for (int sl = 0; sl < 3; sl++) {
        rr[0] += __uint_as_float(P[sl][2 * q] << 16);
        rr[1] += __uint_as_float(P[sl][2 * q] & 0xffff0000u);
        rr[2] += __uint_as_float(P[sl][2 * q + 1] << 16);
        rr[3] += __uint_as_float(P[sl][2 * q + 1] & 0xffff0000u);
      }
      *(uint32_t*)(out + (size_t)orow * kD + ocol + q * 8) = pack_bf16(rr[0], rr[1]);
      *(uint32_t*)(out + (size_t)(orow + 8) * kD + ocol + q * 8) = pack_bf16(rr[2], rr[3]);
    }
    PROF(w, 19);
    if (tid == 0) {
      const uint32_t old = atomicAdd(&g_done, 1u);
      if ((old & 127u) == 127u) st_relaxed(&g_epoch, ld_relaxed(&g_epoch) + 1u);
    }
  }
#undef BAR
}

typedef CUresult (*EncodeFn)(CUtensorMap*, CUtensorMapDataType, cuuint32_t, void*, const cuuint64_t*, const cuuint64_t*,
                             const cuuint32_t*, const cuuint32_t*, CUtensorMapInterleave, CUtensorMapSwizzle,
                             CUtensorMapL2promotion, CUtensorMapFloatOOBfill);

void make_map(EncodeFn enc, CUtensorMap* tm, const void* ptr, int rows, int cols, bool narrow) {
  cuuint64_t gd[2] = {(cuuint64_t)cols, (cuuint64_t)rows};
  cuuint64_t gs[1] = {(cuuint64_t)cols * 2};
  cuuint32_t bd[2] = {narrow ? 32u : 64u, narrow ? 128u : 64u};
  cuuint32_t es[2] = {1, 1};
  enc(tm, CU_TENSOR_MAP_DATA_TYPE_BFLOAT16, 2, const_cast<void*>(ptr), gd, gs, bd, es, CU_TENSOR_MAP_INTERLEAVE_NONE,
      narrow ? CU_TENSOR_MAP_SWIZZLE_64B : CU_TENSOR_MAP_SWIZZLE_128B, CU_TENSOR_MAP_L2_PROMOTION_L2_256B, CU_TENSOR_MAP_FLOAT_OOB_FILL_NONE);
}

}

extern "C" void kernel_launch(void* const* d_in, const int* in_sizes, int n_in, void* d_out, int out_size) {
  static EncodeFn enc = nullptr;
  if (!enc) {
    void* fn = nullptr;
    cudaDriverEntryPointQueryResult qr;
    cudaGetDriverEntryPoint("cuTensorMapEncodeTiled", &fn, cudaEnableDefault, &qr);
    enc = (EncodeFn)fn;
    cudaFuncSetAttribute(fused_kernel, cudaFuncAttributeMaxDynamicSharedMemorySize, kSmemBytes);
  }
  CUtensorMap tm_x, tm_wqkv, tm_w1, tm_w3, tm_w2, tm_wo;
  make_map(enc, &tm_x, d_in[0], kS, kD, false);
  make_map(enc, &tm_wqkv, d_in[1], kD, 3 * kD, true);
  make_map(enc, &tm_wo, d_in[2], kD, kD, false);
  make_map(enc, &tm_w1, d_in[4], kD, kF, true);
  make_map(enc, &tm_w3, d_in[5], kD, kF, true);
  make_map(enc, &tm_w2, d_in[6], kF, kD, false);
  fused_kernel<<<128, 384, kSmemBytes>>>(tm_x, tm_wqkv, tm_w1, tm_w3, tm_w2, tm_wo, (const __nv_bfloat16*)d_in[0],
                                         (__nv_bfloat16*)d_out);
}
```

```cpp
#include <cuda_runtime.h>
#include <cuda_bf16.h>
#include <cuda.h>
#include <stdint.h>

extern __shared__ __align__(1024) uint8_t smem_raw[];

namespace {

constexpr int kS = 2048, kD = 512, kF = 1792;
#define XPOS 1
constexpr uint32_t kSpinLimit = 1u << 22;

__device__ uint4    g_xbuf[16][4][9][2][4][128];
__device__ uint4    g_pbuf[16][2][4][3][2][4][128];
__device__ float    g_kv[2][32][16][16];
__device__ float    g_z[2][32][16];
__device__ uint32_t g_kvcnt[4][32];
__device__ uint32_t g_epoch;
__device__ uint32_t g_done;
#define PROF(wg, i) do {} while (0)
#define TWAIT(acc, stmt) do { stmt; } while (0)

__device__ __forceinline__ uint32_t smem_u32(const void* p) { return (uint32_t)__cvta_generic_to_shared(p); }
__device__ __forceinline__ void mbar_init(uint32_t bar, uint32_t cnt) {
  asm volatile("mbarrier.init.shared::cta.b64 [%0], %1;" ::"r"(bar), "r"(cnt) : "memory");
}
__device__ __forceinline__ void mbar_expect_tx(uint32_t bar, uint32_t bytes) {
  asm volatile("mbarrier.arrive.expect_tx.shared::cta.b64 _, [%0], %1;" ::"r"(bar), "r"(bytes) : "memory");
}
__device__ __forceinline__ void mbar_arrive(uint32_t bar) {
  asm volatile("mbarrier.arrive.shared::cta.b64 _, [%0];" ::"r"(bar) : "memory");
}
__device__ __forceinline__ void mbar_wait(uint32_t bar, uint32_t parity) {
  asm volatile(
      "{\n.reg .pred p;\n"
      "LAB_WAIT:\n"
      "mbarrier.try_wait.parity.shared::cta.b64 p, [%0], %1;\n"
      "@p bra DONE;\n"
      "bra LAB_WAIT;\n"
      "DONE:\n}" ::"r"(bar), "r"(parity) : "memory");
}
__device__ __forceinline__ void tma_load_2d(uint32_t dst, const CUtensorMap* tm, uint32_t bar, int c0, int c1) {
  asm volatile(
      "cp.async.bulk.tensor.2d.shared::cluster.global.mbarrier::complete_tx::bytes [%0], [%1, {%3, %4}], [%2];" ::"r"(dst),
      "l"(tm), "r"(bar), "r"(c0), "r"(c1)
      : "memory");
}
__device__ __forceinline__ void tma_load_2d_mc(uint32_t dst, const CUtensorMap* tm, uint32_t bar, int c0, int c1) {
  asm volatile(
      "cp.async.bulk.tensor.2d.shared::cluster.global.mbarrier::complete_tx::bytes.multicast::cluster [%0], [%1, {%3, %4}], [%2], %5;" ::"r"(dst),
      "l"(tm), "r"(bar), "r"(c0), "r"(c1), "h"((uint16_t)3)
      : "memory");
}
__device__ __forceinline__ void mbar_arrive_cluster(uint32_t bar, uint32_t cta) {
  asm volatile("{\n.reg .b32 ra;\nmapa.shared::cluster.u32 ra, %0, %1;\nmbarrier.arrive.shared::cluster.b64 _, [ra];\n}" ::"r"(bar), "r"(cta) : "memory");
}
__device__ __forceinline__ void prefetch_tmap(const CUtensorMap* tm) {
  asm volatile("prefetch.tensormap [%0];" ::"l"(tm) : "memory");
}
__device__ __forceinline__ void wgmma_fence() { asm volatile("wgmma.fence.sync.aligned;" ::: "memory"); }
__device__ __forceinline__ void wgmma_commit() { asm volatile("wgmma.commit_group.sync.aligned;" ::: "memory"); }
template <int N>
__device__ __forceinline__ void wgmma_wait() { asm volatile("wgmma.wait_group.sync.aligned %0;" ::"n"(N) : "memory"); }
__device__ __forceinline__ void bar_sync(int id, int n) { asm volatile("bar.sync %0, %1;" ::"r"(id), "r"(n) : "memory"); }
__device__ __forceinline__ void bar_arrive(int id, int n) { asm volatile("bar.arrive %0, %1;" ::"r"(id), "r"(n) : "memory"); }
__device__ __forceinline__ void fence_proxy_async() { asm volatile("fence.proxy.async.shared::cta;" ::: "memory"); }

__device__ __forceinline__ uint32_t ld_acquire(const uint32_t* p) {
  uint32_t v;
  asm volatile("ld.acquire.gpu.global.u32 %0, [%1];" : "=r"(v) : "l"(p) : "memory");
  return v;
}
__device__ __forceinline__ uint32_t ld_relaxed(const uint32_t* p) {
  uint32_t v;
  asm volatile("ld.relaxed.gpu.global.u32 %0, [%1];" : "=r"(v) : "l"(p));
  return v;
}
__device__ __forceinline__ void cluster_wait() { asm volatile("barrier.cluster.wait.aligned;" ::: "memory"); }
__device__ __forceinline__ void st_relaxed(uint32_t* p, uint32_t v) {
  asm volatile("st.relaxed.gpu.global.u32 [%0], %1;" ::"l"(p), "r"(v) : "memory");
}
__device__ __forceinline__ void wait_flag_eq(const uint32_t* p, uint32_t val) {
  uint32_t it = 0;
  while (ld_acquire(p) != val) {
    if (++it > kSpinLimit) break;
  }
}
__device__ __forceinline__ void wait_count_ge(const uint32_t* p, uint32_t val) {
  uint32_t it = 0;
  while ((int32_t)(ld_acquire(p) - val) < 0) {
    __nanosleep(64);
    if (++it > kSpinLimit) break;
  }
}
__device__ __forceinline__ void ldg_poll_u4(const void* p, uint32_t& a, uint32_t& b, uint32_t& c, uint32_t& d) {
  asm volatile("ld.relaxed.gpu.global.v4.u32 {%0,%1,%2,%3}, [%4];" : "=r"(a), "=r"(b), "=r"(c), "=r"(d) : "l"(p) : "memory");
}
template <int N>
__device__ __forceinline__ void recv_group(const uint4* p, uint32_t* r, uint32_t tag) {
  uint32_t it = 0;
  while (true) {
    uint32_t bad = 0u;
#pragma unroll
    for (int i = 0; i < 4 * N; i++) bad |= r[i] ^ tag;
    if (!__any_sync(0xffffffffu, (bad & 1u) != 0u) || ++it > kSpinLimit) break;
#pragma unroll
    for (int q = 0; q < N; q++) ldg_poll_u4(p + q * 128, r[q * 4], r[q * 4 + 1], r[q * 4 + 2], r[q * 4 + 3]);
  }
}
__device__ __forceinline__ uint32_t tagged(uint32_t v, uint32_t tag) { return (v & ~1u) | tag; }
__device__ __forceinline__ float4 ldg_cg_f4(const void* p) {
  float4 v;
  asm volatile("ld.global.cg.v4.f32 {%0,%1,%2,%3}, [%4];" : "=f"(v.x), "=f"(v.y), "=f"(v.z), "=f"(v.w) : "l"(p) : "memory");
  return v;
}
__device__ __forceinline__ void stg_u4(void* p, uint32_t a, uint32_t b, uint32_t c, uint32_t d) {
  asm volatile("st.global.v4.u32 [%0], {%1,%2,%3,%4};" ::"l"(p), "r"(a), "r"(b), "r"(c), "r"(d) : "memory");
}
__device__ __forceinline__ void stg_f4(void* p, float a, float b, float c, float d) {
  asm volatile("st.global.v4.f32 [%0], {%1,%2,%3,%4};" ::"l"(p), "f"(a), "f"(b), "f"(c), "f"(d) : "memory");
}
__device__ __forceinline__ void sts_u4(uint32_t addr, uint32_t a, uint32_t b, uint32_t c, uint32_t d) {
  asm volatile("st.shared.v4.u32 [%0], {%1,%2,%3,%4};" ::"r"(addr), "r"(a), "r"(b), "r"(c), "r"(d) : "memory");
}
__device__ __forceinline__ void lds_u4(uint32_t addr, uint32_t& a, uint32_t& b, uint32_t& c, uint32_t& d) {
  asm volatile("ld.shared.v4.u32 {%0,%1,%2,%3}, [%4];" : "=r"(a), "=r"(b), "=r"(c), "=r"(d) : "r"(addr) : "memory");
}
__device__ __forceinline__ uint32_t lds_u32(uint32_t addr) {
  uint32_t v;
  asm volatile("ld.shared.u32 %0, [%1];" : "=r"(v) : "r"(addr) : "memory");
  return v;
}
__device__ __forceinline__ void ldmatrix_x4(uint32_t addr, uint32_t& a, uint32_t& b, uint32_t& c, uint32_t& d) {
  asm volatile("ldmatrix.sync.aligned.m8n8.x4.shared.b16 {%0,%1,%2,%3}, [%4];" : "=r"(a), "=r"(b), "=r"(c), "=r"(d) : "r"(addr) : "memory");
}
__device__ __forceinline__ void ldmatrix_x4_trans(uint32_t addr, uint32_t& a, uint32_t& b, uint32_t& c, uint32_t& d) {
  asm volatile("ldmatrix.sync.aligned.m8n8.x4.trans.shared.b16 {%0,%1,%2,%3}, [%4];" : "=r"(a), "=r"(b), "=r"(c), "=r"(d) : "r"(addr) : "memory");
}
__device__ __forceinline__ void stmatrix_x4(uint32_t addr, uint32_t a, uint32_t b, uint32_t c, uint32_t d) {
  asm volatile("stmatrix.sync.aligned.m8n8.x4.shared.b16 [%0], {%1,%2,%3,%4};" ::"r"(addr), "r"(a), "r"(b), "r"(c), "r"(d) : "memory");
}
__device__ __forceinline__ void mma_16816(float (&c)[4], uint32_t a0, uint32_t a1, uint32_t a2, uint32_t a3, uint32_t b0, uint32_t b1) {
  asm(
      "mma.sync.aligned.m16n8k16.row.col.f32.bf16.bf16.f32 {%0,%1,%2,%3}, {%4,%5,%6,%7}, {%8,%9}, {%0,%1,%2,%3};"
      : "+f"(c[0]), "+f"(c[1]), "+f"(c[2]), "+f"(c[3])
      : "r"(a0), "r"(a1), "r"(a2), "r"(a3), "r"(b0), "r"(b1));
}
__device__ __forceinline__ uint32_t pack_bf16(float lo, float hi) {
  uint32_t r;
  asm("cvt.rn.bf16x2.f32 %0, %1, %2;" : "=r"(r) : "f"(hi), "f"(lo));
  return r;
}
__device__ __forceinline__ uint32_t hsub2_bf16(uint32_t a, uint32_t b) {
  uint32_t r;
  asm("sub.rn.bf16x2 %0, %1, %2;" : "=r"(r) : "r"(a), "r"(b));
  return r;
}
__device__ __forceinline__ float ex2f(float x) {
  float r;
  asm("ex2.approx.ftz.f32 %0, %1;" : "=f"(r) : "f"(x));
  return r;
}
__device__ __forceinline__ float rcpf(float x) {
  float r;
  asm("rcp.approx.ftz.f32 %0, %1;" : "=f"(r) : "f"(x));
  return r;
}
__device__ __forceinline__ void red_add_v2(float* p, float a, float b) {
  asm volatile("red.relaxed.gpu.global.add.v2.f32 [%0], {%1,%2};" ::"l"(p), "f"(a), "f"(b) : "memory");
}
__device__ __forceinline__ void red_add(float* p, float a) {
  asm volatile("red.relaxed.gpu.global.add.f32 [%0], %1;" ::"l"(p), "f"(a) : "memory");
}
__device__ __forceinline__ float phi_f(float t) {
  float e = ex2f(t * 1.4426950408889634f);
  return (t > 0.f ? t + 1.f : e) + 1e-6f;
}

#define R8(a, o) "+f"(a[o + 0]), "+f"(a[o + 1]), "+f"(a[o + 2]), "+f"(a[o + 3]), "+f"(a[o + 4]), "+f"(a[o + 5]), "+f"(a[o + 6]), "+f"(a[o + 7])

#define W8(a, o) "=f"(a[o + 0]), "=f"(a[o + 1]), "=f"(a[o + 2]), "=f"(a[o + 3]), "=f"(a[o + 4]), "=f"(a[o + 5]), "=f"(a[o + 6]), "=f"(a[o + 7])
#define D32 "{%0,%1,%2,%3,%4,%5,%6,%7,%8,%9,%10,%11,%12,%13,%14,%15,%16,%17,%18,%19,%20,%21,%22,%23,%24,%25,%26,%27,%28,%29,%30,%31}"
#define D36 "{%0,%1,%2,%3,%4,%5,%6,%7,%8,%9,%10,%11,%12,%13,%14,%15,%16,%17,%18,%19,%20,%21,%22,%23,%24,%25,%26,%27,%28,%29,%30,%31,%32,%33,%34,%35}"

constexpr uint32_t kHi128 = (1024u >> 4) | (1u << 30);
constexpr uint32_t kHi64 = (512u >> 4) | (2u << 30);
__host__ __device__ constexpr uint32_t desc_lo(uint32_t off, uint32_t lbo) { return (off >> 4) | ((lbo >> 4) << 16); }

template <bool ACC, uint32_t LO, uint32_t HI>
__device__ __forceinline__ void wgmma_n64_rs(float (&d)[32], uint32_t a0, uint32_t a1, uint32_t a2, uint32_t a3) {
  if (ACC) {
    asm volatile(
        "{\n.reg .pred p;\n.reg .b32 lo;\n.reg .b64 dd;\nsetp.eq.b32 p, 0, 0;\nmov.u32 lo, 64;\nadd.u32 lo, lo, %36;\nmov.b64 dd, {lo, %37};\n"
        "wgmma.mma_async.sync.aligned.m64n64k16.f32.bf16.bf16 " D32 ", {%32,%33,%34,%35}, dd, p, 1, 1, 1;\n}"
        : R8(d, 0), R8(d, 8), R8(d, 16), R8(d, 24)
        : "r"(a0), "r"(a1), "r"(a2), "r"(a3), "n"(LO), "n"(HI));
  } else {
    asm volatile(
        "{\n.reg .pred p;\n.reg .b32 lo;\n.reg .b64 dd;\nsetp.ne.b32 p, 0, 0;\nmov.u32 lo, 64;\nadd.u32 lo, lo, %36;\nmov.b64 dd, {lo, %37};\n"
        "wgmma.mma_async.sync.aligned.m64n64k16.f32.bf16.bf16 " D32 ", {%32,%33,%34,%35}, dd, p, 1, 1, 1;\n}"
        : W8(d, 0), W8(d, 8), W8(d, 16), W8(d, 24)
        : "r"(a0), "r"(a1), "r"(a2), "r"(a3), "n"(LO), "n"(HI));
  }
}
template <bool ACC, uint32_t LOA, uint32_t LOB>
__device__ __forceinline__ void wgmma_n72_ss_tt(float (&d)[36], uint32_t base) {
  if (ACC) {
    asm volatile(
        "{\n.reg .pred p;\n.reg .b32 lo;\n.reg .b64 da, db;\nsetp.eq.b32 p, 0, 0;\n"
        "add.u32 lo, %36, %37;\nmov.b64 da, {lo, %39};\nadd.u32 lo, %36, %38;\nmov.b64 db, {lo, %39};\n"
        "wgmma.mma_async.sync.aligned.m64n72k16.f32.bf16.bf16 " D36 ", da, db, p, 1, 1, 1, 1;\n}"
        : R8(d, 0), R8(d, 8), R8(d, 16), R8(d, 24), "+f"(d[32]), "+f"(d[33]), "+f"(d[34]), "+f"(d[35])
        : "r"(base), "n"(LOA), "n"(LOB), "n"(kHi128));
  } else {
    asm volatile(
        "{\n.reg .pred p;\n.reg .b32 lo;\n.reg .b64 da, db;\nsetp.ne.b32 p, 0, 0;\n"
        "add.u32 lo, %36, %37;\nmov.b64 da, {lo, %39};\nadd.u32 lo, %36, %38;\nmov.b64 db, {lo, %39};\n"
        "wgmma.mma_async.sync.aligned.m64n72k16.f32.bf16.bf16 " D36 ", da, db, p, 1, 1, 1, 1;\n}"
        : W8(d, 0), W8(d, 8), W8(d, 16), W8(d, 24), "=f"(d[32]), "=f"(d[33]), "=f"(d[34]), "=f"(d[35])
        : "r"(base), "n"(LOA), "n"(LOB), "n"(kHi128));
  }
}

#define INL __attribute__((always_inline))
template <int V> struct IC { static constexpr int value = V; };
template <int N, int I = 0, typename F>
__device__ __forceinline__ void static_for(F&& f) {
  if constexpr (I < N) { f(IC<I>{}); static_for<N, I + 1>(f); }
}

__host__ __device__ constexpr uint32_t stage_off(int st) {
  return st < 6 ? 131072u + (uint32_t)st * 16384u : (uint32_t)(st - 6) * 65536u + 49152u;
}

constexpr int B_FULL = 0, B_EMPTY = 8, B_XFULL = 16, B_XDONE = 32, B_KVREADY = 33, B_EV = 34, B_COUNT = 38;
constexpr uint32_t kBarOff = 229376;
constexpr int kSmemBytes = 229376 + 1024;

__host__ __device__ constexpr int p2_bi(int i) { return i < 7 ? 0 : i < 14 ? 1 : i < 16 ? 0 : i < 18 ? 1 : i / 9; }
__host__ __device__ constexpr int p2_kb(int i) { return i < 7 ? i : i < 14 ? i - 7 : i < 16 ? i - 7 : i < 18 ? i - 9 : i % 9; }

enum { K_NONE = 0, K_GU = 1, K_KV = 2, K_Q = 3 };

__global__ void __cluster_dims__(2, 1, 1) __launch_bounds__(384, 1)
fused_kernel(const __grid_constant__ CUtensorMap tm_x, const __grid_constant__ CUtensorMap tm_wqkv,
             const __grid_constant__ CUtensorMap tm_w1, const __grid_constant__ CUtensorMap tm_w3,
             const __grid_constant__ CUtensorMap tm_w2, const __grid_constant__ CUtensorMap tm_wo,
             const __nv_bfloat16* __restrict__ x, __nv_bfloat16* __restrict__ out) {
  const uint32_t sbase = smem_u32(smem_raw);
  const uint32_t bars = sbase + kBarOff;
  const int tid = threadIdx.x, lane = tid & 31;
  const int warp = __shfl_sync(0xffffffffu, tid >> 5, 0);
  const int cr = blockIdx.x & 1;
  const int r = (blockIdx.x >> 1) & 7, m = ((blockIdx.x >> 4) << 1) | cr, p = r >> 1, odd = r & 1;
#define BAR(i) (bars + 8u * (uint32_t)(i))
  if (tid == 256) {
    if ((sbase & 0x3FFFFu) != 1024u) __trap();
#pragma unroll
    for (int i = 0; i < 16; i++) mbar_init(BAR(B_XFULL + i), 1);
    fence_proxy_async();
#pragma unroll
    for (int b = 0; b < 8; b++) {
      mbar_expect_tx(BAR(B_XFULL + b), 8192);
      tma_load_2d(sbase + (b >> 3) * 65536 + (b & 7) * 8192, &tm_x, BAR(B_XFULL + b), (b & 7) * 64, m * 128 + (b >> 3) * 64);
    }
#pragma unroll
    for (int i = 0; i < 8; i++) { mbar_init(BAR(B_FULL + i), 1); mbar_init(BAR(B_EMPTY + i), 4); }
#pragma unroll
    for (int i = 0; i < 4; i++) mbar_init(BAR(B_EV + i), 4);
    mbar_init(BAR(B_XDONE), 2);
    mbar_init(BAR(B_KVREADY), 1);
    asm volatile("fence.mbarrier_init.release.cluster;" ::: "memory");
    fence_proxy_async();
  } else if (tid == 288) {
    prefetch_tmap(odd ? &tm_wqkv : (cr ? &tm_w3 : &tm_w1));
  }
  __syncwarp();
  asm volatile("barrier.cluster.arrive.relaxed.aligned;" ::: "memory");
  PROF((tid >> 7), 21);
  __syncthreads();

  if (warp >= 8) {
    asm volatile("setmaxnreg.dec.sync.aligned.u32 24;");
    PROF(2, 3);
    cluster_wait();
    PROF(2, 2);
    const uint32_t epoch = warp == 8 ? 0u : ld_relaxed(&g_epoch);
    const uint32_t tag = epoch + 1u;
    const int par = epoch & 1;
    if (warp == 8) {
      if (lane == 0) {
        int twp = 0;
        for (int j = 0; j < 10; j++) {
          const CUtensorMap* tm;
          int col;
          if (!odd) {
            if (j < 8) { tm = cr ? &tm_w3 : &tm_w1; col = 7 * p * 64 + j * 32; }
            else { tm = &tm_wqkv; col = 128 * p + (j - 8) * 64 + cr * 32; }
          } else {
            if (j < 4) { tm = &tm_wqkv; col = 512 + cr * 512 + 128 * p + j * 32; }
            else { tm = cr ? &tm_w3 : &tm_w1; col = (7 * p + 4) * 64 + (j - 4) * 32; }
          }
          const int t = j >> 1;
          for (int kq = 0; kq < 4; kq++) {
            if (j == 0 && kq == XPOS) {
              for (int b = 8; b < 16; b++) {
                mbar_expect_tx(BAR(B_XFULL + b), 8192);
                tma_load_2d(sbase + 65536 + (b & 7) * 8192, &tm_x, BAR(B_XFULL + b), (b & 7) * 64, m * 128 + 64);
              }
            }
            const int k = (j & 1) * 4 + kq;
            TWAIT(twp, mbar_wait(BAR(B_EMPTY + k), k < 6 ? ((t & 1) ^ 1) : (t & 1)));
            mbar_expect_tx(BAR(B_FULL + k), 16384);
            tma_load_2d_mc(sbase + stage_off(k) + cr * 8192, tm, BAR(B_FULL + k), col, kq * 128);
          }
        }
        for (int j = 0; j < 18; j++) {
          const int st = j & 7, n = 5 + (j >> 3);
          const int i = 2 * j + cr;
          const int bi = p2_bi(i), kb = p2_kb(i);
          const int col = odd * 256 + ((p + 1 + bi) & 3) * 64;
          const CUtensorMap* tmk;
          int row;
          if (!odd) {
            if (kb < 4) { tmk = &tm_w2; row = (7 * p + kb) * 64; }
            else if (kb < 6) { tmk = &tm_wo; row = (2 * p + kb - 4) * 64; }
            else { tmk = &tm_w2; row = (7 * p + 4 + kb - 6) * 64; }
          } else {
            if (kb < 3) { tmk = &tm_w2; row = (7 * p + 4 + kb) * 64; }
            else if (kb < 7) { tmk = &tm_w2; row = (7 * p + kb - 3) * 64; }
            else { tmk = &tm_wo; row = (2 * p + kb - 7) * 64; }
          }
          mbar_wait(BAR(B_EMPTY + st), st < 6 ? ((n & 1) ^ 1) : (n & 1));
          mbar_expect_tx(BAR(B_FULL + st), 16384);
          tma_load_2d_mc(sbase + stage_off(st) + cr * 8192, tmk, BAR(B_FULL + st), col, row);
        }
      }
    } else if (warp <= 10) {
      if (lane == 0 && odd) {
        const int w = warp - 9;
        for (int e = 0; e < 2; e++) {
          mbar_wait(BAR(B_EV + w * 2 + e), 0);
          __threadfence();
          atomicAdd(&g_kvcnt[p][0], 1u);
        }
      }
    } else {
      if (!odd) {
        {
          const int ce = m * 4 + p;
          float* kvn = &g_kv[par ^ 1][0][0][0];
          for (int i = lane; i < 128; i += 32) kvn[ce * 128 + i] = 0.f;
          if (lane < 8) (&g_z[par ^ 1][0][0])[ce * 8 + lane] = 0.f;
        }
        mbar_wait(BAR(B_XDONE), 0);
        wait_count_ge(&g_kvcnt[p][0], 64u * tag);
        const float* kvp = &g_kv[par][8 * p][0][0];
        const uint32_t dst0 = sbase + 5 * 8192, dst1 = dst0 + 65536;
#pragma unroll 4
        for (int i = 0; i < 16; i++) {
          float4 v = ldg_cg_f4(kvp + (i * 32 + lane) * 4);
          uint32_t lo = pack_bf16(v.x, v.y), hi = pack_bf16(v.z, v.w);
          uint32_t off = (uint32_t)(i * 32 + lane) * 8u;
          asm volatile("st.shared.v2.u32 [%0], {%1,%2};" ::"r"(dst0 + off), "r"(lo), "r"(hi) : "memory");
          asm volatile("st.shared.v2.u32 [%0], {%1,%2};" ::"r"(dst1 + off), "r"(lo), "r"(hi) : "memory");
        }
        {
          float4 v = ldg_cg_f4(&g_z[par][8 * p][0] + lane * 4);
          uint32_t lo = pack_bf16(v.x, v.y), hi = pack_bf16(v.z, v.w);
          uint32_t off = 4096u + (uint32_t)lane * 8u;
          asm volatile("st.shared.v2.u32 [%0], {%1,%2};" ::"r"(dst0 + off), "r"(lo), "r"(hi) : "memory");
          asm volatile("st.shared.v2.u32 [%0], {%1,%2};" ::"r"(dst1 + off), "r"(lo), "r"(hi) : "memory");
        }
        __syncwarp();
        if (lane == 0) mbar_arrive(BAR(B_KVREADY));
      }
    }
  } else {
    asm volatile("setmaxnreg.inc.sync.aligned.u32 240;");
    const int w = warp >> 2, wq = warp & 3, t128 = tid & 127;
    const int g = lane >> 2, tq = lane & 3;
    const uint32_t area = sbase + (uint32_t)w * 65536u;
    const bool elect = (t128 == 0);
    PROF(w, 22);
    const uint32_t dbase = (sbase & 0x3FFFFu) >> 4;
    uint32_t xoff = (uint32_t)((m * 4 + p) * 18 + w) * 8192u + (uint32_t)t128 * 16u;
    uint32_t stash = area + (uint32_t)t128 * 16u;
    const uint32_t epoch_c = ld_relaxed(&g_epoch);
    auto xptr = [&](int slot, int jj) INL { return (uint4*)((char*)g_xbuf + ((xoff & ~1u) + (uint32_t)slot * 16384u + (uint32_t)jj * 2048u)); };
    uint32_t A[144];
    float rs0, rs1;
    auto release = [&](int st) INL {
      if (elect) { mbar_arrive_cluster(BAR(B_EMPTY + st), 0); mbar_arrive_cluster(BAR(B_EMPTY + st), 1); }
    };

    {
      const int row = wq * 16 + (lane & 7) + ((lane >> 3) & 1) * 8;
      const uint32_t rbase = area + row * 128;
      float s0[2][4] = {}, q0[2][4] = {}, q1[2][4] = {};
      const uint32_t ones = 0x3F803F80u;
#pragma unroll
      for (int b = 0; b < 8; b++) {
        mbar_wait(BAR(B_XFULL + w * 8 + b), 0);
        if (b == 0) PROF(w, 23);
        if (b == 7) PROF(w, 24);
#pragma unroll
        for (int kk = 0; kk < 4; kk++) {
          const int i = (b * 4 + kk) * 4;
          ldmatrix_x4(rbase + b * 8192 + (((kk * 2 + (lane >> 4)) ^ (row & 7)) << 4), A[i], A[i + 1], A[i + 2], A[i + 3]);
        }
#pragma unroll
        for (int kk = 0; kk < 4; kk++) {
          const int i = (b * 4 + kk) * 4;
          mma_16816(s0[kk & 1], A[i], A[i + 1], A[i + 2], A[i + 3], ones, ones);
          mma_16816(q0[kk & 1], A[i], A[i + 1], A[i + 2], A[i + 3], A[i], A[i + 2]);
          mma_16816(q1[kk & 1], A[i], A[i + 1], A[i + 2], A[i + 3], A[i + 1], A[i + 3]);
        }
      }
      const float mean0 = (s0[0][0] + s0[1][0]) * (1.f / 512.f), mean1 = (s0[0][2] + s0[1][2]) * (1.f / 512.f);
      const uint32_t m0 = pack_bf16(mean0, mean0), m1 = pack_bf16(mean1, mean1);
#pragma unroll
      for (int i = 0; i < 128; i += 2) {
        A[i] = hsub2_bf16(A[i], m0);
        A[i + 1] = hsub2_bf16(A[i + 1], m1);
      }
      float v0 = (g & 1) ? q0[0][1] + q0[1][1] : q0[0][0] + q0[1][0];
      float v1 = (g & 1) ? q1[0][3] + q1[1][3] : q1[0][2] + q1[1][2];
      const int src = 4 * g + (g >> 1);
      v0 = __shfl_sync(0xffffffffu, v0, src);
      v1 = __shfl_sync(0xffffffffu, v1, src);
      v0 = fmaxf(v0 * (1.f / 512.f) - mean0 * mean0, 0.f);
      v1 = fmaxf(v1 * (1.f / 512.f) - mean1 * mean1, 0.f);
      rs0 = rsqrtf(v0 + 1e-5f);
      rs1 = rsqrtf(v1 + 1e-5f);
      bar_sync(1 + w, 128);
      cluster_wait();
      asm volatile("" : "+r"(xoff), "+r"(stash));
      PROF(w, 0);
      release(6); release(7);
      if (elect) mbar_arrive(BAR(B_XDONE));
    }

    auto gu_chunk = [&](float (&acc)[32], int f, int slot, int xslot, int hb) INL {
      const float c0 = rs0 * -1.4426950408889634f, c1 = rs1 * -1.4426950408889634f;
      const float q0 = rs0 * rs0, q1 = rs1 * rs1;
      uint32_t h[4];
#pragma unroll
      for (int i = 0; i < 4; i++) {
        const float ga = acc[f * 8 + 2 * i], gb = acc[f * 8 + 2 * i + 1];
        const float ua = acc[16 + f * 8 + 2 * i], ub = acc[16 + f * 8 + 2 * i + 1];
        const float c = (i & 1) ? c1 : c0, q = (i & 1) ? q1 : q0;
        const float da = 1.f + ex2f(fminf(ga * c, 60.f)), db = 1.f + ex2f(fminf(gb * c, 60.f));
        const float rq = rcpf(da * db) * q;
        h[i] = tagged(pack_bf16(ga * ua * (db * rq), gb * ub * (da * rq)), xoff & 1u);
      }
      const int jj = hb * 2 + f;
      sts_u4(stash + slot * 8192 + jj * 2048, h[0], h[1], h[2], h[3]);
      stg_u4(xptr(xslot, jj), h[0], h[1], h[2], h[3]);
    };
    auto kv_stage = [&](float (&acc)[32], int c, int hb) INL {
      const int srow = wq * 16 + (lane & 7) + ((lane >> 3) & 1) * 8;
      const uint32_t base = area + (3 + c) * 8192 + srow * 128;
#pragma unroll
      for (int jj = 0; jj < 2; jj++) {
        const int a = c * 16 + jj * 8;
        uint32_t r0, r1, r2, r3;
        if (c == 0) {
          r0 = pack_bf16(phi_f(acc[a] * rs0), phi_f(acc[a + 1] * rs0));
          r1 = pack_bf16(phi_f(acc[a + 2] * rs1), phi_f(acc[a + 3] * rs1));
          r2 = pack_bf16(phi_f(acc[a + 4] * rs0), phi_f(acc[a + 5] * rs0));
          r3 = pack_bf16(phi_f(acc[a + 6] * rs1), phi_f(acc[a + 7] * rs1));
        } else {
          r0 = pack_bf16(acc[a] * rs0, acc[a + 1] * rs0);
          r1 = pack_bf16(acc[a + 2] * rs1, acc[a + 3] * rs1);
          r2 = pack_bf16(acc[a + 4] * rs0, acc[a + 5] * rs0);
          r3 = pack_bf16(acc[a + 6] * rs1, acc[a + 7] * rs1);
        }
        stmatrix_x4(base + (((hb * 4 + jj * 2 + (lane >> 4)) ^ (srow & 7)) << 4), r0, r1, r2, r3);
      }
    };
    const uint32_t kvb = area + 5 * 8192;
    const uint32_t kvfrag = kvb + ((lane & 7) + ((lane >> 3) & 1) * 8) * 32 + (lane >> 4) * 16;
    auto signal = [&](int e) INL {
      __syncwarp();
      if (lane == 0) mbar_arrive(BAR(B_EV + w * 2 + e));
    };

    auto pp_wait = [&]() INL { bar_sync(3 + w, 256); };
    auto pp_pass = [&]() INL { bar_arrive(3 + (w ^ 1), 256); };
    if (w == 1) pp_pass();
    int tw1 = 0, tw2 = 0, tw3 = 0;
#pragma unroll 1
    for (int t = 0; t < 5; t++) {
      const uint32_t ph = t & 1;
      const int kind = odd ? (t < 2 ? K_KV : K_GU) : (t < 4 ? K_GU : K_Q);
      const int slot = odd ? t - 2 : t, xslot = odd ? t + 4 : t;
      static_for<2>([&](auto hc) INL {
        constexpr int hb = decltype(hc)::value;
        float acc[32];
        TWAIT(tw2, pp_wait());
        static_for<4>([&](auto kc) INL {
          constexpr int kq = decltype(kc)::value, k = hb * 4 + kq;
          TWAIT(tw1, mbar_wait(BAR(B_FULL + k), ph));
          wgmma_fence();
          static_for<8>([&](auto kkc) INL {
            constexpr int kk = decltype(kkc)::value, i = (kq * 8 + kk) * 4;
            wgmma_n64_rs<(kq | kk) != 0, desc_lo(stage_off(k) + kk * 1024, 8192), kHi64>(acc, A[i], A[i + 1], A[i + 2], A[i + 3]);
          });
          wgmma_commit();
          if (kq == 2) pp_pass();
          if (kq > 0) {
            wgmma_wait<1>();
            release(k - 1);
          }
        });
        TWAIT(tw3, wgmma_wait<0>());
        release(hb * 4 + 3);
        if (hb == 0 && t == 0) xoff |= (epoch_c & 1u) ^ 1u;
        if (kind == K_GU) {
          gu_chunk(acc, 0, slot, xslot, hb);
          gu_chunk(acc, 1, slot, xslot, hb);
        } else if (kind == K_KV) {
          if (hb == 0 && t == 0) sts_u4(stash + 5 * 8192, 0x3F803F80u, 0x3F803F80u, 0x3F803F80u, 0x3F803F80u);
          kv_stage(acc, 0, hb);
          kv_stage(acc, 1, hb);
          if (hb == 1) {
            float kvacc[36];
            const int par = (xoff & 1u) ^ 1u;
            fence_proxy_async();
            bar_sync(1 + w, 128);
            wgmma_fence();
            static_for<4>([&](auto kkc) INL {
              constexpr int kk = decltype(kkc)::value;
              wgmma_n72_ss_tt<kk != 0, desc_lo(3 * 8192 + kk * 2048, 0), desc_lo(4 * 8192 + kk * 2048, 8192 - kk * 2048)>(kvacc, dbase + w * 4096);
            });
            wgmma_commit();
            wgmma_wait<0>();
            float c[8];
#pragma unroll
            for (int i = 0; i < 8; i++)
              c[i] = wq == 0 ? kvacc[i] : (wq == 1 ? kvacc[8 + i] : (wq == 2 ? kvacc[16 + i] : kvacc[24 + i]));
            const int head = (2 * p + t) * 4 + wq;
            float* kvp = &g_kv[par][head][0][0];
            red_add_v2(kvp + g * 16 + 2 * tq, c[0], c[1]);
            red_add_v2(kvp + (g + 8) * 16 + 2 * tq, c[2], c[3]);
            red_add_v2(kvp + g * 16 + 8 + 2 * tq, c[4], c[5]);
            red_add_v2(kvp + (g + 8) * 16 + 8 + 2 * tq, c[6], c[7]);
            if (tq == 0) {
              red_add(&g_z[par][head][g], kvacc[32]);
              red_add(&g_z[par][head][g + 8], kvacc[34]);
            }
            signal(t);
          }
        } else {
          uint32_t aq[4][4];
#pragma unroll
          for (int c = 0; c < 4; c++) {
            const int a = c * 8;
            aq[c][0] = pack_bf16(phi_f(acc[a] * rs0), phi_f(acc[a + 1] * rs0));
            aq[c][1] = pack_bf16(phi_f(acc[a + 2] * rs1), phi_f(acc[a + 3] * rs1));
            aq[c][2] = pack_bf16(phi_f(acc[a + 4] * rs0), phi_f(acc[a + 5] * rs0));
            aq[c][3] = pack_bf16(phi_f(acc[a + 6] * rs1), phi_f(acc[a + 7] * rs1));
          }
          if (hb == 0) mbar_wait(BAR(B_KVREADY), 0);
          uint32_t Bf[4][6];
#pragma unroll
          for (int c = 0; c < 4; c++) {
            ldmatrix_x4_trans(kvfrag + (hb * 4 + c) * 512, Bf[c][0], Bf[c][1], Bf[c][2], Bf[c][3]);
            Bf[c][4] = lds_u32(kvb + 4096 + (hb * 4 + c) * 32 + tq * 4);
            Bf[c][5] = lds_u32(kvb + 4096 + (hb * 4 + c) * 32 + 16 + tq * 4);
          }
          float n0[4][4] = {}, n1[4][4] = {}, dn[4][4] = {};
#pragma unroll
          for (int c = 0; c < 4; c++) {
            mma_16816(dn[c], aq[c][0], aq[c][1], aq[c][2], aq[c][3], Bf[c][4], Bf[c][5]);
            mma_16816(n0[c], aq[c][0], aq[c][1], aq[c][2], aq[c][3], Bf[c][0], Bf[c][1]);
            mma_16816(n1[c], aq[c][0], aq[c][1], aq[c][2], aq[c][3], Bf[c][2], Bf[c][3]);
          }
          if (hb == 1) bar_sync(1 + w, 128);
          const uint32_t tg = xoff & 1u;
#pragma unroll
          for (int c = 0; c < 4; c++) {
            const float i0 = __fdividef(1.f, dn[c][0] + 1e-6f), i1 = __fdividef(1.f, dn[c][2] + 1e-6f);
            aq[c][0] = tagged(pack_bf16(n0[c][0] * i0, n0[c][1] * i0), tg);
            aq[c][1] = tagged(pack_bf16(n0[c][2] * i1, n0[c][3] * i1), tg);
            aq[c][2] = tagged(pack_bf16(n1[c][0] * i0, n1[c][1] * i0), tg);
            aq[c][3] = tagged(pack_bf16(n1[c][2] * i1, n1[c][3] * i1), tg);
          }
#pragma unroll
          for (int c = 0; c < 4; c++) {
            stg_u4(xptr(4 + hb, c), aq[c][0], aq[c][1], aq[c][2], aq[c][3]);
            sts_u4(stash + (4 + hb) * 8192 + c * 2048, aq[c][0], aq[c][1], aq[c][2], aq[c][3]);
          }
        }
      });
      PROF(w, 1 + 2 * t);
    }
    PROF(w, 10);

    const int n_own = odd ? 3 : 6;
    auto load_a = [&](int kb) INL {
      if (kb < n_own) {
#pragma unroll
        for (int jj = 0; jj < 4; jj++) {
          const int i = (kb * 4 + jj) * 4;
          lds_u4(stash + kb * 8192 + jj * 2048, A[i], A[i + 1], A[i + 2], A[i + 3]);
        }
      } else {
        const int xs = odd ? kb - 3 : kb;
#pragma unroll
        for (int jj = 0; jj < 4; jj++) {
          const int i = (kb * 4 + jj) * 4;
          ldg_poll_u4(xptr(xs, jj), A[i], A[i + 1], A[i + 2], A[i + 3]);
        }
      }
    };
    auto fix_a = [&](int kb) INL {
      if (kb >= n_own) {
        const int xs = odd ? kb - 3 : kb;
        recv_group<4>(xptr(xs, 0), &A[kb * 16], xoff & 1u);
      }
    };
#pragma unroll
    for (int kb = 0; kb < 7; kb++) load_a(kb);
    PROF(w, 11);

    const int orow = m * 128 + w * 64 + wq * 16 + g;
    const int ocol = odd * 256 + p * 64 + 2 * tq;
    float acc2[2][32];
    uint32_t poff = (uint32_t)((m * 2 + odd) * 24 + w) * 8192u + (uint32_t)t128 * 16u;
    asm volatile("" : "+r"(poff));
    auto pptr = [&](int dest, int sl) INL { return (uint4*)((char*)g_pbuf + (poff + (uint32_t)(dest * 3 + sl) * 16384u)); };
    uint32_t P[3][16];
    uint32_t xr[16];
    auto send = [&](float (&acc)[32], int bi) INL {
      uint4* dst = pptr((p + 1 + bi) & 3, bi);
#pragma unroll
      for (int q = 0; q < 4; q++)
        stg_u4(dst + q * 128, tagged(pack_bf16(acc[q * 8], acc[q * 8 + 1]), xoff & 1u), tagged(pack_bf16(acc[q * 8 + 2], acc[q * 8 + 3]), xoff & 1u),
               tagged(pack_bf16(acc[q * 8 + 4], acc[q * 8 + 5]), xoff & 1u), tagged(pack_bf16(acc[q * 8 + 6], acc[q * 8 + 7]), xoff & 1u));
      PROF(w, 12 + 2 * bi);
    };
    auto fetch = [&](int sl) INL {
#pragma unroll
      for (int q = 0; q < 4; q++) ldg_poll_u4(pptr(p, sl) + q * 128, P[sl][q * 4], P[sl][q * 4 + 1], P[sl][q * 4 + 2], P[sl][q * 4 + 3]);
    };
    static_for<36>([&](auto ic) INL {
      constexpr int i = decltype(ic)::value, bi = p2_bi(i), kb = p2_kb(i), j = i >> 1, st = j & 7;
      if (i == 9) { load_a(7); load_a(8); }
      if (i == 14) PROF(w, 2);
      if (bi == 0 && kb >= 3) fix_a(kb);
      if (i == 15) PROF(w, 4);
      if (i == 7) PROF(w, 6);
      if (i == 0 || i == 7 || i == 14 || i == 18 || i == 27) pp_wait();
      if ((i & 1) == 0) mbar_wait(BAR(B_FULL + st), (5 + (j >> 3)) & 1);
      wgmma_fence();
      static_for<4>([&](auto kkc) INL {
        constexpr int kk = decltype(kkc)::value, a = (kb * 4 + kk) * 4;
        wgmma_n64_rs<(kb | kk) != 0, desc_lo(stage_off(st) + (i & 1) * 8192 + kk * 2048, 0), kHi128>(acc2[bi & 1], A[a], A[a + 1], A[a + 2], A[a + 3]);
      });
      wgmma_commit();
      if (i == 4 || i == 11 || i == 15 || i == 24 || (i == 33 && w == 0)) pp_pass();
      if (i > 0) {
        wgmma_wait<1>();
        if ((i & 1) == 0 && j - 1 <= 9) release((j - 1) & 7);
      }
      if constexpr (i == 17) { send(acc2[0], 0); wgmma_wait<0>(); send(acc2[1], 1); }
      if constexpr (i == 26) { wgmma_wait<0>(); send(acc2[0], 2); }
      if constexpr (i == 29) fetch(0);
      if constexpr (i == 30) fetch(1);
      if constexpr (i == 28) {
#pragma unroll
        for (int q = 0; q < 8; q++) {
          xr[2 * q] = __ldg((const uint32_t*)(x + (size_t)orow * kD + ocol + q * 8));
          xr[2 * q + 1] = __ldg((const uint32_t*)(x + (size_t)(orow + 8) * kD + ocol + q * 8));
        }
      }
      if constexpr (i == 32) fetch(2);
    });
#pragma unroll
    for (int sl = 0; sl < 3; sl++) { PROF(w, 13 + 2 * sl); recv_group<4>(pptr(p, sl), &P[sl][0], xoff & 1u); }
    wgmma_wait<0>();
    PROF(w, 18);
#pragma unroll
    for (int q = 0; q < 8; q++) {
      float rr[4];
      rr[0] = acc2[1][q * 4 + 0] + __uint_as_float(xr[2 * q] << 16);
      rr[1] = acc2[1][q * 4 + 1] + __uint_as_float(xr[2 * q] & 0xffff0000u);
      rr[2] = acc2[1][q * 4 + 2] + __uint_as_float(xr[2 * q + 1] << 16);
      rr[3] = acc2[1][q * 4 + 3] + __uint_as_float(xr[2 * q + 1] & 0xffff0000u);
#pragma unroll
      for (int sl = 0; sl < 3; sl++) {
        rr[0] += __uint_as_float(P[sl][2 * q] << 16);
        rr[1] += __uint_as_float(P[sl][2 * q] & 0xffff0000u);
        rr[2] += __uint_as_float(P[sl][2 * q + 1] << 16);
        rr[3] += __uint_as_float(P[sl][2 * q + 1] & 0xffff0000u);
      }
      *(uint32_t*)(out + (size_t)orow * kD + ocol + q * 8) = pack_bf16(rr[0], rr[1]);
      *(uint32_t*)(out + (size_t)(orow + 8) * kD + ocol + q * 8) = pack_bf16(rr[2], rr[3]);
    }
    PROF(w, 19);
    if (tid == 0) {
      const uint32_t old = atomicAdd(&g_done, 1u);
      if ((old & 127u) == 127u) st_relaxed(&g_epoch, ld_relaxed(&g_epoch) + 1u);
    }
  }
#undef BAR
}

typedef CUresult (*EncodeFn)(CUtensorMap*, CUtensorMapDataType, cuuint32_t, void*, const cuuint64_t*, const cuuint64_t*,
                             const cuuint32_t*, const cuuint32_t*, CUtensorMapInterleave, CUtensorMapSwizzle,
                             CUtensorMapL2promotion, CUtensorMapFloatOOBfill);

void make_map(EncodeFn enc, CUtensorMap* tm, const void* ptr, int rows, int cols, bool narrow) {
  cuuint64_t gd[2] = {(cuuint64_t)cols, (cuuint64_t)rows};
  cuuint64_t gs[1] = {(cuuint64_t)cols * 2};
  cuuint32_t bd[2] = {narrow ? 32u : 64u, narrow ? 128u : 64u};
  cuuint32_t es[2] = {1, 1};
  enc(tm, CU_TENSOR_MAP_DATA_TYPE_BFLOAT16, 2, const_cast<void*>(ptr), gd, gs, bd, es, CU_TENSOR_MAP_INTERLEAVE_NONE,
      narrow ? CU_TENSOR_MAP_SWIZZLE_64B : CU_TENSOR_MAP_SWIZZLE_128B, CU_TENSOR_MAP_L2_PROMOTION_L2_256B, CU_TENSOR_MAP_FLOAT_OOB_FILL_NONE);
}

}

extern "C" void kernel_launch(void* const* d_in, const int* in_sizes, int n_in, void* d_out, int out_size) {
  static EncodeFn enc = nullptr;
  if (!enc) {
    void* fn = nullptr;
    cudaDriverEntryPointQueryResult qr;
    cudaGetDriverEntryPoint("cuTensorMapEncodeTiled", &fn, cudaEnableDefault, &qr);
    enc = (EncodeFn)fn;
    cudaFuncSetAttribute(fused_kernel, cudaFuncAttributeMaxDynamicSharedMemorySize, kSmemBytes);
  }
  CUtensorMap tm_x, tm_wqkv, tm_w1, tm_w3, tm_w2, tm_wo;
  make_map(enc, &tm_x, d_in[0], kS, kD, false);
  make_map(enc, &tm_wqkv, d_in[1], kD, 3 * kD, true);
  make_map(enc, &tm_wo, d_in[2], kD, kD, false);
  make_map(enc, &tm_w1, d_in[4], kD, kF, true);
  make_map(enc, &tm_w3, d_in[5], kD, kF, true);
  make_map(enc, &tm_w2, d_in[6], kF, kD, false);
  fused_kernel<<<128, 384, kSmemBytes>>>(tm_x, tm_wqkv, tm_w1, tm_w3, tm_w2, tm_wo, (const __nv_bfloat16*)d_in[0],
                                         (__nv_bfloat16*)d_out);
}
```

```cpp
#include <cuda_runtime.h>
#include <cuda_bf16.h>
#include <cuda.h>
#include <stdint.h>

extern __shared__ __align__(1024) uint8_t smem_raw[];

namespace {

constexpr int kS = 2048, kD = 512, kF = 1792;
#define XPOS 1
constexpr uint32_t kSpinLimit = 1u << 22;

__device__ uint4    g_xbuf[16][4][9][2][4][128];
__device__ uint4    g_pbuf[16][2][4][3][2][4][128];
__device__ float    g_kv[2][32][16][16];
__device__ float    g_z[2][32][16];
__device__ uint32_t g_kvcnt[4][32];
__device__ uint32_t g_epoch;
__device__ uint32_t g_done;
#define PROF(wg, i) do {} while (0)
#define TWAIT(acc, stmt) do { stmt; } while (0)

__device__ __forceinline__ uint32_t smem_u32(const void* p) { return (uint32_t)__cvta_generic_to_shared(p); }
__device__ __forceinline__ void mbar_init(uint32_t bar, uint32_t cnt) {
  asm volatile("mbarrier.init.shared::cta.b64 [%0], %1;" ::"r"(bar), "r"(cnt) : "memory");
}
__device__ __forceinline__ void mbar_expect_tx(uint32_t bar, uint32_t bytes) {
  asm volatile("mbarrier.arrive.expect_tx.shared::cta.b64 _, [%0], %1;" ::"r"(bar), "r"(bytes) : "memory");
}
__device__ __forceinline__ void mbar_arrive(uint32_t bar) {
  asm volatile("mbarrier.arrive.shared::cta.b64 _, [%0];" ::"r"(bar) : "memory");
}
__device__ __forceinline__ void mbar_wait(uint32_t bar, uint32_t parity) {
  asm volatile(
      "{\n.reg .pred p;\n"
      "LAB_WAIT:\n"
      "mbarrier.try_wait.parity.shared::cta.b64 p, [%0], %1;\n"
      "@p bra DONE;\n"
      "bra LAB_WAIT;\n"
      "DONE:\n}" ::"r"(bar), "r"(parity) : "memory");
}
__device__ __forceinline__ void tma_load_2d(uint32_t dst, const CUtensorMap* tm, uint32_t bar, int c0, int c1) {
  asm volatile(
      "cp.async.bulk.tensor.2d.shared::cluster.global.mbarrier::complete_tx::bytes [%0], [%1, {%3, %4}], [%2];" ::"r"(dst),
      "l"(tm), "r"(bar), "r"(c0), "r"(c1)
      : "memory");
}
__device__ __forceinline__ void tma_load_2d_mc(uint32_t dst, const CUtensorMap* tm, uint32_t bar, int c0, int c1) {
  asm volatile(
      "cp.async.bulk.tensor.2d.shared::cluster.global.mbarrier::complete_tx::bytes.multicast::cluster [%0], [%1, {%3, %4}], [%2], %5;" ::"r"(dst),
      "l"(tm), "r"(bar), "r"(c0), "r"(c1), "h"((uint16_t)3)
      : "memory");
}
__device__ __forceinline__ void mbar_arrive_cluster(uint32_t bar, uint32_t cta) {
  asm volatile("{\n.reg .b32 ra;\nmapa.shared::cluster.u32 ra, %0, %1;\nmbarrier.arrive.shared::cluster.b64 _, [ra];\n}" ::"r"(bar), "r"(cta) : "memory");
}
__device__ __forceinline__ void prefetch_tmap(const CUtensorMap* tm) {
  asm volatile("prefetch.tensormap [%0];" ::"l"(tm) : "memory");
}
__device__ __forceinline__ void wgmma_fence() { asm volatile("wgmma.fence.sync.aligned;" ::: "memory"); }
__device__ __forceinline__ void wgmma_commit() { asm volatile("wgmma.commit_group.sync.aligned;" ::: "memory"); }
template <int N>
__device__ __forceinline__ void wgmma_wait() { asm volatile("wgmma.wait_group.sync.aligned %0;" ::"n"(N) : "memory"); }
__device__ __forceinline__ void bar_sync(int id, int n) { asm volatile("bar.sync %0, %1;" ::"r"(id), "r"(n) : "memory"); }
__device__ __forceinline__ void bar_arrive(int id, int n) { asm volatile("bar.arrive %0, %1;" ::"r"(id), "r"(n) : "memory"); }
__device__ __forceinline__ void fence_proxy_async() { asm volatile("fence.proxy.async.shared::cta;" ::: "memory"); }

__device__ __forceinline__ uint32_t ld_acquire(const uint32_t* p) {
  uint32_t v;
  asm volatile("ld.acquire.gpu.global.u32 %0, [%1];" : "=r"(v) : "l"(p) : "memory");
  return v;
}
__device__ __forceinline__ uint32_t ld_relaxed(const uint32_t* p) {
  uint32_t v;
  asm volatile("ld.relaxed.gpu.global.u32 %0, [%1];" : "=r"(v) : "l"(p));
  return v;
}
__device__ __forceinline__ void cluster_wait() { asm volatile("barrier.cluster.wait.aligned;" ::: "memory"); }
__device__ __forceinline__ void st_relaxed(uint32_t* p, uint32_t v) {
  asm volatile("st.relaxed.gpu.global.u32 [%0], %1;" ::"l"(p), "r"(v) : "memory");
}
__device__ __forceinline__ void wait_flag_eq(const uint32_t* p, uint32_t val) {
  uint32_t it = 0;
  while (ld_acquire(p) != val) {
    if (++it > kSpinLimit) break;
  }
}
__device__ __forceinline__ void wait_count_ge(const uint32_t* p, uint32_t val) {
  uint32_t it = 0;
  while ((int32_t)(ld_acquire(p) - val) < 0) {
    __nanosleep(64);
    if (++it > kSpinLimit) break;
  }
}
__device__ __forceinline__ void ldg_poll_u4(const void* p, uint32_t& a, uint32_t& b, uint32_t& c, uint32_t& d) {
  asm volatile("ld.relaxed.gpu.global.v4.u32 {%0,%1,%2,%3}, [%4];" : "=r"(a), "=r"(b), "=r"(c), "=r"(d) : "l"(p) : "memory");
}
template <int N>
__device__ __forceinline__ void recv_group(const uint4* p, uint32_t* r, uint32_t tag) {
  uint32_t it = 0;
  while (true) {
    uint32_t bad = 0u;
#pragma unroll
    for (int i = 0; i < 4 * N; i++) bad |= r[i] ^ tag;
    if (!__any_sync(0xffffffffu, (bad & 1u) != 0u) || ++it > kSpinLimit) break;
#pragma unroll
    for (int q = 0; q < N; q++) ldg_poll_u4(p + q * 128, r[q * 4], r[q * 4 + 1], r[q * 4 + 2], r[q * 4 + 3]);
  }
}
__device__ __forceinline__ uint32_t tagged(uint32_t v, uint32_t tag) { return (v & ~1u) | tag; }
__device__ __forceinline__ float4 ldg_cg_f4(const void* p) {
  float4 v;
  asm volatile("ld.global.cg.v4.f32 {%0,%1,%2,%3}, [%4];" : "=f"(v.x), "=f"(v.y), "=f"(v.z), "=f"(v.w) : "l"(p) : "memory");
  return v;
}
__device__ __forceinline__ void stg_u4(void* p, uint32_t a, uint32_t b, uint32_t c, uint32_t d) {
  asm volatile("st.global.v4.u32 [%0], {%1,%2,%3,%4};" ::"l"(p), "r"(a), "r"(b), "r"(c), "r"(d) : "memory");
}
__device__ __forceinline__ void stg_f4(void* p, float a, float b, float c, float d) {
  asm volatile("st.global.v4.f32 [%0], {%1,%2,%3,%4};" ::"l"(p), "f"(a), "f"(b), "f"(c), "f"(d) : "memory");
}
__device__ __forceinline__ void sts_u4(uint32_t addr, uint32_t a, uint32_t b, uint32_t c, uint32_t d) {
  asm volatile("st.shared.v4.u32 [%0], {%1,%2,%3,%4};" ::"r"(addr), "r"(a), "r"(b), "r"(c), "r"(d) : "memory");
}
__device__ __forceinline__ void lds_u4(uint32_t addr, uint32_t& a, uint32_t& b, uint32_t& c, uint32_t& d) {
  asm volatile("ld.shared.v4.u32 {%0,%1,%2,%3}, [%4];" : "=r"(a), "=r"(b), "=r"(c), "=r"(d) : "r"(addr) : "memory");
}
__device__ __forceinline__ uint32_t lds_u32(uint32_t addr) {
  uint32_t v;
  asm volatile("ld.shared.u32 %0, [%1];" : "=r"(v) : "r"(addr) : "memory");
  return v;
}
__device__ __forceinline__ void ldmatrix_x4(uint32_t addr, uint32_t& a, uint32_t& b, uint32_t& c, uint32_t& d) {
  asm volatile("ldmatrix.sync.aligned.m8n8.x4.shared.b16 {%0,%1,%2,%3}, [%4];" : "=r"(a), "=r"(b), "=r"(c), "=r"(d) : "r"(addr) : "memory");
}
__device__ __forceinline__ void ldmatrix_x4_trans(uint32_t addr, uint32_t& a, uint32_t& b, uint32_t& c, uint32_t& d) {
  asm volatile("ldmatrix.sync.aligned.m8n8.x4.trans.shared.b16 {%0,%1,%2,%3}, [%4];" : "=r"(a), "=r"(b), "=r"(c), "=r"(d) : "r"(addr) : "memory");
}
__device__ __forceinline__ void stmatrix_x4(uint32_t addr, uint32_t a, uint32_t b, uint32_t c, uint32_t d) {
  asm volatile("stmatrix.sync.aligned.m8n8.x4.shared.b16 [%0], {%1,%2,%3,%4};" ::"r"(addr), "r"(a), "r"(b), "r"(c), "r"(d) : "memory");
}
__device__ __forceinline__ void mma_16816(float (&c)[4], uint32_t a0, uint32_t a1, uint32_t a2, uint32_t a3, uint32_t b0, uint32_t b1) {
  asm(
      "mma.sync.aligned.m16n8k16.row.col.f32.bf16.bf16.f32 {%0,%1,%2,%3}, {%4,%5,%6,%7}, {%8,%9}, {%0,%1,%2,%3};"
      : "+f"(c[0]), "+f"(c[1]), "+f"(c[2]), "+f"(c[3])
      : "r"(a0), "r"(a1), "r"(a2), "r"(a3), "r"(b0), "r"(b1));
}
__device__ __forceinline__ uint32_t pack_bf16(float lo, float hi) {
  uint32_t r;
  asm("cvt.rn.bf16x2.f32 %0, %1, %2;" : "=r"(r) : "f"(hi), "f"(lo));
  return r;
}
__device__ __forceinline__ uint32_t hsub2_bf16(uint32_t a, uint32_t b) {
  uint32_t r;
  asm("sub.rn.bf16x2 %0, %1, %2;" : "=r"(r) : "r"(a), "r"(b));
  return r;
}
__device__ __forceinline__ float ex2f(float x) {
  float r;
  asm("ex2.approx.ftz.f32 %0, %1;" : "=f"(r) : "f"(x));
  return r;
}
__device__ __forceinline__ float rcpf(float x) {
  float r;
  asm("rcp.approx.ftz.f32 %0, %1;" : "=f"(r) : "f"(x));
  return r;
}
__device__ __forceinline__ void red_add_v2(float* p, float a, float b) {
  asm volatile("red.relaxed.gpu.global.add.v2.f32 [%0], {%1,%2};" ::"l"(p), "f"(a), "f"(b) : "memory");
}
__device__ __forceinline__ void red_add(float* p, float a) {
  asm volatile("red.relaxed.gpu.global.add.f32 [%0], %1;" ::"l"(p), "f"(a) : "memory");
}
__device__ __forceinline__ float phi_f(float t) {
  float e = ex2f(t * 1.4426950408889634f);
  return (t > 0.f ? t + 1.f : e) + 1e-6f;
}

#define R8(a, o) "+f"(a[o + 0]), "+f"(a[o + 1]), "+f"(a[o + 2]), "+f"(a[o + 3]), "+f"(a[o + 4]), "+f"(a[o + 5]), "+f"(a[o + 6]), "+f"(a[o + 7])

#define W8(a, o) "=f"(a[o + 0]), "=f"(a[o + 1]), "=f"(a[o + 2]), "=f"(a[o + 3]), "=f"(a[o + 4]), "=f"(a[o + 5]), "=f"(a[o + 6]), "=f"(a[o + 7])
#define D32 "{%0,%1,%2,%3,%4,%5,%6,%7,%8,%9,%10,%11,%12,%13,%14,%15,%16,%17,%18,%19,%20,%21,%22,%23,%24,%25,%26,%27,%28,%29,%30,%31}"
#define D36 "{%0,%1,%2,%3,%4,%5,%6,%7,%8,%9,%10,%11,%12,%13,%14,%15,%16,%17,%18,%19,%20,%21,%22,%23,%24,%25,%26,%27,%28,%29,%30,%31,%32,%33,%34,%35}"

constexpr uint32_t kHi128 = (1024u >> 4) | (1u << 30);
constexpr uint32_t kHi64 = (512u >> 4) | (2u << 30);
__host__ __device__ constexpr uint32_t desc_lo(uint32_t off, uint32_t lbo) { return (off >> 4) | ((lbo >> 4) << 16); }

template <bool ACC, uint32_t LO, uint32_t HI>
__device__ __forceinline__ void wgmma_n64_rs(float (&d)[32], uint32_t a0, uint32_t a1, uint32_t a2, uint32_t a3) {
  if (ACC) {
    asm volatile(
        "{\n.reg .pred p;\n.reg .b32 lo;\n.reg .b64 dd;\nsetp.eq.b32 p, 0, 0;\nmov.u32 lo, 64;\nadd.u32 lo, lo, %36;\nmov.b64 dd, {lo, %37};\n"
        "wgmma.mma_async.sync.aligned.m64n64k16.f32.bf16.bf16 " D32 ", {%32,%33,%34,%35}, dd, p, 1, 1, 1;\n}"
        : R8(d, 0), R8(d, 8), R8(d, 16), R8(d, 24)
        : "r"(a0), "r"(a1), "r"(a2), "r"(a3), "n"(LO), "n"(HI));
  } else {
    asm volatile(
        "{\n.reg .pred p;\n.reg .b32 lo;\n.reg .b64 dd;\nsetp.ne.b32 p, 0, 0;\nmov.u32 lo, 64;\nadd.u32 lo, lo, %36;\nmov.b64 dd, {lo, %37};\n"
        "wgmma.mma_async.sync.aligned.m64n64k16.f32.bf16.bf16 " D32 ", {%32,%33,%34,%35}, dd, p, 1, 1, 1;\n}"
        : W8(d, 0), W8(d, 8), W8(d, 16), W8(d, 24)
        : "r"(a0), "r"(a1), "r"(a2), "r"(a3), "n"(LO), "n"(HI));
  }
}
template <bool ACC, uint32_t LOA, uint32_t LOB>
__device__ __forceinline__ void wgmma_n72_ss_tt(float (&d)[36], uint32_t base) {
  if (ACC) {
    asm volatile(
        "{\n.reg .pred p;\n.reg .b32 lo;\n.reg .b64 da, db;\nsetp.eq.b32 p, 0, 0;\n"
        "add.u32 lo, %36, %37;\nmov.b64 da, {lo, %39};\nadd.u32 lo, %36, %38;\nmov.b64 db, {lo, %39};\n"
        "wgmma.mma_async.sync.aligned.m64n72k16.f32.bf16.bf16 " D36 ", da, db, p, 1, 1, 1, 1;\n}"
        : R8(d, 0), R8(d, 8), R8(d, 16), R8(d, 24), "+f"(d[32]), "+f"(d[33]), "+f"(d[34]), "+f"(d[35])
        : "r"(base), "n"(LOA), "n"(LOB), "n"(kHi128));
  } else {
    asm volatile(
        "{\n.reg .pred p;\n.reg .b32 lo;\n.reg .b64 da, db;\nsetp.ne.b32 p, 0, 0;\n"
        "add.u32 lo, %36, %37;\nmov.b64 da, {lo, %39};\nadd.u32 lo, %36, %38;\nmov.b64 db, {lo, %39};\n"
        "wgmma.mma_async.sync.aligned.m64n72k16.f32.bf16.bf16 " D36 ", da, db, p, 1, 1, 1, 1;\n}"
        : W8(d, 0), W8(d, 8), W8(d, 16), W8(d, 24), "=f"(d[32]), "=f"(d[33]), "=f"(d[34]), "=f"(d[35])
        : "r"(base), "n"(LOA), "n"(LOB), "n"(kHi128));
  }
}

#define INL __attribute__((always_inline))
template <int V> struct IC { static constexpr int value = V; };
template <int N, int I = 0, typename F>
__device__ __forceinline__ void static_for(F&& f) {
  if constexpr (I < N) { f(IC<I>{}); static_for<N, I + 1>(f); }
}

__host__ __device__ constexpr uint32_t stage_off(int st) {
  return st < 6 ? 131072u + (uint32_t)st * 16384u : (uint32_t)(st - 6) * 65536u + 49152u;
}

constexpr int B_FULL = 0, B_EMPTY = 8, B_XFULL = 16, B_XDONE = 32, B_KVREADY = 33, B_EV = 34, B_COUNT = 38;
constexpr uint32_t kBarOff = 229376;
constexpr int kSmemBytes = 229376 + 1024;

__host__ __device__ constexpr int p2_bi(int i) { return i < 7 ? 0 : i < 14 ? 1 : i < 16 ? 0 : i < 18 ? 1 : i / 9; }
__host__ __device__ constexpr int p2_kb(int i) { return i < 7 ? i : i < 14 ? i - 7 : i < 16 ? i - 7 : i < 18 ? i - 9 : i % 9; }

enum { K_NONE = 0, K_GU = 1, K_KV = 2, K_Q = 3 };

__global__ void __cluster_dims__(2, 1, 1) __launch_bounds__(384, 1)
fused_kernel(const __grid_constant__ CUtensorMap tm_x, const __grid_constant__ CUtensorMap tm_wqkv,
             const __grid_constant__ CUtensorMap tm_w1, const __grid_constant__ CUtensorMap tm_w3,
             const __grid_constant__ CUtensorMap tm_w2, const __grid_constant__ CUtensorMap tm_wo,
             const __nv_bfloat16* __restrict__ x, __nv_bfloat16* __restrict__ out) {
  const uint32_t sbase = smem_u32(smem_raw);
  const uint32_t bars = sbase + kBarOff;
  const int tid = threadIdx.x, lane = tid & 31;
  const int warp = __shfl_sync(0xffffffffu, tid >> 5, 0);
  const int cr = blockIdx.x & 1;
  const int r = (blockIdx.x >> 1) & 7, m = ((blockIdx.x >> 4) << 1) | cr, p = r >> 1, odd = r & 1;
#define BAR(i) (bars + 8u * (uint32_t)(i))
  if (tid == 256) {
    if ((sbase & 0x3FFFFu) != 1024u) __trap();
#pragma unroll
    for (int i = 0; i < 16; i++) mbar_init(BAR(B_XFULL + i), 1);
    fence_proxy_async();
#pragma unroll
    for (int b = 0; b < 8; b++) {
      mbar_expect_tx(BAR(B_XFULL + b), 8192);
      tma_load_2d(sbase + (b >> 3) * 65536 + (b & 7) * 8192, &tm_x, BAR(B_XFULL + b), (b & 7) * 64, m * 128 + (b >> 3) * 64);
    }
#pragma unroll
    for (int i = 0; i < 8; i++) { mbar_init(BAR(B_FULL + i), 1); mbar_init(BAR(B_EMPTY + i), 4); }
#pragma unroll
    for (int i = 0; i < 4; i++) mbar_init(BAR(B_EV + i), 4);
    mbar_init(BAR(B_XDONE), 2);
    mbar_init(BAR(B_KVREADY), 3);
    asm volatile("fence.mbarrier_init.release.cluster;" ::: "memory");
    fence_proxy_async();
  } else if (tid == 288) {
    prefetch_tmap(odd ? &tm_wqkv : (cr ? &tm_w3 : &tm_w1));
  }
  __syncwarp();
  asm volatile("barrier.cluster.arrive.relaxed.aligned;" ::: "memory");
  PROF((tid >> 7), 21);
  __syncthreads();

  if (warp >= 8) {
    asm volatile("setmaxnreg.dec.sync.aligned.u32 24;");
    PROF(2, 3);
    cluster_wait();
    PROF(2, 2);
    const uint32_t epoch = warp == 8 ? 0u : ld_relaxed(&g_epoch);
    const uint32_t tag = epoch + 1u;
    const int par = epoch & 1;
    if (warp == 8) {
      if (lane == 0) {
        int twp = 0;
        for (int j = 0; j < 10; j++) {
          const CUtensorMap* tm;
          int col;
          if (!odd) {
            if (j < 8) { tm = cr ? &tm_w3 : &tm_w1; col = 7 * p * 64 + j * 32; }
            else { tm = &tm_wqkv; col = 128 * p + (j - 8) * 64 + cr * 32; }
          } else {
            if (j < 4) { tm = &tm_wqkv; col = 512 + cr * 512 + 128 * p + j * 32; }
            else { tm = cr ? &tm_w3 : &tm_w1; col = (7 * p + 4) * 64 + (j - 4) * 32; }
          }
          const int t = j >> 1;
          for (int kq = 0; kq < 4; kq++) {
            if (j == 0 && kq == XPOS) {
              for (int b = 8; b < 16; b++) {
                mbar_expect_tx(BAR(B_XFULL + b), 8192);
                tma_load_2d(sbase + 65536 + (b & 7) * 8192, &tm_x, BAR(B_XFULL + b), (b & 7) * 64, m * 128 + 64);
              }
            }
            const int k = (j & 1) * 4 + kq;
            TWAIT(twp, mbar_wait(BAR(B_EMPTY + k), k < 6 ? ((t & 1) ^ 1) : (t & 1)));
            mbar_expect_tx(BAR(B_FULL + k), 16384);
            tma_load_2d_mc(sbase + stage_off(k) + cr * 8192, tm, BAR(B_FULL + k), col, kq * 128);
          }
        }
        for (int j = 0; j < 18; j++) {
          const int st = j & 7, n = 5 + (j >> 3);
          const int i = 2 * j + cr;
          const int bi = p2_bi(i), kb = p2_kb(i);
          const int col = odd * 256 + ((p + 1 + bi) & 3) * 64;
          const CUtensorMap* tmk;
          int row;
          if (!odd) {
            if (kb < 4) { tmk = &tm_w2; row = (7 * p + kb) * 64; }
            else if (kb < 6) { tmk = &tm_wo; row = (2 * p + kb - 4) * 64; }
            else { tmk = &tm_w2; row = (7 * p + 4 + kb - 6) * 64; }
          } else {
            if (kb < 3) { tmk = &tm_w2; row = (7 * p + 4 + kb) * 64; }
            else if (kb < 7) { tmk = &tm_w2; row = (7 * p + kb - 3) * 64; }
            else { tmk = &tm_wo; row = (2 * p + kb - 7) * 64; }
          }
          mbar_wait(BAR(B_EMPTY + st), st < 6 ? ((n & 1) ^ 1) : (n & 1));
          mbar_expect_tx(BAR(B_FULL + st), 16384);
          tma_load_2d_mc(sbase + stage_off(st) + cr * 8192, tmk, BAR(B_FULL + st), col, row);
        }
      }
    } else if (odd) {
      if (lane == 0 && warp <= 10) {
        const int w = warp - 9;
        for (int e = 0; e < 2; e++) {
          mbar_wait(BAR(B_EV + w * 2 + e), 0);
          __threadfence();
          atomicAdd(&g_kvcnt[p][0], 1u);
        }
      }
    } else {
      const int hl = tid - 288;
      {
        const int ce = m * 4 + p;
        if (hl < 32) *(float4*)(&g_kv[par ^ 1][0][0][0] + ce * 128 + hl * 4) = make_float4(0.f, 0.f, 0.f, 0.f);
        else if (hl < 40) (&g_z[par ^ 1][0][0])[ce * 8 + hl - 32] = 0.f;
      }
      mbar_wait(BAR(B_XDONE), 0);
      wait_count_ge(&g_kvcnt[p][0], 64u * tag);
      const float* kvp = &g_kv[par][8 * p][0][0];
      const float* zp = &g_z[par][8 * p][0];
      const uint32_t dst0 = sbase + 5 * 8192, dst1 = dst0 + 65536;
#pragma unroll
      for (int h2 = 0; h2 < 2; h2++) {
        float4 v[3];
#pragma unroll
        for (int i = 0; i < 3; i++) {
          const int c = (h2 * 3 + i) * 96 + hl;
          v[i] = c < 512 ? ldg_cg_f4(kvp + c * 4) : (c < 544 ? ldg_cg_f4(zp + (c - 512) * 4) : make_float4(0.f, 0.f, 0.f, 0.f));
        }
#pragma unroll
        for (int i = 0; i < 3; i++) {
          const int c = (h2 * 3 + i) * 96 + hl;
          if (c < 544) {
            const uint32_t lo = pack_bf16(v[i].x, v[i].y), hi = pack_bf16(v[i].z, v[i].w);
            asm volatile("st.shared.v2.u32 [%0], {%1,%2};" ::"r"(dst0 + c * 8), "r"(lo), "r"(hi) : "memory");
            asm volatile("st.shared.v2.u32 [%0], {%1,%2};" ::"r"(dst1 + c * 8), "r"(lo), "r"(hi) : "memory");
          }
        }
      }
      __syncwarp();
      if (lane == 0) mbar_arrive(BAR(B_KVREADY));
    }
  } else {
    asm volatile("setmaxnreg.inc.sync.aligned.u32 240;");
    const int w = warp >> 2, wq = warp & 3, t128 = tid & 127;
    const int g = lane >> 2, tq = lane & 3;
    const uint32_t area = sbase + (uint32_t)w * 65536u;
    const bool elect = (t128 == 0);
    PROF(w, 22);
    const uint32_t dbase = (sbase & 0x3FFFFu) >> 4;
    uint32_t xoff = (uint32_t)((m * 4 + p) * 18 + w) * 8192u + (uint32_t)t128 * 16u;
    uint32_t stash = area + (uint32_t)t128 * 16u;
    const uint32_t epoch_c = ld_relaxed(&g_epoch);
    auto xptr = [&](int slot, int jj) INL { return (uint4*)((char*)g_xbuf + ((xoff & ~1u) + (uint32_t)slot * 16384u + (uint32_t)jj * 2048u)); };
    uint32_t A[144];
    float rs0, rs1;
    auto release = [&](int st) INL {
      if (elect) { mbar_arrive_cluster(BAR(B_EMPTY + st), 0); mbar_arrive_cluster(BAR(B_EMPTY + st), 1); }
    };

    {
      const int row = wq * 16 + (lane & 7) + ((lane >> 3) & 1) * 8;
      const uint32_t rbase = area + row * 128;
      float s0[2][4] = {}, q0[2][4] = {}, q1[2][4] = {};
      const uint32_t ones = 0x3F803F80u;
#pragma unroll
      for (int b = 0; b < 8; b++) {
        mbar_wait(BAR(B_XFULL + w * 8 + b), 0);
        if (b == 0) PROF(w, 23);
        if (b == 7) PROF(w, 24);
#pragma unroll
        for (int kk = 0; kk < 4; kk++) {
          const int i = (b * 4 + kk) * 4;
          ldmatrix_x4(rbase + b * 8192 + (((kk * 2 + (lane >> 4)) ^ (row & 7)) << 4), A[i], A[i + 1], A[i + 2], A[i + 3]);
        }
#pragma unroll
        for (int kk = 0; kk < 4; kk++) {
          const int i = (b * 4 + kk) * 4;
          mma_16816(s0[kk & 1], A[i], A[i + 1], A[i + 2], A[i + 3], ones, ones);
          mma_16816(q0[kk & 1], A[i], A[i + 1], A[i + 2], A[i + 3], A[i], A[i + 2]);
          mma_16816(q1[kk & 1], A[i], A[i + 1], A[i + 2], A[i + 3], A[i + 1], A[i + 3]);
        }
      }
      const float mean0 = (s0[0][0] + s0[1][0]) * (1.f / 512.f), mean1 = (s0[0][2] + s0[1][2]) * (1.f / 512.f);
      const uint32_t m0 = pack_bf16(mean0, mean0), m1 = pack_bf16(mean1, mean1);
#pragma unroll
      for (int i = 0; i < 128; i += 2) {
        A[i] = hsub2_bf16(A[i], m0);
        A[i + 1] = hsub2_bf16(A[i + 1], m1);
      }
      float v0 = (g & 1) ? q0[0][1] + q0[1][1] : q0[0][0] + q0[1][0];
      float v1 = (g & 1) ? q1[0][3] + q1[1][3] : q1[0][2] + q1[1][2];
      const int src = 4 * g + (g >> 1);
      v0 = __shfl_sync(0xffffffffu, v0, src);
      v1 = __shfl_sync(0xffffffffu, v1, src);
      v0 = fmaxf(v0 * (1.f / 512.f) - mean0 * mean0, 0.f);
      v1 = fmaxf(v1 * (1.f / 512.f) - mean1 * mean1, 0.f);
      rs0 = rsqrtf(v0 + 1e-5f);
      rs1 = rsqrtf(v1 + 1e-5f);
      bar_sync(1 + w, 128);
      cluster_wait();
      asm volatile("" : "+r"(xoff), "+r"(stash));
      PROF(w, 0);
      release(6); release(7);
      if (elect) mbar_arrive(BAR(B_XDONE));
    }

    auto gu_chunk = [&](float (&acc)[32], int f, int slot, int xslot, int hb) INL {
      const float c0 = rs0 * -1.4426950408889634f, c1 = rs1 * -1.4426950408889634f;
      const float q0 = rs0 * rs0, q1 = rs1 * rs1;
      uint32_t h[4];
#pragma unroll
      for (int i = 0; i < 4; i++) {
        const float ga = acc[f * 8 + 2 * i], gb = acc[f * 8 + 2 * i + 1];
        const float ua = acc[16 + f * 8 + 2 * i], ub = acc[16 + f * 8 + 2 * i + 1];
        const float c = (i & 1) ? c1 : c0, q = (i & 1) ? q1 : q0;
        const float da = 1.f + ex2f(fminf(ga * c, 60.f)), db = 1.f + ex2f(fminf(gb * c, 60.f));
        const float rq = rcpf(da * db) * q;
        h[i] = tagged(pack_bf16(ga * ua * (db * rq), gb * ub * (da * rq)), xoff & 1u);
      }
      const int jj = hb * 2 + f;
      sts_u4(stash + slot * 8192 + jj * 2048, h[0], h[1], h[2], h[3]);
      stg_u4(xptr(xslot, jj), h[0], h[1], h[2], h[3]);
    };
    auto kv_stage = [&](float (&acc)[32], int c, int hb) INL {
      const int srow = wq * 16 + (lane & 7) + ((lane >> 3) & 1) * 8;
      const uint32_t base = area + (3 + c) * 8192 + srow * 128;
#pragma unroll
      for (int jj = 0; jj < 2; jj++) {
        const int a = c * 16 + jj * 8;
        uint32_t r0, r1, r2, r3;
        if (c == 0) {
          r0 = pack_bf16(phi_f(acc[a] * rs0), phi_f(acc[a + 1] * rs0));
          r1 = pack_bf16(phi_f(acc[a + 2] * rs1), phi_f(acc[a + 3] * rs1));
          r2 = pack_bf16(phi_f(acc[a + 4] * rs0), phi_f(acc[a + 5] * rs0));
          r3 = pack_bf16(phi_f(acc[a + 6] * rs1), phi_f(acc[a + 7] * rs1));
        } else {
          r0 = pack_bf16(acc[a] * rs0, acc[a + 1] * rs0);
          r1 = pack_bf16(acc[a + 2] * rs1, acc[a + 3] * rs1);
          r2 = pack_bf16(acc[a + 4] * rs0, acc[a + 5] * rs0);
          r3 = pack_bf16(acc[a + 6] * rs1, acc[a + 7] * rs1);
        }
        stmatrix_x4(base + (((hb * 4 + jj * 2 + (lane >> 4)) ^ (srow & 7)) << 4), r0, r1, r2, r3);
      }
    };
    const uint32_t kvb = area + 5 * 8192;
    const uint32_t kvfrag = kvb + ((lane & 7) + ((lane >> 3) & 1) * 8) * 32 + (lane >> 4) * 16;
    auto signal = [&](int e) INL {
      __syncwarp();
      if (lane == 0) mbar_arrive(BAR(B_EV + w * 2 + e));
    };

    auto pp_wait = [&]() INL { bar_sync(3 + w, 256); };
    auto pp_pass = [&]() INL { bar_arrive(3 + (w ^ 1), 256); };
    if (w == 1) pp_pass();
    int tw1 = 0, tw2 = 0, tw3 = 0;
#pragma unroll 1
    for (int t = 0; t < 5; t++) {
      const uint32_t ph = t & 1;
      const int kind = odd ? (t < 2 ? K_KV : K_GU) : (t < 4 ? K_GU : K_Q);
      const int slot = odd ? t - 2 : t, xslot = odd ? t + 4 : t;
      static_for<2>([&](auto hc) INL {
        constexpr int hb = decltype(hc)::value;
        float acc[32];
        TWAIT(tw2, pp_wait());
        static_for<4>([&](auto kc) INL {
          constexpr int kq = decltype(kc)::value, k = hb * 4 + kq;
          TWAIT(tw1, mbar_wait(BAR(B_FULL + k), ph));
          wgmma_fence();
          static_for<8>([&](auto kkc) INL {
            constexpr int kk = decltype(kkc)::value, i = (kq * 8 + kk) * 4;
            wgmma_n64_rs<(kq | kk) != 0, desc_lo(stage_off(k) + kk * 1024, 8192), kHi64>(acc, A[i], A[i + 1], A[i + 2], A[i + 3]);
          });
          wgmma_commit();
          if (kq == 2) pp_pass();
          if (kq > 0) {
            wgmma_wait<1>();
            release(k - 1);
          }
        });
        TWAIT(tw3, wgmma_wait<0>());
        release(hb * 4 + 3);
        if (hb == 0 && t == 0) xoff |= (epoch_c & 1u) ^ 1u;
        if (kind == K_GU) {
          gu_chunk(acc, 0, slot, xslot, hb);
          gu_chunk(acc, 1, slot, xslot, hb);
        } else if (kind == K_KV) {
          if (hb == 0 && t == 0) sts_u4(stash + 5 * 8192, 0x3F803F80u, 0x3F803F80u, 0x3F803F80u, 0x3F803F80u);
          kv_stage(acc, 0, hb);
          kv_stage(acc, 1, hb);
          if (hb == 1) {
            float kvacc[36];
            const int par = (xoff & 1u) ^ 1u;
            fence_proxy_async();
            bar_sync(1 + w, 128);
            wgmma_fence();
            static_for<4>([&](auto kkc) INL {
              constexpr int kk = decltype(kkc)::value;
              wgmma_n72_ss_tt<kk != 0, desc_lo(3 * 8192 + kk * 2048, 0), desc_lo(4 * 8192 + kk * 2048, 8192 - kk * 2048)>(kvacc, dbase + w * 4096);
            });
            wgmma_commit();
            wgmma_wait<0>();
            float c[8];
#pragma unroll
            for (int i = 0; i < 8; i++)
              c[i] = wq == 0 ? kvacc[i] : (wq == 1 ? kvacc[8 + i] : (wq == 2 ? kvacc[16 + i] : kvacc[24 + i]));
            const int head = (2 * p + t) * 4 + wq;
            float* kvp = &g_kv[par][head][0][0];
            red_add_v2(kvp + g * 16 + 2 * tq, c[0], c[1]);
            red_add_v2(kvp + (g + 8) * 16 + 2 * tq, c[2], c[3]);
            red_add_v2(kvp + g * 16 + 8 + 2 * tq, c[4], c[5]);
            red_add_v2(kvp + (g + 8) * 16 + 8 + 2 * tq, c[6], c[7]);
            if (tq == 0) {
              red_add(&g_z[par][head][g], kvacc[32]);
              red_add(&g_z[par][head][g + 8], kvacc[34]);
            }
            signal(t);
          }
        } else {
          uint32_t aq[4][4];
#pragma unroll
          for (int c = 0; c < 4; c++) {
            const int a = c * 8;
            aq[c][0] = pack_bf16(phi_f(acc[a] * rs0), phi_f(acc[a + 1] * rs0));
            aq[c][1] = pack_bf16(phi_f(acc[a + 2] * rs1), phi_f(acc[a + 3] * rs1));
            aq[c][2] = pack_bf16(phi_f(acc[a + 4] * rs0), phi_f(acc[a + 5] * rs0));
            aq[c][3] = pack_bf16(phi_f(acc[a + 6] * rs1), phi_f(acc[a + 7] * rs1));
          }
          if (hb == 0) mbar_wait(BAR(B_KVREADY), 0);
          uint32_t Bf[4][6];
#pragma unroll
          for (int c = 0; c < 4; c++) {
            ldmatrix_x4_trans(kvfrag + (hb * 4 + c) * 512, Bf[c][0], Bf[c][1], Bf[c][2], Bf[c][3]);
            Bf[c][4] = lds_u32(kvb + 4096 + (hb * 4 + c) * 32 + tq * 4);
            Bf[c][5] = lds_u32(kvb + 4096 + (hb * 4 + c) * 32 + 16 + tq * 4);
          }
          float n0[4][4] = {}, n1[4][4] = {}, dn[4][4] = {};
#pragma unroll
          for (int c = 0; c < 4; c++) {
            mma_16816(dn[c], aq[c][0], aq[c][1], aq[c][2], aq[c][3], Bf[c][4], Bf[c][5]);
            mma_16816(n0[c], aq[c][0], aq[c][1], aq[c][2], aq[c][3], Bf[c][0], Bf[c][1]);
            mma_16816(n1[c], aq[c][0], aq[c][1], aq[c][2], aq[c][3], Bf[c][2], Bf[c][3]);
          }
          if (hb == 1) bar_sync(1 + w, 128);
          const uint32_t tg = xoff & 1u;
#pragma unroll
          for (int c = 0; c < 4; c++) {
            const float i0 = __fdividef(1.f, dn[c][0] + 1e-6f), i1 = __fdividef(1.f, dn[c][2] + 1e-6f);
            aq[c][0] = tagged(pack_bf16(n0[c][0] * i0, n0[c][1] * i0), tg);
            aq[c][1] = tagged(pack_bf16(n0[c][2] * i1, n0[c][3] * i1), tg);
            aq[c][2] = tagged(pack_bf16(n1[c][0] * i0, n1[c][1] * i0), tg);
            aq[c][3] = tagged(pack_bf16(n1[c][2] * i1, n1[c][3] * i1), tg);
          }
#pragma unroll
          for (int c = 0; c < 4; c++) {
            stg_u4(xptr(4 + hb, c), aq[c][0], aq[c][1], aq[c][2], aq[c][3]);
            sts_u4(stash + (4 + hb) * 8192 + c * 2048, aq[c][0], aq[c][1], aq[c][2], aq[c][3]);
          }
        }
      });
      PROF(w, 1 + 2 * t);
    }
    PROF(w, 10);

    const int n_own = odd ? 3 : 6;
    auto load_a = [&](int kb) INL {
      if (kb < n_own) {
#pragma unroll
        for (int jj = 0; jj < 4; jj++) {
          const int i = (kb * 4 + jj) * 4;
          lds_u4(stash + kb * 8192 + jj * 2048, A[i], A[i + 1], A[i + 2], A[i + 3]);
        }
      } else {
        const int xs = odd ? kb - 3 : kb;
#pragma unroll
        for (int jj = 0; jj < 4; jj++) {
          const int i = (kb * 4 + jj) * 4;
          ldg_poll_u4(xptr(xs, jj), A[i], A[i + 1], A[i + 2], A[i + 3]);
        }
      }
    };
    auto fix_a = [&](int kb) INL {
      if (kb >= n_own) {
        const int xs = odd ? kb - 3 : kb;
        recv_group<4>(xptr(xs, 0), &A[kb * 16], xoff & 1u);
      }
    };
#pragma unroll
    for (int kb = 0; kb < 7; kb++) load_a(kb);
    PROF(w, 11);

    const int orow = m * 128 + w * 64 + wq * 16 + g;
    const int ocol = odd * 256 + p * 64 + 2 * tq;
    float acc2[2][32];
    uint32_t poff = (uint32_t)((m * 2 + odd) * 24 + w) * 8192u + (uint32_t)t128 * 16u;
    asm volatile("" : "+r"(poff));
    auto pptr = [&](int dest, int sl) INL { return (uint4*)((char*)g_pbuf + (poff + (uint32_t)(dest * 3 + sl) * 16384u)); };
    uint32_t P[3][16];
    uint32_t xr[16];
    auto send = [&](float (&acc)[32], int bi) INL {
      uint4* dst = pptr((p + 1 + bi) & 3, bi);
#pragma unroll
      for (int q = 0; q < 4; q++)
        stg_u4(dst + q * 128, tagged(pack_bf16(acc[q * 8], acc[q * 8 + 1]), xoff & 1u), tagged(pack_bf16(acc[q * 8 + 2], acc[q * 8 + 3]), xoff & 1u),
               tagged(pack_bf16(acc[q * 8 + 4], acc[q * 8 + 5]), xoff & 1u), tagged(pack_bf16(acc[q * 8 + 6], acc[q * 8 + 7]), xoff & 1u));
      PROF(w, 12 + 2 * bi);
    };
    auto fetch = [&](int sl) INL {
#pragma unroll
      for (int q = 0; q < 4; q++) ldg_poll_u4(pptr(p, sl) + q * 128, P[sl][q * 4], P[sl][q * 4 + 1], P[sl][q * 4 + 2], P[sl][q * 4 + 3]);
    };
    static_for<36>([&](auto ic) INL {
      constexpr int i = decltype(ic)::value, bi = p2_bi(i), kb = p2_kb(i), j = i >> 1, st = j & 7;
      if (i == 9) { load_a(7); load_a(8); }
      if (i == 14) PROF(w, 2);
      if (bi == 0 && kb >= 3) fix_a(kb);
      if (i == 15) PROF(w, 4);
      if (i == 7) PROF(w, 6);
      if (i == 0 || i == 7 || i == 14 || i == 18 || i == 27) pp_wait();
      if ((i & 1) == 0) mbar_wait(BAR(B_FULL + st), (5 + (j >> 3)) & 1);
      wgmma_fence();
      static_for<4>([&](auto kkc) INL {
        constexpr int kk = decltype(kkc)::value, a = (kb * 4 + kk) * 4;
        wgmma_n64_rs<(kb | kk) != 0, desc_lo(stage_off(st) + (i & 1) * 8192 + kk * 2048, 0), kHi128>(acc2[bi & 1], A[a], A[a + 1], A[a + 2], A[a + 3]);
      });
      wgmma_commit();
      if (i == 4 || i == 11 || i == 15 || i == 24 || (i == 33 && w == 0)) pp_pass();
      if (i > 0) {
        wgmma_wait<1>();
        if ((i & 1) == 0 && j - 1 <= 9) release((j - 1) & 7);
      }
      if constexpr (i == 17) { send(acc2[0], 0); wgmma_wait<0>(); send(acc2[1], 1); }
      if constexpr (i == 26) { wgmma_wait<0>(); send(acc2[0], 2); }
      if constexpr (i == 29) fetch(0);
      if constexpr (i == 30) fetch(1);
      if constexpr (i == 28) {
#pragma unroll
        for (int q = 0; q < 8; q++) {
          xr[2 * q] = __ldg((const uint32_t*)(x + (size_t)orow * kD + ocol + q * 8));
          xr[2 * q + 1] = __ldg((const uint32_t*)(x + (size_t)(orow + 8) * kD + ocol + q * 8));
        }
      }
      if constexpr (i == 32) fetch(2);
    });
#pragma unroll
    for (int sl = 0; sl < 3; sl++) { PROF(w, 13 + 2 * sl); recv_group<4>(pptr(p, sl), &P[sl][0], xoff & 1u); }
    wgmma_wait<0>();
    PROF(w, 18);
#pragma unroll
    for (int q = 0; q < 8; q++) {
      float rr[4];
      rr[0] = acc2[1][q * 4 + 0] + __uint_as_float(xr[2 * q] << 16);
      rr[1] = acc2[1][q * 4 + 1] + __uint_as_float(xr[2 * q] & 0xffff0000u);
      rr[2] = acc2[1][q * 4 + 2] + __uint_as_float(xr[2 * q + 1] << 16);
      rr[3] = acc2[1][q * 4 + 3] + __uint_as_float(xr[2 * q + 1] & 0xffff0000u);
#pragma unroll
      for (int sl = 0; sl < 3; sl++) {
        rr[0] += __uint_as_float(P[sl][2 * q] << 16);
        rr[1] += __uint_as_float(P[sl][2 * q] & 0xffff0000u);
        rr[2] += __uint_as_float(P[sl][2 * q + 1] << 16);
        rr[3] += __uint_as_float(P[sl][2 * q + 1] & 0xffff0000u);
      }
      *(uint32_t*)(out + (size_t)orow * kD + ocol + q * 8) = pack_bf16(rr[0], rr[1]);
      *(uint32_t*)(out + (size_t)(orow + 8) * kD + ocol + q * 8) = pack_bf16(rr[2], rr[3]);
    }
    PROF(w, 19);
    if (tid == 0) {
      const uint32_t old = atomicAdd(&g_done, 1u);
      if ((old & 127u) == 127u) st_relaxed(&g_epoch, ld_relaxed(&g_epoch) + 1u);
    }
  }
#undef BAR
}

typedef CUresult (*EncodeFn)(CUtensorMap*, CUtensorMapDataType, cuuint32_t, void*, const cuuint64_t*, const cuuint64_t*,
                             const cuuint32_t*, const cuuint32_t*, CUtensorMapInterleave, CUtensorMapSwizzle,
                             CUtensorMapL2promotion, CUtensorMapFloatOOBfill);

void make_map(EncodeFn enc, CUtensorMap* tm, const void* ptr, int rows, int cols, bool narrow) {
  cuuint64_t gd[2] = {(cuuint64_t)cols, (cuuint64_t)rows};
  cuuint64_t gs[1] = {(cuuint64_t)cols * 2};
  cuuint32_t bd[2] = {narrow ? 32u : 64u, narrow ? 128u : 64u};
  cuuint32_t es[2] = {1, 1};
  enc(tm, CU_TENSOR_MAP_DATA_TYPE_BFLOAT16, 2, const_cast<void*>(ptr), gd, gs, bd, es, CU_TENSOR_MAP_INTERLEAVE_NONE,
      narrow ? CU_TENSOR_MAP_SWIZZLE_64B : CU_TENSOR_MAP_SWIZZLE_128B, CU_TENSOR_MAP_L2_PROMOTION_L2_256B, CU_TENSOR_MAP_FLOAT_OOB_FILL_NONE);
}

}

extern "C" void kernel_launch(void* const* d_in, const int* in_sizes, int n_in, void* d_out, int out_size) {
  static EncodeFn enc = nullptr;
  if (!enc) {
    void* fn = nullptr;
    cudaDriverEntryPointQueryResult qr;
    cudaGetDriverEntryPoint("cuTensorMapEncodeTiled", &fn, cudaEnableDefault, &qr);
    enc = (EncodeFn)fn;
    cudaFuncSetAttribute(fused_kernel, cudaFuncAttributeMaxDynamicSharedMemorySize, kSmemBytes);
  }
  CUtensorMap tm_x, tm_wqkv, tm_w1, tm_w3, tm_w2, tm_wo;
  make_map(enc, &tm_x, d_in[0], kS, kD, false);
  make_map(enc, &tm_wqkv, d_in[1], kD, 3 * kD, true);
  make_map(enc, &tm_wo, d_in[2], kD, kD, false);
  make_map(enc, &tm_w1, d_in[4], kD, kF, true);
  make_map(enc, &tm_w3, d_in[5], kD, kF, true);
  make_map(enc, &tm_w2, d_in[6], kF, kD, false);
  fused_kernel<<<128, 384, kSmemBytes>>>(tm_x, tm_wqkv, tm_w1, tm_w3, tm_w2, tm_wo, (const __nv_bfloat16*)d_in[0],
                                         (__nv_bfloat16*)d_out);
}
```

```cpp
#include <cuda_runtime.h>
#include <cuda_bf16.h>
#include <cuda.h>
#include <stdint.h>

extern __shared__ __align__(1024) uint8_t smem_raw[];

namespace {

constexpr int kS = 2048, kD = 512, kF = 1792;
#define XPOS 1
constexpr uint32_t kSpinLimit = 1u << 22;

__device__ uint4    g_xbuf[16][4][9][2][4][128];
__device__ uint4    g_pbuf[16][2][4][3][2][4][128];
__device__ float    g_kv[2][32][16][16];
__device__ float    g_z[2][32][16];
__device__ uint32_t g_kvcnt[4][32];
__device__ uint32_t g_epoch;
__device__ uint32_t g_done;
#define PROF(wg, i) do {} while (0)
#define TWAIT(acc, stmt) do { stmt; } while (0)

__device__ __forceinline__ uint32_t smem_u32(const void* p) { return (uint32_t)__cvta_generic_to_shared(p); }
__device__ __forceinline__ void mbar_init(uint32_t bar, uint32_t cnt) {
  asm volatile("mbarrier.init.shared::cta.b64 [%0], %1;" ::"r"(bar), "r"(cnt) : "memory");
}
__device__ __forceinline__ void mbar_expect_tx(uint32_t bar, uint32_t bytes) {
  asm volatile("mbarrier.arrive.expect_tx.shared::cta.b64 _, [%0], %1;" ::"r"(bar), "r"(bytes) : "memory");
}
__device__ __forceinline__ void mbar_arrive(uint32_t bar) {
  asm volatile("mbarrier.arrive.shared::cta.b64 _, [%0];" ::"r"(bar) : "memory");
}
__device__ __forceinline__ void mbar_wait(uint32_t bar, uint32_t parity) {
  asm volatile(
      "{\n.reg .pred p;\n"
      "LAB_WAIT:\n"
      "mbarrier.try_wait.parity.shared::cta.b64 p, [%0], %1;\n"
      "@p bra DONE;\n"
      "bra LAB_WAIT;\n"
      "DONE:\n}" ::"r"(bar), "r"(parity) : "memory");
}
__device__ __forceinline__ void tma_load_2d(uint32_t dst, const CUtensorMap* tm, uint32_t bar, int c0, int c1) {
  asm volatile(
      "cp.async.bulk.tensor.2d.shared::cluster.global.mbarrier::complete_tx::bytes [%0], [%1, {%3, %4}], [%2];" ::"r"(dst),
      "l"(tm), "r"(bar), "r"(c0), "r"(c1)
      : "memory");
}
__device__ __forceinline__ void tma_load_2d_mc(uint32_t dst, const CUtensorMap* tm, uint32_t bar, int c0, int c1) {
  asm volatile(
      "cp.async.bulk.tensor.2d.shared::cluster.global.mbarrier::complete_tx::bytes.multicast::cluster [%0], [%1, {%3, %4}], [%2], %5;" ::"r"(dst),
      "l"(tm), "r"(bar), "r"(c0), "r"(c1), "h"((uint16_t)3)
      : "memory");
}
__device__ __forceinline__ void mbar_arrive_cluster(uint32_t bar, uint32_t cta) {
  asm volatile("{\n.reg .b32 ra;\nmapa.shared::cluster.u32 ra, %0, %1;\nmbarrier.arrive.shared::cluster.b64 _, [ra];\n}" ::"r"(bar), "r"(cta) : "memory");
}
__device__ __forceinline__ void prefetch_tmap(const CUtensorMap* tm) {
  asm volatile("prefetch.tensormap [%0];" ::"l"(tm) : "memory");
}
__device__ __forceinline__ void wgmma_fence() { asm volatile("wgmma.fence.sync.aligned;" ::: "memory"); }
__device__ __forceinline__ void wgmma_commit() { asm volatile("wgmma.commit_group.sync.aligned;" ::: "memory"); }
template <int N>
__device__ __forceinline__ void wgmma_wait() { asm volatile("wgmma.wait_group.sync.aligned %0;" ::"n"(N) : "memory"); }
__device__ __forceinline__ void bar_sync(int id, int n) { asm volatile("bar.sync %0, %1;" ::"r"(id), "r"(n) : "memory"); }
__device__ __forceinline__ void bar_arrive(int id, int n) { asm volatile("bar.arrive %0, %1;" ::"r"(id), "r"(n) : "memory"); }
__device__ __forceinline__ void fence_proxy_async() { asm volatile("fence.proxy.async.shared::cta;" ::: "memory"); }

__device__ __forceinline__ uint32_t ld_acquire(const uint32_t* p) {
  uint32_t v;
  asm volatile("ld.acquire.gpu.global.u32 %0, [%1];" : "=r"(v) : "l"(p) : "memory");
  return v;
}
__device__ __forceinline__ uint32_t ld_relaxed(const uint32_t* p) {
  uint32_t v;
  asm volatile("ld.relaxed.gpu.global.u32 %0, [%1];" : "=r"(v) : "l"(p));
  return v;
}
__device__ __forceinline__ void cluster_wait() { asm volatile("barrier.cluster.wait.aligned;" ::: "memory"); }
__device__ __forceinline__ void st_relaxed(uint32_t* p, uint32_t v) {
  asm volatile("st.relaxed.gpu.global.u32 [%0], %1;" ::"l"(p), "r"(v) : "memory");
}
__device__ __forceinline__ void wait_flag_eq(const uint32_t* p, uint32_t val) {
  uint32_t it = 0;
  while (ld_acquire(p) != val) {
    if (++it > kSpinLimit) break;
  }
}
__device__ __forceinline__ void wait_count_ge(const uint32_t* p, uint32_t val) {
  uint32_t it = 0;
  while ((int32_t)(ld_acquire(p) - val) < 0) {
    __nanosleep(64);
    if (++it > kSpinLimit) break;
  }
}
__device__ __forceinline__ void ldg_poll_u4(const void* p, uint32_t& a, uint32_t& b, uint32_t& c, uint32_t& d) {
  asm volatile("ld.relaxed.gpu.global.v4.u32 {%0,%1,%2,%3}, [%4];" : "=r"(a), "=r"(b), "=r"(c), "=r"(d) : "l"(p) : "memory");
}
template <int N>
__device__ __forceinline__ void recv_group(const uint4* p, uint32_t* r, uint32_t tag) {
  uint32_t it = 0;
  while (true) {
    uint32_t bad = 0u;
#pragma unroll
    for (int i = 0; i < 4 * N; i++) bad |= r[i] ^ tag;
    if (!__any_sync(0xffffffffu, (bad & 1u) != 0u) || ++it > kSpinLimit) break;
#pragma unroll
    for (int q = 0; q < N; q++) ldg_poll_u4(p + q * 128, r[q * 4], r[q * 4 + 1], r[q * 4 + 2], r[q * 4 + 3]);
  }
}
__device__ __forceinline__ uint32_t tagged(uint32_t v, uint32_t tag) { return (v & ~1u) | tag; }
__device__ __forceinline__ float4 ldg_cg_f4(const void* p) {
  float4 v;
  asm volatile("ld.global.cg.v4.f32 {%0,%1,%2,%3}, [%4];" : "=f"(v.x), "=f"(v.y), "=f"(v.z), "=f"(v.w) : "l"(p) : "memory");
  return v;
}
__device__ __forceinline__ void stg_u4(void* p, uint32_t a, uint32_t b, uint32_t c, uint32_t d) {
  asm volatile("st.global.v4.u32 [%0], {%1,%2,%3,%4};" ::"l"(p), "r"(a), "r"(b), "r"(c), "r"(d) : "memory");
}
__device__ __forceinline__ void stg_f4(void* p, float a, float b, float c, float d) {
  asm volatile("st.global.v4.f32 [%0], {%1,%2,%3,%4};" ::"l"(p), "f"(a), "f"(b), "f"(c), "f"(d) : "memory");
}
__device__ __forceinline__ void sts_u4(uint32_t addr, uint32_t a, uint32_t b, uint32_t c, uint32_t d) {
  asm volatile("st.shared.v4.u32 [%0], {%1,%2,%3,%4};" ::"r"(addr), "r"(a), "r"(b), "r"(c), "r"(d) : "memory");
}
__device__ __forceinline__ void lds_u4(uint32_t addr, uint32_t& a, uint32_t& b, uint32_t& c, uint32_t& d) {
  asm volatile("ld.shared.v4.u32 {%0,%1,%2,%3}, [%4];" : "=r"(a), "=r"(b), "=r"(c), "=r"(d) : "r"(addr) : "memory");
}
__device__ __forceinline__ uint32_t lds_u32(uint32_t addr) {
  uint32_t v;
  asm volatile("ld.shared.u32 %0, [%1];" : "=r"(v) : "r"(addr) : "memory");
  return v;
}
__device__ __forceinline__ void ldmatrix_x4(uint32_t addr, uint32_t& a, uint32_t& b, uint32_t& c, uint32_t& d) {
  asm volatile("ldmatrix.sync.aligned.m8n8.x4.shared.b16 {%0,%1,%2,%3}, [%4];" : "=r"(a), "=r"(b), "=r"(c), "=r"(d) : "r"(addr) : "memory");
}
__device__ __forceinline__ void ldmatrix_x4_trans(uint32_t addr, uint32_t& a, uint32_t& b, uint32_t& c, uint32_t& d) {
  asm volatile("ldmatrix.sync.aligned.m8n8.x4.trans.shared.b16 {%0,%1,%2,%3}, [%4];" : "=r"(a), "=r"(b), "=r"(c), "=r"(d) : "r"(addr) : "memory");
}
__device__ __forceinline__ void stmatrix_x4(uint32_t addr, uint32_t a, uint32_t b, uint32_t c, uint32_t d) {
  asm volatile("stmatrix.sync.aligned.m8n8.x4.shared.b16 [%0], {%1,%2,%3,%4};" ::"r"(addr), "r"(a), "r"(b), "r"(c), "r"(d) : "memory");
}
__device__ __forceinline__ void mma_16816(float (&c)[4], uint32_t a0, uint32_t a1, uint32_t a2, uint32_t a3, uint32_t b0, uint32_t b1) {
  asm(
      "mma.sync.aligned.m16n8k16.row.col.f32.bf16.bf16.f32 {%0,%1,%2,%3}, {%4,%5,%6,%7}, {%8,%9}, {%0,%1,%2,%3};"
      : "+f"(c[0]), "+f"(c[1]), "+f"(c[2]), "+f"(c[3])
      : "r"(a0), "r"(a1), "r"(a2), "r"(a3), "r"(b0), "r"(b1));
}
__device__ __forceinline__ uint32_t pack_bf16(float lo, float hi) {
  uint32_t r;
  asm("cvt.rn.bf16x2.f32 %0, %1, %2;" : "=r"(r) : "f"(hi), "f"(lo));
  return r;
}
__device__ __forceinline__ uint32_t hsub2_bf16(uint32_t a, uint32_t b) {
  uint32_t r;
  asm("sub.rn.bf16x2 %0, %1, %2;" : "=r"(r) : "r"(a), "r"(b));
  return r;
}
__device__ __forceinline__ float ex2f(float x) {
  float r;
  asm("ex2.approx.ftz.f32 %0, %1;" : "=f"(r) : "f"(x));
  return r;
}
__device__ __forceinline__ float rcpf(float x) {
  float r;
  asm("rcp.approx.ftz.f32 %0, %1;" : "=f"(r) : "f"(x));
  return r;
}
__device__ __forceinline__ void red_add_v2(float* p, float a, float b) {
  asm volatile("red.relaxed.gpu.global.add.v2.f32 [%0], {%1,%2};" ::"l"(p), "f"(a), "f"(b) : "memory");
}
__device__ __forceinline__ void red_add(float* p, float a) {
  asm volatile("red.relaxed.gpu.global.add.f32 [%0], %1;" ::"l"(p), "f"(a) : "memory");
}
__device__ __forceinline__ float phi_f(float t) {
  float e = ex2f(t * 1.4426950408889634f);
  return (t > 0.f ? t + 1.f : e) + 1e-6f;
}

#define R8(a, o) "+f"(a[o + 0]), "+f"(a[o + 1]), "+f"(a[o + 2]), "+f"(a[o + 3]), "+f"(a[o + 4]), "+f"(a[o + 5]), "+f"(a[o + 6]), "+f"(a[o + 7])

#define W8(a, o) "=f"(a[o + 0]), "=f"(a[o + 1]), "=f"(a[o + 2]), "=f"(a[o + 3]), "=f"(a[o + 4]), "=f"(a[o + 5]), "=f"(a[o + 6]), "=f"(a[o + 7])
#define D32 "{%0,%1,%2,%3,%4,%5,%6,%7,%8,%9,%10,%11,%12,%13,%14,%15,%16,%17,%18,%19,%20,%21,%22,%23,%24,%25,%26,%27,%28,%29,%30,%31}"
#define D36 "{%0,%1,%2,%3,%4,%5,%6,%7,%8,%9,%10,%11,%12,%13,%14,%15,%16,%17,%18,%19,%20,%21,%22,%23,%24,%25,%26,%27,%28,%29,%30,%31,%32,%33,%34,%35}"

constexpr uint32_t kHi128 = (1024u >> 4) | (1u << 30);
constexpr uint32_t kHi64 = (512u >> 4) | (2u << 30);
__host__ __device__ constexpr uint32_t desc_lo(uint32_t off, uint32_t lbo) { return (off >> 4) | ((lbo >> 4) << 16); }

template <bool ACC, uint32_t LO, uint32_t HI>
__device__ __forceinline__ void wgmma_n64_rs(float (&d)[32], uint32_t a0, uint32_t a1, uint32_t a2, uint32_t a3) {
  if (ACC) {
    asm volatile(
        "{\n.reg .pred p;\n.reg .b32 lo;\n.reg .b64 dd;\nsetp.eq.b32 p, 0, 0;\nmov.u32 lo, 64;\nadd.u32 lo, lo, %36;\nmov.b64 dd, {lo, %37};\n"
        "wgmma.mma_async.sync.aligned.m64n64k16.f32.bf16.bf16 " D32 ", {%32,%33,%34,%35}, dd, p, 1, 1, 1;\n}"
        : R8(d, 0), R8(d, 8), R8(d, 16), R8(d, 24)
        : "r"(a0), "r"(a1), "r"(a2), "r"(a3), "n"(LO), "n"(HI));
  } else {
    asm volatile(
        "{\n.reg .pred p;\n.reg .b32 lo;\n.reg .b64 dd;\nsetp.ne.b32 p, 0, 0;\nmov.u32 lo, 64;\nadd.u32 lo, lo, %36;\nmov.b64 dd, {lo, %37};\n"
        "wgmma.mma_async.sync.aligned.m64n64k16.f32.bf16.bf16 " D32 ", {%32,%33,%34,%35}, dd, p, 1, 1, 1;\n}"
        : W8(d, 0), W8(d, 8), W8(d, 16), W8(d, 24)
        : "r"(a0), "r"(a1), "r"(a2), "r"(a3), "n"(LO), "n"(HI));
  }
}
template <bool ACC, uint32_t LOA, uint32_t LOB>
__device__ __forceinline__ void wgmma_n72_ss_tt(float (&d)[36], uint32_t base) {
  if (ACC) {
    asm volatile(
        "{\n.reg .pred p;\n.reg .b32 lo;\n.reg .b64 da, db;\nsetp.eq.b32 p, 0, 0;\n"
        "add.u32 lo, %36, %37;\nmov.b64 da, {lo, %39};\nadd.u32 lo, %36, %38;\nmov.b64 db, {lo, %39};\n"
        "wgmma.mma_async.sync.aligned.m64n72k16.f32.bf16.bf16 " D36 ", da, db, p, 1, 1, 1, 1;\n}"
        : R8(d, 0), R8(d, 8), R8(d, 16), R8(d, 24), "+f"(d[32]), "+f"(d[33]), "+f"(d[34]), "+f"(d[35])
        : "r"(base), "n"(LOA), "n"(LOB), "n"(kHi128));
  } else {
    asm volatile(
        "{\n.reg .pred p;\n.reg .b32 lo;\n.reg .b64 da, db;\nsetp.ne.b32 p, 0, 0;\n"
        "add.u32 lo, %36, %37;\nmov.b64 da, {lo, %39};\nadd.u32 lo, %36, %38;\nmov.b64 db, {lo, %39};\n"
        "wgmma.mma_async.sync.aligned.m64n72k16.f32.bf16.bf16 " D36 ", da, db, p, 1, 1, 1, 1;\n}"
        : W8(d, 0), W8(d, 8), W8(d, 16), W8(d, 24), "=f"(d[32]), "=f"(d[33]), "=f"(d[34]), "=f"(d[35])
        : "r"(base), "n"(LOA), "n"(LOB), "n"(kHi128));
  }
}

#define INL __attribute__((always_inline))
template <int V> struct IC { static constexpr int value = V; };
template <int N, int I = 0, typename F>
__device__ __forceinline__ void static_for(F&& f) {
  if constexpr (I < N) { f(IC<I>{}); static_for<N, I + 1>(f); }
}

__host__ __device__ constexpr uint32_t stage_off(int st) {
  return st < 6 ? 131072u + (uint32_t)st * 16384u : (uint32_t)(st - 6) * 65536u + 49152u;
}

constexpr int B_FULL = 0, B_EMPTY = 8, B_XFULL = 16, B_XDONE = 32, B_KVREADY = 33, B_EV = 34, B_COUNT = 38;
constexpr uint32_t kBarOff = 229376;
constexpr int kSmemBytes = 229376 + 1024;

__host__ __device__ constexpr int p2_bi(int i) { return i < 7 ? 0 : i < 14 ? 1 : i < 16 ? 0 : i < 18 ? 1 : i / 9; }
__host__ __device__ constexpr int p2_kb(int i) { return i < 7 ? i : i < 14 ? i - 7 : i < 16 ? i - 7 : i < 18 ? i - 9 : i % 9; }

enum { K_NONE = 0, K_GU = 1, K_KV = 2, K_Q = 3 };

__global__ void __cluster_dims__(2, 1, 1) __launch_bounds__(384, 1)
fused_kernel(const __grid_constant__ CUtensorMap tm_x, const __grid_constant__ CUtensorMap tm_wqkv,
             const __grid_constant__ CUtensorMap tm_w1, const __grid_constant__ CUtensorMap tm_w3,
             const __grid_constant__ CUtensorMap tm_w2, const __grid_constant__ CUtensorMap tm_wo,
             const __nv_bfloat16* __restrict__ x, __nv_bfloat16* __restrict__ out) {
  const uint32_t sbase = smem_u32(smem_raw);
  const uint32_t bars = sbase + kBarOff;
  const int tid = threadIdx.x, lane = tid & 31;
  const int warp = __shfl_sync(0xffffffffu, tid >> 5, 0);
  const int cr = blockIdx.x & 1;
  const int r = (blockIdx.x >> 1) & 7, m = ((blockIdx.x >> 4) << 1) | cr, p = r >> 1, odd = r & 1;
#define BAR(i) (bars + 8u * (uint32_t)(i))
  if (tid == 256) {
    if ((sbase & 0x3FFFFu) != 1024u) __trap();
#pragma unroll
    for (int i = 0; i < 16; i++) mbar_init(BAR(B_XFULL + i), 1);
    fence_proxy_async();
#pragma unroll
    for (int b = 0; b < 8; b++) {
      mbar_expect_tx(BAR(B_XFULL + b), 8192);
      tma_load_2d(sbase + (b >> 3) * 65536 + (b & 7) * 8192, &tm_x, BAR(B_XFULL + b), (b & 7) * 64, m * 128 + (b >> 3) * 64);
    }
#pragma unroll
    for (int i = 0; i < 8; i++) { mbar_init(BAR(B_FULL + i), 1); mbar_init(BAR(B_EMPTY + i), 4); }
#pragma unroll
    for (int i = 0; i < 4; i++) mbar_init(BAR(B_EV + i), 4);
    mbar_init(BAR(B_XDONE), 2);
    mbar_init(BAR(B_KVREADY), 3);
    asm volatile("fence.mbarrier_init.release.cluster;" ::: "memory");
    fence_proxy_async();
  } else if (tid == 288) {
    prefetch_tmap(odd ? &tm_wqkv : (cr ? &tm_w3 : &tm_w1));
  }
  __syncwarp();
  asm volatile("barrier.cluster.arrive.relaxed.aligned;" ::: "memory");
  PROF((tid >> 7), 21);
  __syncthreads();

  if (warp >= 8) {
    asm volatile("setmaxnreg.dec.sync.aligned.u32 24;");
    PROF(2, 3);
    cluster_wait();
    PROF(2, 2);
    const uint32_t epoch = warp == 8 ? 0u : ld_relaxed(&g_epoch);
    const uint32_t tag = epoch + 1u;
    const int par = epoch & 1;
    if (warp == 8) {
      if (lane == 0) {
        int twp = 0;
        for (int j = 0; j < 10; j++) {
          const CUtensorMap* tm;
          int col;
          if (!odd) {
            if (j < 8) { tm = cr ? &tm_w3 : &tm_w1; col = 7 * p * 64 + j * 32; }
            else { tm = &tm_wqkv; col = 128 * p + (j - 8) * 64 + cr * 32; }
          } else {
            if (j < 4) { tm = &tm_wqkv; col = 512 + cr * 512 + 128 * p + j * 32; }
            else { tm = cr ? &tm_w3 : &tm_w1; col = (7 * p + 4) * 64 + (j - 4) * 32; }
          }
          const int t = j >> 1;
          for (int kq = 0; kq < 4; kq++) {
            if (j == 0 && kq == XPOS) {
              for (int b = 8; b < 16; b++) {
                mbar_expect_tx(BAR(B_XFULL + b), 8192);
                tma_load_2d(sbase + 65536 + (b & 7) * 8192, &tm_x, BAR(B_XFULL + b), (b & 7) * 64, m * 128 + 64);
              }
            }
            const int k = (j & 1) * 4 + kq;
            TWAIT(twp, mbar_wait(BAR(B_EMPTY + k), k < 6 ? ((t & 1) ^ 1) : (t & 1)));
            mbar_expect_tx(BAR(B_FULL + k), 16384);
            tma_load_2d_mc(sbase + stage_off(k) + cr * 8192, tm, BAR(B_FULL + k), col, kq * 128);
          }
        }
        for (int j = 0; j < 18; j++) {
          const int st = j & 7, n = 5 + (j >> 3);
          const int i = 2 * j + cr;
          const int bi = p2_bi(i), kb = p2_kb(i);
          const int col = odd * 256 + ((p + 1 + bi) & 3) * 64;
          const CUtensorMap* tmk;
          int row;
          if (!odd) {
            if (kb < 4) { tmk = &tm_w2; row = (7 * p + kb) * 64; }
            else if (kb < 6) { tmk = &tm_wo; row = (2 * p + kb - 4) * 64; }
            else { tmk = &tm_w2; row = (7 * p + 4 + kb - 6) * 64; }
          } else {
            if (kb < 3) { tmk = &tm_w2; row = (7 * p + 4 + kb) * 64; }
            else if (kb < 7) { tmk = &tm_w2; row = (7 * p + kb - 3) * 64; }
            else { tmk = &tm_wo; row = (2 * p + kb - 7) * 64; }
          }
          mbar_wait(BAR(B_EMPTY + st), st < 6 ? ((n & 1) ^ 1) : (n & 1));
          mbar_expect_tx(BAR(B_FULL + st), 16384);
          tma_load_2d_mc(sbase + stage_off(st) + cr * 8192, tmk, BAR(B_FULL + st), col, row);
        }
      }
    } else if (odd) {
      if (lane == 0 && warp <= 10) {
        const int w = warp - 9;
        for (int e = 0; e < 2; e++) {
          mbar_wait(BAR(B_EV + w * 2 + e), 0);
          __threadfence();
          atomicAdd(&g_kvcnt[p][0], 1u);
        }
      }
    } else {
      const int hl = tid - 288;
      {
        const int ce = m * 4 + p;
        if (hl < 32) *(float4*)(&g_kv[par ^ 1][0][0][0] + ce * 128 + hl * 4) = make_float4(0.f, 0.f, 0.f, 0.f);
        else if (hl < 40) (&g_z[par ^ 1][0][0])[ce * 8 + hl - 32] = 0.f;
      }
      mbar_wait(BAR(B_XDONE), 0);
      wait_count_ge(&g_kvcnt[p][0], 64u * tag);
      const float* kvp = &g_kv[par][8 * p][0][0];
      const float* zp = &g_z[par][8 * p][0];
      const uint32_t dst0 = sbase + 5 * 8192, dst1 = dst0 + 65536;
#pragma unroll
      for (int h2 = 0; h2 < 2; h2++) {
        float4 v[3];
#pragma unroll
        for (int i = 0; i < 3; i++) {
          const int c = (h2 * 3 + i) * 96 + hl;
          v[i] = c < 512 ? ldg_cg_f4(kvp + c * 4) : (c < 544 ? ldg_cg_f4(zp + (c - 512) * 4) : make_float4(0.f, 0.f, 0.f, 0.f));
        }
#pragma unroll
        for (int i = 0; i < 3; i++) {
          const int c = (h2 * 3 + i) * 96 + hl;
          if (c < 544) {
            const uint32_t lo = pack_bf16(v[i].x, v[i].y), hi = pack_bf16(v[i].z, v[i].w);
            asm volatile("st.shared.v2.u32 [%0], {%1,%2};" ::"r"(dst0 + c * 8), "r"(lo), "r"(hi) : "memory");
            asm volatile("st.shared.v2.u32 [%0], {%1,%2};" ::"r"(dst1 + c * 8), "r"(lo), "r"(hi) : "memory");
          }
        }
      }
      __syncwarp();
      if (lane == 0) mbar_arrive(BAR(B_KVREADY));
    }
  } else {
    asm volatile("setmaxnreg.inc.sync.aligned.u32 240;");
    const int w = warp >> 2, wq = warp & 3, t128 = tid & 127;
    const int g = lane >> 2, tq = lane & 3;
    const uint32_t area = sbase + (uint32_t)w * 65536u;
    const bool elect = (t128 == 0);
    PROF(w, 22);
    const uint32_t dbase = (sbase & 0x3FFFFu) >> 4;
    uint32_t xoff = (uint32_t)((m * 4 + p) * 18 + w) * 8192u + (uint32_t)t128 * 16u;
    uint32_t stash = area + (uint32_t)t128 * 16u;
    const uint32_t epoch_c = ld_relaxed(&g_epoch);
    auto xptr = [&](int slot, int jj) INL { return (uint4*)((char*)g_xbuf + ((xoff & ~1u) + (uint32_t)slot * 16384u + (uint32_t)jj * 2048u)); };
    uint32_t A[144];
    float rs0, rs1;
    auto release = [&](int st) INL {
      if (elect) { mbar_arrive_cluster(BAR(B_EMPTY + st), 0); mbar_arrive_cluster(BAR(B_EMPTY + st), 1); }
    };

    {
      const int row = wq * 16 + (lane & 7) + ((lane >> 3) & 1) * 8;
      const uint32_t rbase = area + row * 128;
      float s0[2][4] = {}, q0[2][4] = {}, q1[2][4] = {};
      const uint32_t ones = 0x3F803F80u;
#pragma unroll
      for (int b = 0; b < 8; b++) {
        mbar_wait(BAR(B_XFULL + w * 8 + b), 0);
        if (b == 0) PROF(w, 23);
        if (b == 7) PROF(w, 24);
#pragma unroll
        for (int kk = 0; kk < 4; kk++) {
          const int i = (b * 4 + kk) * 4;
          ldmatrix_x4(rbase + b * 8192 + (((kk * 2 + (lane >> 4)) ^ (row & 7)) << 4), A[i], A[i + 1], A[i + 2], A[i + 3]);
        }
#pragma unroll
        for (int kk = 0; kk < 4; kk++) {
          const int i = (b * 4 + kk) * 4;
          mma_16816(s0[kk & 1], A[i], A[i + 1], A[i + 2], A[i + 3], ones, ones);
          mma_16816(q0[kk & 1], A[i], A[i + 1], A[i + 2], A[i + 3], A[i], A[i + 2]);
          mma_16816(q1[kk & 1], A[i], A[i + 1], A[i + 2], A[i + 3], A[i + 1], A[i + 3]);
        }
      }
      const float mean0 = (s0[0][0] + s0[1][0]) * (1.f / 512.f), mean1 = (s0[0][2] + s0[1][2]) * (1.f / 512.f);
      const uint32_t m0 = pack_bf16(mean0, mean0), m1 = pack_bf16(mean1, mean1);
#pragma unroll
      for (int i = 0; i < 128; i += 2) {
        A[i] = hsub2_bf16(A[i], m0);
        A[i + 1] = hsub2_bf16(A[i + 1], m1);
      }
      float v0 = (g & 1) ? q0[0][1] + q0[1][1] : q0[0][0] + q0[1][0];
      float v1 = (g & 1) ? q1[0][3] + q1[1][3] : q1[0][2] + q1[1][2];
      const int src = 4 * g + (g >> 1);
      v0 = __shfl_sync(0xffffffffu, v0, src);
      v1 = __shfl_sync(0xffffffffu, v1, src);
      v0 = fmaxf(v0 * (1.f / 512.f) - mean0 * mean0, 0.f);
      v1 = fmaxf(v1 * (1.f / 512.f) - mean1 * mean1, 0.f);
      rs0 = rsqrtf(v0 + 1e-5f);
      rs1 = rsqrtf(v1 + 1e-5f);
      bar_sync(1 + w, 128);
      cluster_wait();
      asm volatile("" : "+r"(xoff), "+r"(stash));
      PROF(w, 0);
      release(6); release(7);
      if (elect) mbar_arrive(BAR(B_XDONE));
    }

    auto gu_chunk = [&](float (&acc)[32], int f, int slot, int xslot, int hb) INL {
      const float c0 = rs0 * -1.4426950408889634f, c1 = rs1 * -1.4426950408889634f;
      const float q0 = rs0 * rs0, q1 = rs1 * rs1;
      uint32_t h[4];
#pragma unroll
      for (int i = 0; i < 4; i++) {
        const float ga = acc[f * 8 + 2 * i], gb = acc[f * 8 + 2 * i + 1];
        const float ua = acc[16 + f * 8 + 2 * i], ub = acc[16 + f * 8 + 2 * i + 1];
        const float c = (i & 1) ? c1 : c0, q = (i & 1) ? q1 : q0;
        const float da = 1.f + ex2f(fminf(ga * c, 60.f)), db = 1.f + ex2f(fminf(gb * c, 60.f));
        const float rq = rcpf(da * db) * q;
        h[i] = tagged(pack_bf16(ga * ua * (db * rq), gb * ub * (da * rq)), xoff & 1u);
      }
      const int jj = hb * 2 + f;
      sts_u4(stash + slot * 8192 + jj * 2048, h[0], h[1], h[2], h[3]);
      stg_u4(xptr(xslot, jj), h[0], h[1], h[2], h[3]);
    };
    auto kv_stage = [&](float (&acc)[32], int c, int hb) INL {
      const int srow = wq * 16 + (lane & 7) + ((lane >> 3) & 1) * 8;
      const uint32_t base = area + (3 + c) * 8192 + srow * 128;
#pragma unroll
      for (int jj = 0; jj < 2; jj++) {
        const int a = c * 16 + jj * 8;
        uint32_t r0, r1, r2, r3;
        if (c == 0) {
          r0 = pack_bf16(phi_f(acc[a] * rs0), phi_f(acc[a + 1] * rs0));
          r1 = pack_bf16(phi_f(acc[a + 2] * rs1), phi_f(acc[a + 3] * rs1));
          r2 = pack_bf16(phi_f(acc[a + 4] * rs0), phi_f(acc[a + 5] * rs0));
          r3 = pack_bf16(phi_f(acc[a + 6] * rs1), phi_f(acc[a + 7] * rs1));
        } else {
          r0 = pack_bf16(acc[a] * rs0, acc[a + 1] * rs0);
          r1 = pack_bf16(acc[a + 2] * rs1, acc[a + 3] * rs1);
          r2 = pack_bf16(acc[a + 4] * rs0, acc[a + 5] * rs0);
          r3 = pack_bf16(acc[a + 6] * rs1, acc[a + 7] * rs1);
        }
        stmatrix_x4(base + (((hb * 4 + jj * 2 + (lane >> 4)) ^ (srow & 7)) << 4), r0, r1, r2, r3);
      }
    };
    const uint32_t kvb = area + 5 * 8192;
    const uint32_t kvfrag = kvb + ((lane & 7) + ((lane >> 3) & 1) * 8) * 32 + (lane >> 4) * 16;
    auto signal = [&](int e) INL {
      __syncwarp();
      if (lane == 0) mbar_arrive(BAR(B_EV + w * 2 + e));
    };

    auto pp_wait = [&]() INL { bar_sync(3 + w, 256); };
    auto pp_pass = [&]() INL { bar_arrive(3 + (w ^ 1), 256); };
    if (w == 1) pp_pass();
    int tw1 = 0, tw2 = 0, tw3 = 0;
#pragma unroll 1
    for (int t = 0; t < 5; t++) {
      const uint32_t ph = t & 1;
      const int kind = odd ? (t < 2 ? K_KV : K_GU) : (t < 4 ? K_GU : K_Q);
      const int slot = odd ? t - 2 : t, xslot = odd ? t + 4 : t;
      static_for<2>([&](auto hc) INL {
        constexpr int hb = decltype(hc)::value;
        float acc[32];
        TWAIT(tw2, pp_wait());
        static_for<4>([&](auto kc) INL {
          constexpr int kq = decltype(kc)::value, k = hb * 4 + kq;
          TWAIT(tw1, mbar_wait(BAR(B_FULL + k), ph));
          wgmma_fence();
          static_for<8>([&](auto kkc) INL {
            constexpr int kk = decltype(kkc)::value, i = (kq * 8 + kk) * 4;
            wgmma_n64_rs<(kq | kk) != 0, desc_lo(stage_off(k) + kk * 1024, 8192), kHi64>(acc, A[i], A[i + 1], A[i + 2], A[i + 3]);
          });
          wgmma_commit();
          if (kq == 2) pp_pass();
          if (kq > 0) {
            wgmma_wait<1>();
            release(k - 1);
          }
        });
        TWAIT(tw3, wgmma_wait<0>());
        release(hb * 4 + 3);
        if (hb == 0 && t == 0) xoff |= (epoch_c & 1u) ^ 1u;
        if (kind == K_GU) {
          gu_chunk(acc, 0, slot, xslot, hb);
          gu_chunk(acc, 1, slot, xslot, hb);
        } else if (kind == K_KV) {
          if (hb == 0 && t == 0) sts_u4(stash + 5 * 8192, 0x3F803F80u, 0x3F803F80u, 0x3F803F80u, 0x3F803F80u);
          kv_stage(acc, 0, hb);
          kv_stage(acc, 1, hb);
          if (hb == 1) {
            float kvacc[36];
            const int par = (xoff & 1u) ^ 1u;
            fence_proxy_async();
            bar_sync(1 + w, 128);
            wgmma_fence();
            static_for<4>([&](auto kkc) INL {
              constexpr int kk = decltype(kkc)::value;
              wgmma_n72_ss_tt<kk != 0, desc_lo(3 * 8192 + kk * 2048, 0), desc_lo(4 * 8192 + kk * 2048, 8192 - kk * 2048)>(kvacc, dbase + w * 4096);
            });
            wgmma_commit();
            wgmma_wait<0>();
            float c[8];
#pragma unroll
            for (int i = 0; i < 8; i++)
              c[i] = wq == 0 ? kvacc[i] : (wq == 1 ? kvacc[8 + i] : (wq == 2 ? kvacc[16 + i] : kvacc[24 + i]));
            const int head = (2 * p + t) * 4 + wq;
            float* kvp = &g_kv[par][head][0][0];
            red_add_v2(kvp + g * 16 + 2 * tq, c[0], c[1]);
            red_add_v2(kvp + (g + 8) * 16 + 2 * tq, c[2], c[3]);
            red_add_v2(kvp + g * 16 + 8 + 2 * tq, c[4], c[5]);
            red_add_v2(kvp + (g + 8) * 16 + 8 + 2 * tq, c[6], c[7]);
            if (tq == 0) {
              red_add(&g_z[par][head][g], kvacc[32]);
              red_add(&g_z[par][head][g + 8], kvacc[34]);
            }
            signal(t);
          }
        } else {
          uint32_t aq[4][4];
#pragma unroll
          for (int c = 0; c < 4; c++) {
            const int a = c * 8;
            aq[c][0] = pack_bf16(phi_f(acc[a] * rs0), phi_f(acc[a + 1] * rs0));
            aq[c][1] = pack_bf16(phi_f(acc[a + 2] * rs1), phi_f(acc[a + 3] * rs1));
            aq[c][2] = pack_bf16(phi_f(acc[a + 4] * rs0), phi_f(acc[a + 5] * rs0));
            aq[c][3] = pack_bf16(phi_f(acc[a + 6] * rs1), phi_f(acc[a + 7] * rs1));
          }
          if (hb == 0) mbar_wait(BAR(B_KVREADY), 0);
          uint32_t Bf[4][6];
#pragma unroll
          for (int c = 0; c < 4; c++) {
            ldmatrix_x4_trans(kvfrag + (hb * 4 + c) * 512, Bf[c][0], Bf[c][1], Bf[c][2], Bf[c][3]);
            Bf[c][4] = lds_u32(kvb + 4096 + (hb * 4 + c) * 32 + tq * 4);
            Bf[c][5] = lds_u32(kvb + 4096 + (hb * 4 + c) * 32 + 16 + tq * 4);
          }
          float n0[4][4] = {}, n1[4][4] = {}, dn[4][4] = {};
#pragma unroll
          for (int c = 0; c < 4; c++) {
            mma_16816(dn[c], aq[c][0], aq[c][1], aq[c][2], aq[c][3], Bf[c][4], Bf[c][5]);
            mma_16816(n0[c], aq[c][0], aq[c][1], aq[c][2], aq[c][3], Bf[c][0], Bf[c][1]);
            mma_16816(n1[c], aq[c][0], aq[c][1], aq[c][2], aq[c][3], Bf[c][2], Bf[c][3]);
          }
          if (hb == 1) bar_sync(1 + w, 128);
          const uint32_t tg = xoff & 1u;
#pragma unroll
          for (int c = 0; c < 4; c++) {
            const float i0 = __fdividef(1.f, dn[c][0] + 1e-6f), i1 = __fdividef(1.f, dn[c][2] + 1e-6f);
            aq[c][0] = tagged(pack_bf16(n0[c][0] * i0, n0[c][1] * i0), tg);
            aq[c][1] = tagged(pack_bf16(n0[c][2] * i1, n0[c][3] * i1), tg);
            aq[c][2] = tagged(pack_bf16(n1[c][0] * i0, n1[c][1] * i0), tg);
            aq[c][3] = tagged(pack_bf16(n1[c][2] * i1, n1[c][3] * i1), tg);
          }
#pragma unroll
          for (int c = 0; c < 4; c++) {
            stg_u4(xptr(4 + hb, c), aq[c][0], aq[c][1], aq[c][2], aq[c][3]);
            sts_u4(stash + (4 + hb) * 8192 + c * 2048, aq[c][0], aq[c][1], aq[c][2], aq[c][3]);
          }
        }
      });
      PROF(w, 1 + 2 * t);
    }
    PROF(w, 10);

    const int n_own = odd ? 3 : 6;
    auto load_a = [&](int kb) INL {
      if (kb < n_own) {
#pragma unroll
        for (int jj = 0; jj < 4; jj++) {
          const int i = (kb * 4 + jj) * 4;
          lds_u4(stash + kb * 8192 + jj * 2048, A[i], A[i + 1], A[i + 2], A[i + 3]);
        }
      } else {
        const int xs = odd ? kb - 3 : kb;
#pragma unroll
        for (int jj = 0; jj < 4; jj++) {
          const int i = (kb * 4 + jj) * 4;
          ldg_poll_u4(xptr(xs, jj), A[i], A[i + 1], A[i + 2], A[i + 3]);
        }
      }
    };
    auto fix_a = [&](int kb) INL {
      if (kb >= n_own) {
        const int xs = odd ? kb - 3 : kb;
        recv_group<4>(xptr(xs, 0), &A[kb * 16], xoff & 1u);
      }
    };
#pragma unroll
    for (int kb = 0; kb < 7; kb++) load_a(kb);
    PROF(w, 11);

    const uint32_t ooff = (uint32_t)(m * 128 + w * 64 + wq * 16 + (lane >> 3)) * kD + odd * 256 + p * 64 + (lane & 7) * 8;
    float acc2[2][32];
    uint32_t poff = (uint32_t)((m * 2 + odd) * 24 + w) * 8192u + (uint32_t)t128 * 16u;
    asm volatile("" : "+r"(poff));
    auto pptr = [&](int dest, int sl) INL { return (uint4*)((char*)g_pbuf + (poff + (uint32_t)(dest * 3 + sl) * 16384u)); };
    uint32_t P[3][16];
    uint4 xr[4];
    auto send = [&](float (&acc)[32], int bi) INL {
      uint4* dst = pptr((p + 1 + bi) & 3, bi);
#pragma unroll
      for (int q = 0; q < 4; q++)
        stg_u4(dst + q * 128, tagged(pack_bf16(acc[q * 8], acc[q * 8 + 1]), xoff & 1u), tagged(pack_bf16(acc[q * 8 + 2], acc[q * 8 + 3]), xoff & 1u),
               tagged(pack_bf16(acc[q * 8 + 4], acc[q * 8 + 5]), xoff & 1u), tagged(pack_bf16(acc[q * 8 + 6], acc[q * 8 + 7]), xoff & 1u));
      PROF(w, 12 + 2 * bi);
    };
    auto fetch = [&](int sl) INL {
#pragma unroll
      for (int q = 0; q < 4; q++) ldg_poll_u4(pptr(p, sl) + q * 128, P[sl][q * 4], P[sl][q * 4 + 1], P[sl][q * 4 + 2], P[sl][q * 4 + 3]);
    };
    static_for<36>([&](auto ic) INL {
      constexpr int i = decltype(ic)::value, bi = p2_bi(i), kb = p2_kb(i), j = i >> 1, st = j & 7;
      if (i == 9) { load_a(7); load_a(8); }
      if (i == 14) PROF(w, 2);
      if (bi == 0 && kb >= 3) fix_a(kb);
      if (i == 15) PROF(w, 4);
      if (i == 7) PROF(w, 6);
      if (i == 0 || i == 7 || i == 14 || i == 18 || i == 27) pp_wait();
      if ((i & 1) == 0) mbar_wait(BAR(B_FULL + st), (5 + (j >> 3)) & 1);
      wgmma_fence();
      static_for<4>([&](auto kkc) INL {
        constexpr int kk = decltype(kkc)::value, a = (kb * 4 + kk) * 4;
        wgmma_n64_rs<(kb | kk) != 0, desc_lo(stage_off(st) + (i & 1) * 8192 + kk * 2048, 0), kHi128>(acc2[bi & 1], A[a], A[a + 1], A[a + 2], A[a + 3]);
      });
      wgmma_commit();
      if (i == 4 || i == 11 || i == 15 || i == 24 || (i == 33 && w == 0)) pp_pass();
      if (i > 0) {
        wgmma_wait<1>();
        if ((i & 1) == 0 && j - 1 <= 9) release((j - 1) & 7);
      }
      if constexpr (i == 17) { send(acc2[0], 0); wgmma_wait<0>(); send(acc2[1], 1); }
      if constexpr (i == 26) { wgmma_wait<0>(); send(acc2[0], 2); }
      if constexpr (i == 29) fetch(0);
      if constexpr (i == 30) fetch(1);
      if constexpr (i == 28) {
#pragma unroll
        for (int q = 0; q < 4; q++) xr[q] = __ldg((const uint4*)(x + ooff + q * 4 * kD));
      }
      if constexpr (i == 32) fetch(2);
    });
#pragma unroll
    for (int sl = 0; sl < 3; sl++) { PROF(w, 13 + 2 * sl); recv_group<4>(pptr(p, sl), &P[sl][0], xoff & 1u); }
    wgmma_wait<0>();
    PROF(w, 18);
    {
      const uint32_t tile = area + wq * 4352;
#pragma unroll
      for (int q = 0; q < 8; q++) {
        float rr[4];
#pragma unroll
        for (int e = 0; e < 4; e++) rr[e] = acc2[1][q * 4 + e];
#pragma unroll
        for (int sl = 0; sl < 3; sl++) {
          rr[0] += __uint_as_float(P[sl][2 * q] << 16);
          rr[1] += __uint_as_float(P[sl][2 * q] & 0xffff0000u);
          rr[2] += __uint_as_float(P[sl][2 * q + 1] << 16);
          rr[3] += __uint_as_float(P[sl][2 * q + 1] & 0xffff0000u);
        }
        const uint32_t ad = tile + g * 272 + q * 32 + tq * 8;
        asm volatile("st.shared.v2.f32 [%0], {%1,%2};" ::"r"(ad), "f"(rr[0]), "f"(rr[1]) : "memory");
        asm volatile("st.shared.v2.f32 [%0], {%1,%2};" ::"r"(ad + 8 * 272), "f"(rr[2]), "f"(rr[3]) : "memory");
      }
      __syncwarp();
#pragma unroll
      for (int q = 0; q < 4; q++) {
        const uint32_t ad = tile + ((lane >> 3) + 4 * q) * 272 + (lane & 7) * 32;
        uint32_t v[8];
        lds_u4(ad, v[0], v[1], v[2], v[3]);
        lds_u4(ad + 16, v[4], v[5], v[6], v[7]);
        const uint32_t xv[4] = {xr[q].x, xr[q].y, xr[q].z, xr[q].w};
        uint32_t o[4];
#pragma unroll
        for (int e = 0; e < 4; e++)
          o[e] = pack_bf16(__uint_as_float(v[2 * e]) + __uint_as_float(xv[e] << 16), __uint_as_float(v[2 * e + 1]) + __uint_as_float(xv[e] & 0xffff0000u));
        stg_u4(out + ooff + q * 4 * kD, o[0], o[1], o[2], o[3]);
      }
    }
    PROF(w, 19);
    if (tid == 0) {
      const uint32_t old = atomicAdd(&g_done, 1u);
      if ((old & 127u) == 127u) st_relaxed(&g_epoch, ld_relaxed(&g_epoch) + 1u);
    }
  }
#undef BAR
}

typedef CUresult (*EncodeFn)(CUtensorMap*, CUtensorMapDataType, cuuint32_t, void*, const cuuint64_t*, const cuuint64_t*,
                             const cuuint32_t*, const cuuint32_t*, CUtensorMapInterleave, CUtensorMapSwizzle,
                             CUtensorMapL2promotion, CUtensorMapFloatOOBfill);

void make_map(EncodeFn enc, CUtensorMap* tm, const void* ptr, int rows, int cols, bool narrow) {
  cuuint64_t gd[2] = {(cuuint64_t)cols, (cuuint64_t)rows};
  cuuint64_t gs[1] = {(cuuint64_t)cols * 2};
  cuuint32_t bd[2] = {narrow ? 32u : 64u, narrow ? 128u : 64u};
  cuuint32_t es[2] = {1, 1};
  enc(tm, CU_TENSOR_MAP_DATA_TYPE_BFLOAT16, 2, const_cast<void*>(ptr), gd, gs, bd, es, CU_TENSOR_MAP_INTERLEAVE_NONE,
      narrow ? CU_TENSOR_MAP_SWIZZLE_64B : CU_TENSOR_MAP_SWIZZLE_128B, CU_TENSOR_MAP_L2_PROMOTION_L2_256B, CU_TENSOR_MAP_FLOAT_OOB_FILL_NONE);
}

}

extern "C" void kernel_launch(void* const* d_in, const int* in_sizes, int n_in, void* d_out, int out_size) {
  static EncodeFn enc = nullptr;
  if (!enc) {
    void* fn = nullptr;
    cudaDriverEntryPointQueryResult qr;
    cudaGetDriverEntryPoint("cuTensorMapEncodeTiled", &fn, cudaEnableDefault, &qr);
    enc = (EncodeFn)fn;
    cudaFuncSetAttribute(fused_kernel, cudaFuncAttributeMaxDynamicSharedMemorySize, kSmemBytes);
  }
  CUtensorMap tm_x, tm_wqkv, tm_w1, tm_w3, tm_w2, tm_wo;
  make_map(enc, &tm_x, d_in[0], kS, kD, false);
  make_map(enc, &tm_wqkv, d_in[1], kD, 3 * kD, true);
  make_map(enc, &tm_wo, d_in[2], kD, kD, false);
  make_map(enc, &tm_w1, d_in[4], kD, kF, true);
  make_map(enc, &tm_w3, d_in[5], kD, kF, true);
  make_map(enc, &tm_w2, d_in[6], kF, kD, false);
  fused_kernel<<<128, 384, kSmemBytes>>>(tm_x, tm_wqkv, tm_w1, tm_w3, tm_w2, tm_wo, (const __nv_bfloat16*)d_in[0],
                                         (__nv_bfloat16*)d_out);
}
```

```cpp
#include <cuda_runtime.h>
#include <cuda_bf16.h>
#include <cuda.h>
#include <stdint.h>

extern __shared__ __align__(1024) uint8_t smem_raw[];

namespace {

constexpr int kS = 2048, kD = 512, kF = 1792;
#define XPOS 1
constexpr uint32_t kSpinLimit = 1u << 22;

__device__ uint4    g_xbuf[16][4][9][2][4][128];
__device__ uint4    g_pbuf[16][2][4][3][2][4][128];
__device__ float    g_kv[2][32][16][16];
__device__ float    g_z[2][32][16];
__device__ uint32_t g_kvcnt[4][32];
__device__ uint32_t g_epoch;
__device__ uint32_t g_done;
#define PROF(wg, i) do {} while (0)
#define TWAIT(acc, stmt) do { stmt; } while (0)

__device__ __forceinline__ uint32_t smem_u32(const void* p) { return (uint32_t)__cvta_generic_to_shared(p); }
__device__ __forceinline__ void mbar_init(uint32_t bar, uint32_t cnt) {
  asm volatile("mbarrier.init.shared::cta.b64 [%0], %1;" ::"r"(bar), "r"(cnt) : "memory");
}
__device__ __forceinline__ void mbar_expect_tx(uint32_t bar, uint32_t bytes) {
  asm volatile("mbarrier.arrive.expect_tx.shared::cta.b64 _, [%0], %1;" ::"r"(bar), "r"(bytes) : "memory");
}
__device__ __forceinline__ void mbar_arrive(uint32_t bar) {
  asm volatile("mbarrier.arrive.shared::cta.b64 _, [%0];" ::"r"(bar) : "memory");
}
__device__ __forceinline__ void mbar_wait(uint32_t bar, uint32_t parity) {
  asm volatile(
      "{\n.reg .pred p;\n"
      "LAB_WAIT:\n"
      "mbarrier.try_wait.parity.shared::cta.b64 p, [%0], %1;\n"
      "@p bra DONE;\n"
      "bra LAB_WAIT;\n"
      "DONE:\n}" ::"r"(bar), "r"(parity) : "memory");
}
__device__ __forceinline__ void tma_load_2d(uint32_t dst, const CUtensorMap* tm, uint32_t bar, int c0, int c1) {
  asm volatile(
      "cp.async.bulk.tensor.2d.shared::cluster.global.mbarrier::complete_tx::bytes [%0], [%1, {%3, %4}], [%2];" ::"r"(dst),
      "l"(tm), "r"(bar), "r"(c0), "r"(c1)
      : "memory");
}
__device__ __forceinline__ void tma_load_2d_mc(uint32_t dst, const CUtensorMap* tm, uint32_t bar, int c0, int c1) {
  asm volatile(
      "cp.async.bulk.tensor.2d.shared::cluster.global.mbarrier::complete_tx::bytes.multicast::cluster [%0], [%1, {%3, %4}], [%2], %5;" ::"r"(dst),
      "l"(tm), "r"(bar), "r"(c0), "r"(c1), "h"((uint16_t)3)
      : "memory");
}
__device__ __forceinline__ void mbar_arrive_cluster(uint32_t bar, uint32_t cta) {
  asm volatile("{\n.reg .b32 ra;\nmapa.shared::cluster.u32 ra, %0, %1;\nmbarrier.arrive.shared::cluster.b64 _, [ra];\n}" ::"r"(bar), "r"(cta) : "memory");
}
__device__ __forceinline__ void prefetch_tmap(const CUtensorMap* tm) {
  asm volatile("prefetch.tensormap [%0];" ::"l"(tm) : "memory");
}
__device__ __forceinline__ void wgmma_fence() { asm volatile("wgmma.fence.sync.aligned;" ::: "memory"); }
__device__ __forceinline__ void wgmma_commit() { asm volatile("wgmma.commit_group.sync.aligned;" ::: "memory"); }
template <int N>
__device__ __forceinline__ void wgmma_wait() { asm volatile("wgmma.wait_group.sync.aligned %0;" ::"n"(N) : "memory"); }
__device__ __forceinline__ void bar_sync(int id, int n) { asm volatile("bar.sync %0, %1;" ::"r"(id), "r"(n) : "memory"); }
__device__ __forceinline__ void bar_arrive(int id, int n) { asm volatile("bar.arrive %0, %1;" ::"r"(id), "r"(n) : "memory"); }
__device__ __forceinline__ void fence_proxy_async() { asm volatile("fence.proxy.async.shared::cta;" ::: "memory"); }

__device__ __forceinline__ uint32_t ld_acquire(const uint32_t* p) {
  uint32_t v;
  asm volatile("ld.acquire.gpu.global.u32 %0, [%1];" : "=r"(v) : "l"(p) : "memory");
  return v;
}
__device__ __forceinline__ uint32_t ld_relaxed(const uint32_t* p) {
  uint32_t v;
  asm volatile("ld.relaxed.gpu.global.u32 %0, [%1];" : "=r"(v) : "l"(p));
  return v;
}
__device__ __forceinline__ void cluster_wait() { asm volatile("barrier.cluster.wait.aligned;" ::: "memory"); }
__device__ __forceinline__ void st_relaxed(uint32_t* p, uint32_t v) {
  asm volatile("st.relaxed.gpu.global.u32 [%0], %1;" ::"l"(p), "r"(v) : "memory");
}
__device__ __forceinline__ void wait_flag_eq(const uint32_t* p, uint32_t val) {
  uint32_t it = 0;
  while (ld_acquire(p) != val) {
    if (++it > kSpinLimit) break;
  }
}
__device__ __forceinline__ void wait_count_ge(const uint32_t* p, uint32_t val) {
  uint32_t it = 0;
  while ((int32_t)(ld_acquire(p) - val) < 0) {
    __nanosleep(64);
    if (++it > kSpinLimit) break;
  }
}
__device__ __forceinline__ void ldg_poll_u4(const void* p, uint32_t& a, uint32_t& b, uint32_t& c, uint32_t& d) {
  asm volatile("ld.relaxed.gpu.global.v4.u32 {%0,%1,%2,%3}, [%4];" : "=r"(a), "=r"(b), "=r"(c), "=r"(d) : "l"(p) : "memory");
}
template <int N>
__device__ __forceinline__ void recv_group(const uint4* p, uint32_t* r, uint32_t tag) {
  uint32_t it = 0;
  while (true) {
    uint32_t bad = 0u;
#pragma unroll
    for (int i = 0; i < 4 * N; i++) bad |= r[i] ^ tag;
    if (!__any_sync(0xffffffffu, (bad & 1u) != 0u) || ++it > kSpinLimit) break;
#pragma unroll
    for (int q = 0; q < N; q++) ldg_poll_u4(p + q * 128, r[q * 4], r[q * 4 + 1], r[q * 4 + 2], r[q * 4 + 3]);
  }
}
__device__ __forceinline__ uint32_t tagged(uint32_t v, uint32_t tag) { return (v & ~1u) | tag; }
__device__ __forceinline__ float4 ldg_cg_f4(const void* p) {
  float4 v;
  asm volatile("ld.global.cg.v4.f32 {%0,%1,%2,%3}, [%4];" : "=f"(v.x), "=f"(v.y), "=f"(v.z), "=f"(v.w) : "l"(p) : "memory");
  return v;
}
__device__ __forceinline__ void stg_u4(void* p, uint32_t a, uint32_t b, uint32_t c, uint32_t d) {
  asm volatile("st.global.v4.u32 [%0], {%1,%2,%3,%4};" ::"l"(p), "r"(a), "r"(b), "r"(c), "r"(d) : "memory");
}
__device__ __forceinline__ void stg_f4(void* p, float a, float b, float c, float d) {
  asm volatile("st.global.v4.f32 [%0], {%1,%2,%3,%4};" ::"l"(p), "f"(a), "f"(b), "f"(c), "f"(d) : "memory");
}
__device__ __forceinline__ void sts_u4(uint32_t addr, uint32_t a, uint32_t b, uint32_t c, uint32_t d) {
  asm volatile("st.shared.v4.u32 [%0], {%1,%2,%3,%4};" ::"r"(addr), "r"(a), "r"(b), "r"(c), "r"(d) : "memory");
}
__device__ __forceinline__ void lds_u4(uint32_t addr, uint32_t& a, uint32_t& b, uint32_t& c, uint32_t& d) {
  asm volatile("ld.shared.v4.u32 {%0,%1,%2,%3}, [%4];" : "=r"(a), "=r"(b), "=r"(c), "=r"(d) : "r"(addr) : "memory");
}
__device__ __forceinline__ uint32_t lds_u32(uint32_t addr) {
  uint32_t v;
  asm volatile("ld.shared.u32 %0, [%1];" : "=r"(v) : "r"(addr) : "memory");
  return v;
}
__device__ __forceinline__ void ldmatrix_x4(uint32_t addr, uint32_t& a, uint32_t& b, uint32_t& c, uint32_t& d) {
  asm volatile("ldmatrix.sync.aligned.m8n8.x4.shared.b16 {%0,%1,%2,%3}, [%4];" : "=r"(a), "=r"(b), "=r"(c), "=r"(d) : "r"(addr) : "memory");
}
__device__ __forceinline__ void ldmatrix_x4_trans(uint32_t addr, uint32_t& a, uint32_t& b, uint32_t& c, uint32_t& d) {
  asm volatile("ldmatrix.sync.aligned.m8n8.x4.trans.shared.b16 {%0,%1,%2,%3}, [%4];" : "=r"(a), "=r"(b), "=r"(c), "=r"(d) : "r"(addr) : "memory");
}
__device__ __forceinline__ void stmatrix_x4(uint32_t addr, uint32_t a, uint32_t b, uint32_t c, uint32_t d) {
  asm volatile("stmatrix.sync.aligned.m8n8.x4.shared.b16 [%0], {%1,%2,%3,%4};" ::"r"(addr), "r"(a), "r"(b), "r"(c), "r"(d) : "memory");
}
__device__ __forceinline__ void mma_16816(float (&c)[4], uint32_t a0, uint32_t a1, uint32_t a2, uint32_t a3, uint32_t b0, uint32_t b1) {
  asm(
      "mma.sync.aligned.m16n8k16.row.col.f32.bf16.bf16.f32 {%0,%1,%2,%3}, {%4,%5,%6,%7}, {%8,%9}, {%0,%1,%2,%3};"
      : "+f"(c[0]), "+f"(c[1]), "+f"(c[2]), "+f"(c[3])
      : "r"(a0), "r"(a1), "r"(a2), "r"(a3), "r"(b0), "r"(b1));
}
__device__ __forceinline__ uint32_t pack_bf16(float lo, float hi) {
  uint32_t r;
  asm("cvt.rn.bf16x2.f32 %0, %1, %2;" : "=r"(r) : "f"(hi), "f"(lo));
  return r;
}
__device__ __forceinline__ uint32_t hsub2_bf16(uint32_t a, uint32_t b) {
  uint32_t r;
  asm("sub.rn.bf16x2 %0, %1, %2;" : "=r"(r) : "r"(a), "r"(b));
  return r;
}
__device__ __forceinline__ float ex2f(float x) {
  float r;
  asm("ex2.approx.ftz.f32 %0, %1;" : "=f"(r) : "f"(x));
  return r;
}
__device__ __forceinline__ float rcpf(float x) {
  float r;
  asm("rcp.approx.ftz.f32 %0, %1;" : "=f"(r) : "f"(x));
  return r;
}
__device__ __forceinline__ void red_add_v2(float* p, float a, float b) {
  asm volatile("red.relaxed.gpu.global.add.v2.f32 [%0], {%1,%2};" ::"l"(p), "f"(a), "f"(b) : "memory");
}
__device__ __forceinline__ void red_add(float* p, float a) {
  asm volatile("red.relaxed.gpu.global.add.f32 [%0], %1;" ::"l"(p), "f"(a) : "memory");
}
__device__ __forceinline__ float phi_f(float t) {
  float e = ex2f(t * 1.4426950408889634f);
  return (t > 0.f ? t + 1.f : e) + 1e-6f;
}

#define R8(a, o) "+f"(a[o + 0]), "+f"(a[o + 1]), "+f"(a[o + 2]), "+f"(a[o + 3]), "+f"(a[o + 4]), "+f"(a[o + 5]), "+f"(a[o + 6]), "+f"(a[o + 7])

#define W8(a, o) "=f"(a[o + 0]), "=f"(a[o + 1]), "=f"(a[o + 2]), "=f"(a[o + 3]), "=f"(a[o + 4]), "=f"(a[o + 5]), "=f"(a[o + 6]), "=f"(a[o + 7])
#define D32 "{%0,%1,%2,%3,%4,%5,%6,%7,%8,%9,%10,%11,%12,%13,%14,%15,%16,%17,%18,%19,%20,%21,%22,%23,%24,%25,%26,%27,%28,%29,%30,%31}"
#define D36 "{%0,%1,%2,%3,%4,%5,%6,%7,%8,%9,%10,%11,%12,%13,%14,%15,%16,%17,%18,%19,%20,%21,%22,%23,%24,%25,%26,%27,%28,%29,%30,%31,%32,%33,%34,%35}"

constexpr uint32_t kHi128 = (1024u >> 4) | (1u << 30);
constexpr uint32_t kHi64 = (512u >> 4) | (2u << 30);
__host__ __device__ constexpr uint32_t desc_lo(uint32_t off, uint32_t lbo) { return (off >> 4) | ((lbo >> 4) << 16); }

template <bool ACC, uint32_t LO, uint32_t HI>
__device__ __forceinline__ void wgmma_n64_rs(float (&d)[32], uint32_t a0, uint32_t a1, uint32_t a2, uint32_t a3) {
  if (ACC) {
    asm volatile(
        "{\n.reg .pred p;\n.reg .b32 lo;\n.reg .b64 dd;\nsetp.eq.b32 p, 0, 0;\nmov.u32 lo, 64;\nadd.u32 lo, lo, %36;\nmov.b64 dd, {lo, %37};\n"
        "wgmma.mma_async.sync.aligned.m64n64k16.f32.bf16.bf16 " D32 ", {%32,%33,%34,%35}, dd, p, 1, 1, 1;\n}"
        : R8(d, 0), R8(d, 8), R8(d, 16), R8(d, 24)
        : "r"(a0), "r"(a1), "r"(a2), "r"(a3), "n"(LO), "n"(HI));
  } else {
    asm volatile(
        "{\n.reg .pred p;\n.reg .b32 lo;\n.reg .b64 dd;\nsetp.ne.b32 p, 0, 0;\nmov.u32 lo, 64;\nadd.u32 lo, lo, %36;\nmov.b64 dd, {lo, %37};\n"
        "wgmma.mma_async.sync.aligned.m64n64k16.f32.bf16.bf16 " D32 ", {%32,%33,%34,%35}, dd, p, 1, 1, 1;\n}"
        : W8(d, 0), W8(d, 8), W8(d, 16), W8(d, 24)
        : "r"(a0), "r"(a1), "r"(a2), "r"(a3), "n"(LO), "n"(HI));
  }
}
template <bool ACC, uint32_t LOA, uint32_t LOB>
__device__ __forceinline__ void wgmma_n72_ss_tt(float (&d)[36], uint32_t base) {
  if (ACC) {
    asm volatile(
        "{\n.reg .pred p;\n.reg .b32 lo;\n.reg .b64 da, db;\nsetp.eq.b32 p, 0, 0;\n"
        "add.u32 lo, %36, %37;\nmov.b64 da, {lo, %39};\nadd.u32 lo, %36, %38;\nmov.b64 db, {lo, %39};\n"
        "wgmma.mma_async.sync.aligned.m64n72k16.f32.bf16.bf16 " D36 ", da, db, p, 1, 1, 1, 1;\n}"
        : R8(d, 0), R8(d, 8), R8(d, 16), R8(d, 24), "+f"(d[32]), "+f"(d[33]), "+f"(d[34]), "+f"(d[35])
        : "r"(base), "n"(LOA), "n"(LOB), "n"(kHi128));
  } else {
    asm volatile(
        "{\n.reg .pred p;\n.reg .b32 lo;\n.reg .b64 da, db;\nsetp.ne.b32 p, 0, 0;\n"
        "add.u32 lo, %36, %37;\nmov.b64 da, {lo, %39};\nadd.u32 lo, %36, %38;\nmov.b64 db, {lo, %39};\n"
        "wgmma.mma_async.sync.aligned.m64n72k16.f32.bf16.bf16 " D36 ", da, db, p, 1, 1, 1, 1;\n}"
        : W8(d, 0), W8(d, 8), W8(d, 16), W8(d, 24), "=f"(d[32]), "=f"(d[33]), "=f"(d[34]), "=f"(d[35])
        : "r"(base), "n"(LOA), "n"(LOB), "n"(kHi128));
  }
}

#define INL __attribute__((always_inline))
template <int V> struct IC { static constexpr int value = V; };
template <int N, int I = 0, typename F>
__device__ __forceinline__ void static_for(F&& f) {
  if constexpr (I < N) { f(IC<I>{}); static_for<N, I + 1>(f); }
}

__host__ __device__ constexpr uint32_t stage_off(int st) {
  return st < 6 ? 131072u + (uint32_t)st * 16384u : (uint32_t)(st - 6) * 65536u + 49152u;
}

constexpr int B_FULL = 0, B_EMPTY = 8, B_XFULL = 16, B_XDONE = 32, B_KVREADY = 33, B_EV = 34, B_COUNT = 38;
constexpr uint32_t kBarOff = 229376;
constexpr int kSmemBytes = 229376 + 1024;

__host__ __device__ constexpr int p2_bi(int i) { return i < 7 ? 0 : i < 14 ? 1 : i < 16 ? 0 : i < 18 ? 1 : i / 9; }
__host__ __device__ constexpr int p2_kb(int i) { return i < 7 ? i : i < 14 ? i - 7 : i < 16 ? i - 7 : i < 18 ? i - 9 : i % 9; }

enum { K_NONE = 0, K_GU = 1, K_KV = 2, K_Q = 3 };

__global__ void __cluster_dims__(2, 1, 1) __launch_bounds__(384, 1)
fused_kernel(const __grid_constant__ CUtensorMap tm_x, const __grid_constant__ CUtensorMap tm_wqkv,
             const __grid_constant__ CUtensorMap tm_w1, const __grid_constant__ CUtensorMap tm_w3,
             const __grid_constant__ CUtensorMap tm_w2, const __grid_constant__ CUtensorMap tm_wo,
             const __nv_bfloat16* __restrict__ x, __nv_bfloat16* __restrict__ out,
             const __nv_bfloat16* __restrict__ wqkv, const __nv_bfloat16* __restrict__ w1, const __nv_bfloat16* __restrict__ w3) {
  const uint32_t sbase = smem_u32(smem_raw);
  const uint32_t bars = sbase + kBarOff;
  const int tid = threadIdx.x, lane = tid & 31;
  const int warp = __shfl_sync(0xffffffffu, tid >> 5, 0);
  const int cr = blockIdx.x & 1;
  const int r = (blockIdx.x >> 1) & 7, m = ((blockIdx.x >> 4) << 1) | cr, p = r >> 1, odd = r & 1;
#define BAR(i) (bars + 8u * (uint32_t)(i))
  if (tid < 256) {
    const char* xp = (const char*)(x + (size_t)(m * 128) * kD) + tid * 512;
#pragma unroll
    for (int i = 0; i < 4; i++) asm volatile("prefetch.global.L2 [%0];" ::"l"(xp + i * 128));
  } else if (tid >= 288) {
    const __nv_bfloat16* wp = odd ? wqkv + 512 + cr * 512 + 128 * p : (cr ? w3 : w1) + 7 * p * 64;
    const int ld = odd ? 3 * kD : kF;
    for (int k = tid - 288; k < 512; k += 96) asm volatile("prefetch.global.L2 [%0];" ::"l"(wp + (size_t)k * ld));
  }
  if (tid == 256) {
    if ((sbase & 0x3FFFFu) != 1024u) __trap();
#pragma unroll
    for (int i = 0; i < 16; i++) mbar_init(BAR(B_XFULL + i), 1);
    fence_proxy_async();
#pragma unroll
    for (int b = 0; b < 8; b++) {
      mbar_expect_tx(BAR(B_XFULL + b), 8192);
      tma_load_2d(sbase + (b >> 3) * 65536 + (b & 7) * 8192, &tm_x, BAR(B_XFULL + b), (b & 7) * 64, m * 128 + (b >> 3) * 64);
    }
#pragma unroll
    for (int i = 0; i < 8; i++) { mbar_init(BAR(B_FULL + i), 1); mbar_init(BAR(B_EMPTY + i), 4); }
#pragma unroll
    for (int i = 0; i < 4; i++) mbar_init(BAR(B_EV + i), 4);
    mbar_init(BAR(B_XDONE), 2);
    mbar_init(BAR(B_KVREADY), 3);
    asm volatile("fence.mbarrier_init.release.cluster;" ::: "memory");
    fence_proxy_async();
  } else if (tid == 288) {
    prefetch_tmap(odd ? &tm_wqkv : (cr ? &tm_w3 : &tm_w1));
  }
  __syncwarp();
  asm volatile("barrier.cluster.arrive.relaxed.aligned;" ::: "memory");
  PROF((tid >> 7), 21);
  __syncthreads();

  if (warp >= 8) {
    asm volatile("setmaxnreg.dec.sync.aligned.u32 24;");
    PROF(2, 3);
    cluster_wait();
    PROF(2, 2);
    const uint32_t epoch = warp == 8 ? 0u : ld_relaxed(&g_epoch);
    const uint32_t tag = epoch + 1u;
    const int par = epoch & 1;
    if (warp == 8) {
      if (lane == 0) {
        int twp = 0;
        for (int j = 0; j < 10; j++) {
          const CUtensorMap* tm;
          int col;
          if (!odd) {
            if (j < 8) { tm = cr ? &tm_w3 : &tm_w1; col = 7 * p * 64 + j * 32; }
            else { tm = &tm_wqkv; col = 128 * p + (j - 8) * 64 + cr * 32; }
          } else {
            if (j < 4) { tm = &tm_wqkv; col = 512 + cr * 512 + 128 * p + j * 32; }
            else { tm = cr ? &tm_w3 : &tm_w1; col = (7 * p + 4) * 64 + (j - 4) * 32; }
          }
          const int t = j >> 1;
          for (int kq = 0; kq < 4; kq++) {
            if (j == 0 && kq == XPOS) {
              for (int b = 8; b < 16; b++) {
                mbar_expect_tx(BAR(B_XFULL + b), 8192);
                tma_load_2d(sbase + 65536 + (b & 7) * 8192, &tm_x, BAR(B_XFULL + b), (b & 7) * 64, m * 128 + 64);
              }
            }
            const int k = (j & 1) * 4 + kq;
            TWAIT(twp, mbar_wait(BAR(B_EMPTY + k), k < 6 ? ((t & 1) ^ 1) : (t & 1)));
            mbar_expect_tx(BAR(B_FULL + k), 16384);
            tma_load_2d_mc(sbase + stage_off(k) + cr * 8192, tm, BAR(B_FULL + k), col, kq * 128);
          }
        }
        for (int j = 0; j < 18; j++) {
          const int st = j & 7, n = 5 + (j >> 3);
          const int i = 2 * j + cr;
          const int bi = p2_bi(i), kb = p2_kb(i);
          const int col = odd * 256 + ((p + 1 + bi) & 3) * 64;
          const CUtensorMap* tmk;
          int row;
          if (!odd) {
            if (kb < 4) { tmk = &tm_w2; row = (7 * p + kb) * 64; }
            else if (kb < 6) { tmk = &tm_wo; row = (2 * p + kb - 4) * 64; }
            else { tmk = &tm_w2; row = (7 * p + 4 + kb - 6) * 64; }
          } else {
            if (kb < 3) { tmk = &tm_w2; row = (7 * p + 4 + kb) * 64; }
            else if (kb < 7) { tmk = &tm_w2; row = (7 * p + kb - 3) * 64; }
            else { tmk = &tm_wo; row = (2 * p + kb - 7) * 64; }
          }
          mbar_wait(BAR(B_EMPTY + st), st < 6 ? ((n & 1) ^ 1) : (n & 1));
          mbar_expect_tx(BAR(B_FULL + st), 16384);
          tma_load_2d_mc(sbase + stage_off(st) + cr * 8192, tmk, BAR(B_FULL + st), col, row);
        }
      }
    } else if (odd) {
      if (lane == 0 && warp <= 10) {
        const int w = warp - 9;
        for (int e = 0; e < 2; e++) {
          mbar_wait(BAR(B_EV + w * 2 + e), 0);
          __threadfence();
          atomicAdd(&g_kvcnt[p][0], 1u);
        }
      }
    } else {
      const int hl = tid - 288;
      {
        const int ce = m * 4 + p;
        if (hl < 32) *(float4*)(&g_kv[par ^ 1][0][0][0] + ce * 128 + hl * 4) = make_float4(0.f, 0.f, 0.f, 0.f);
        else if (hl < 40) (&g_z[par ^ 1][0][0])[ce * 8 + hl - 32] = 0.f;
      }
      mbar_wait(BAR(B_XDONE), 0);
      wait_count_ge(&g_kvcnt[p][0], 64u * tag);
      const float* kvp = &g_kv[par][8 * p][0][0];
      const float* zp = &g_z[par][8 * p][0];
      const uint32_t dst0 = sbase + 5 * 8192, dst1 = dst0 + 65536;
#pragma unroll
      for (int h2 = 0; h2 < 2; h2++) {
        float4 v[3];
#pragma unroll
        for (int i = 0; i < 3; i++) {
          const int c = (h2 * 3 + i) * 96 + hl;
          v[i] = c < 512 ? ldg_cg_f4(kvp + c * 4) : (c < 544 ? ldg_cg_f4(zp + (c - 512) * 4) : make_float4(0.f, 0.f, 0.f, 0.f));
        }
#pragma unroll
        for (int i = 0; i < 3; i++) {
          const int c = (h2 * 3 + i) * 96 + hl;
          if (c < 544) {
            const uint32_t lo = pack_bf16(v[i].x, v[i].y), hi = pack_bf16(v[i].z, v[i].w);
            asm volatile("st.shared.v2.u32 [%0], {%1,%2};" ::"r"(dst0 + c * 8), "r"(lo), "r"(hi) : "memory");
            asm volatile("st.shared.v2.u32 [%0], {%1,%2};" ::"r"(dst1 + c * 8), "r"(lo), "r"(hi) : "memory");
          }
        }
      }
      __syncwarp();
      if (lane == 0) mbar_arrive(BAR(B_KVREADY));
    }
  } else {
    asm volatile("setmaxnreg.inc.sync.aligned.u32 240;");
    const int w = warp >> 2, wq = warp & 3, t128 = tid & 127;
    const int g = lane >> 2, tq = lane & 3;
    const uint32_t area = sbase + (uint32_t)w * 65536u;
    const bool elect = (t128 == 0);
    PROF(w, 22);
    const uint32_t dbase = (sbase & 0x3FFFFu) >> 4;
    uint32_t xoff = (uint32_t)((m * 4 + p) * 18 + w) * 8192u + (uint32_t)t128 * 16u;
    uint32_t stash = area + (uint32_t)t128 * 16u;
    const uint32_t epoch_c = ld_relaxed(&g_epoch);
    auto xptr = [&](int slot, int jj) INL { return (uint4*)((char*)g_xbuf + ((xoff & ~1u) + (uint32_t)slot * 16384u + (uint32_t)jj * 2048u)); };
    uint32_t A[144];
    float rs0, rs1;
    auto release = [&](int st) INL {
      if (elect) { mbar_arrive_cluster(BAR(B_EMPTY + st), 0); mbar_arrive_cluster(BAR(B_EMPTY + st), 1); }
    };

    {
      const int row = wq * 16 + (lane & 7) + ((lane >> 3) & 1) * 8;
      const uint32_t rbase = area + row * 128;
      float s0[2][4] = {}, q0[2][4] = {}, q1[2][4] = {};
      const uint32_t ones = 0x3F803F80u;
#pragma unroll
      for (int b = 0; b < 8; b++) {
        mbar_wait(BAR(B_XFULL + w * 8 + b), 0);
        if (b == 0) PROF(w, 23);
        if (b == 7) PROF(w, 24);
#pragma unroll
        for (int kk = 0; kk < 4; kk++) {
          const int i = (b * 4 + kk) * 4;
          ldmatrix_x4(rbase + b * 8192 + (((kk * 2 + (lane >> 4)) ^ (row & 7)) << 4), A[i], A[i + 1], A[i + 2], A[i + 3]);
        }
#pragma unroll
        for (int kk = 0; kk < 4; kk++) {
          const int i = (b * 4 + kk) * 4;
          mma_16816(s0[kk & 1], A[i], A[i + 1], A[i + 2], A[i + 3], ones, ones);
          mma_16816(q0[kk & 1], A[i], A[i + 1], A[i + 2], A[i + 3], A[i], A[i + 2]);
          mma_16816(q1[kk & 1], A[i], A[i + 1], A[i + 2], A[i + 3], A[i + 1], A[i + 3]);
        }
      }
      const float mean0 = (s0[0][0] + s0[1][0]) * (1.f / 512.f), mean1 = (s0[0][2] + s0[1][2]) * (1.f / 512.f);
      const uint32_t m0 = pack_bf16(mean0, mean0), m1 = pack_bf16(mean1, mean1);
#pragma unroll
      for (int i = 0; i < 128; i += 2) {
        A[i] = hsub2_bf16(A[i], m0);
        A[i + 1] = hsub2_bf16(A[i + 1], m1);
      }
      float v0 = (g & 1) ? q0[0][1] + q0[1][1] : q0[0][0] + q0[1][0];
      float v1 = (g & 1) ? q1[0][3] + q1[1][3] : q1[0][2] + q1[1][2];
      const int src = 4 * g + (g >> 1);
      v0 = __shfl_sync(0xffffffffu, v0, src);
      v1 = __shfl_sync(0xffffffffu, v1, src);
      v0 = fmaxf(v0 * (1.f / 512.f) - mean0 * mean0, 0.f);
      v1 = fmaxf(v1 * (1.f / 512.f) - mean1 * mean1, 0.f);
      rs0 = rsqrtf(v0 + 1e-5f);
      rs1 = rsqrtf(v1 + 1e-5f);
      bar_sync(1 + w, 128);
      cluster_wait();
      asm volatile("" : "+r"(xoff), "+r"(stash));
      PROF(w, 0);
      release(6); release(7);
      if (elect) mbar_arrive(BAR(B_XDONE));
    }

    auto gu_chunk = [&](float (&acc)[32], int f, int slot, int xslot, int hb) INL {
      const float c0 = rs0 * -1.4426950408889634f, c1 = rs1 * -1.4426950408889634f;
      const float q0 = rs0 * rs0, q1 = rs1 * rs1;
      uint32_t h[4];
#pragma unroll
      for (int i = 0; i < 4; i++) {
        const float ga = acc[f * 8 + 2 * i], gb = acc[f * 8 + 2 * i + 1];
        const float ua = acc[16 + f * 8 + 2 * i], ub = acc[16 + f * 8 + 2 * i + 1];
        const float c = (i & 1) ? c1 : c0, q = (i & 1) ? q1 : q0;
        const float da = 1.f + ex2f(fminf(ga * c, 60.f)), db = 1.f + ex2f(fminf(gb * c, 60.f));
        const float rq = rcpf(da * db) * q;
        h[i] = tagged(pack_bf16(ga * ua * (db * rq), gb * ub * (da * rq)), xoff & 1u);
      }
      const int jj = hb * 2 + f;
      sts_u4(stash + slot * 8192 + jj * 2048, h[0], h[1], h[2], h[3]);
      stg_u4(xptr(xslot, jj), h[0], h[1], h[2], h[3]);
    };
    auto kv_stage = [&](float (&acc)[32], int c, int hb) INL {
      const int srow = wq * 16 + (lane & 7) + ((lane >> 3) & 1) * 8;
      const uint32_t base = area + (3 + c) * 8192 + srow * 128;
#pragma unroll
      for (int jj = 0; jj < 2; jj++) {
        const int a = c * 16 + jj * 8;
        uint32_t r0, r1, r2, r3;
        if (c == 0) {
          r0 = pack_bf16(phi_f(acc[a] * rs0), phi_f(acc[a + 1] * rs0));
          r1 = pack_bf16(phi_f(acc[a + 2] * rs1), phi_f(acc[a + 3] * rs1));
          r2 = pack_bf16(phi_f(acc[a + 4] * rs0), phi_f(acc[a + 5] * rs0));
          r3 = pack_bf16(phi_f(acc[a + 6] * rs1), phi_f(acc[a + 7] * rs1));
        } else {
          r0 = pack_bf16(acc[a] * rs0, acc[a + 1] * rs0);
          r1 = pack_bf16(acc[a + 2] * rs1, acc[a + 3] * rs1);
          r2 = pack_bf16(acc[a + 4] * rs0, acc[a + 5] * rs0);
          r3 = pack_bf16(acc[a + 6] * rs1, acc[a + 7] * rs1);
        }
        stmatrix_x4(base + (((hb * 4 + jj * 2 + (lane >> 4)) ^ (srow & 7)) << 4), r0, r1, r2, r3);
      }
    };
    const uint32_t kvb = area + 5 * 8192;
    const uint32_t kvfrag = kvb + ((lane & 7) + ((lane >> 3) & 1) * 8) * 32 + (lane >> 4) * 16;
    auto signal = [&](int e) INL {
      __syncwarp();
      if (lane == 0) mbar_arrive(BAR(B_EV + w * 2 + e));
    };

    auto pp_wait = [&]() INL { bar_sync(3 + w, 256); };
    auto pp_pass = [&]() INL { bar_arrive(3 + (w ^ 1), 256); };
    if (w == 1) pp_pass();
    int tw1 = 0, tw2 = 0, tw3 = 0;
#pragma unroll 1
    for (int t = 0; t < 5; t++) {
      const uint32_t ph = t & 1;
      const int kind = odd ? (t < 2 ? K_KV : K_GU) : (t < 4 ? K_GU : K_Q);
      const int slot = odd ? t - 2 : t, xslot = odd ? t + 4 : t;
      static_for<2>([&](auto hc) INL {
        constexpr int hb = decltype(hc)::value;
        float acc[32];
        TWAIT(tw2, pp_wait());
        static_for<4>([&](auto kc) INL {
          constexpr int kq = decltype(kc)::value, k = hb * 4 + kq;
          TWAIT(tw1, mbar_wait(BAR(B_FULL + k), ph));
          wgmma_fence();
          static_for<8>([&](auto kkc) INL {
            constexpr int kk = decltype(kkc)::value, i = (kq * 8 + kk) * 4;
            wgmma_n64_rs<(kq | kk) != 0, desc_lo(stage_off(k) + kk * 1024, 8192), kHi64>(acc, A[i], A[i + 1], A[i + 2], A[i + 3]);
          });
          wgmma_commit();
          if (kq == 2) pp_pass();
          if (kq > 0) {
            wgmma_wait<1>();
            release(k - 1);
          }
        });
        TWAIT(tw3, wgmma_wait<0>());
        release(hb * 4 + 3);
        if (hb == 0 && t == 0) xoff |= (epoch_c & 1u) ^ 1u;
        if (kind == K_GU) {
          gu_chunk(acc, 0, slot, xslot, hb);
          gu_chunk(acc, 1, slot, xslot, hb);
        } else if (kind == K_KV) {
          if (hb == 0 && t == 0) sts_u4(stash + 5 * 8192, 0x3F803F80u, 0x3F803F80u, 0x3F803F80u, 0x3F803F80u);
          kv_stage(acc, 0, hb);
          kv_stage(acc, 1, hb);
          if (hb == 1) {
            float kvacc[36];
            const int par = (xoff & 1u) ^ 1u;
            fence_proxy_async();
            bar_sync(1 + w, 128);
            wgmma_fence();
            static_for<4>([&](auto kkc) INL {
              constexpr int kk = decltype(kkc)::value;
              wgmma_n72_ss_tt<kk != 0, desc_lo(3 * 8192 + kk * 2048, 0), desc_lo(4 * 8192 + kk * 2048, 8192 - kk * 2048)>(kvacc, dbase + w * 4096);
            });
            wgmma_commit();
            wgmma_wait<0>();
            float c[8];
#pragma unroll
            for (int i = 0; i < 8; i++)
              c[i] = wq == 0 ? kvacc[i] : (wq == 1 ? kvacc[8 + i] : (wq == 2 ? kvacc[16 + i] : kvacc[24 + i]));
            const int head = (2 * p + t) * 4 + wq;
            float* kvp = &g_kv[par][head][0][0];
            red_add_v2(kvp + g * 16 + 2 * tq, c[0], c[1]);
            red_add_v2(kvp + (g + 8) * 16 + 2 * tq, c[2], c[3]);
            red_add_v2(kvp + g * 16 + 8 + 2 * tq, c[4], c[5]);
            red_add_v2(kvp + (g + 8) * 16 + 8 + 2 * tq, c[6], c[7]);
            if (tq == 0) {
              red_add(&g_z[par][head][g], kvacc[32]);
              red_add(&g_z[par][head][g + 8], kvacc[34]);
            }
            signal(t);
          }
        } else {
          uint32_t aq[4][4];
#pragma unroll
          for (int c = 0; c < 4; c++) {
            const int a = c * 8;
            aq[c][0] = pack_bf16(phi_f(acc[a] * rs0), phi_f(acc[a + 1] * rs0));
            aq[c][1] = pack_bf16(phi_f(acc[a + 2] * rs1), phi_f(acc[a + 3] * rs1));
            aq[c][2] = pack_bf16(phi_f(acc[a + 4] * rs0), phi_f(acc[a + 5] * rs0));
            aq[c][3] = pack_bf16(phi_f(acc[a + 6] * rs1), phi_f(acc[a + 7] * rs1));
          }
          if (hb == 0) mbar_wait(BAR(B_KVREADY), 0);
          uint32_t Bf[4][6];
#pragma unroll
          for (int c = 0; c < 4; c++) {
            ldmatrix_x4_trans(kvfrag + (hb * 4 + c) * 512, Bf[c][0], Bf[c][1], Bf[c][2], Bf[c][3]);
            Bf[c][4] = lds_u32(kvb + 4096 + (hb * 4 + c) * 32 + tq * 4);
            Bf[c][5] = lds_u32(kvb + 4096 + (hb * 4 + c) * 32 + 16 + tq * 4);
          }
          float n0[4][4] = {}, n1[4][4] = {}, dn[4][4] = {};
#pragma unroll
          for (int c = 0; c < 4; c++) {
            mma_16816(dn[c], aq[c][0], aq[c][1], aq[c][2], aq[c][3], Bf[c][4], Bf[c][5]);
            mma_16816(n0[c], aq[c][0], aq[c][1], aq[c][2], aq[c][3], Bf[c][0], Bf[c][1]);
            mma_16816(n1[c], aq[c][0], aq[c][1], aq[c][2], aq[c][3], Bf[c][2], Bf[c][3]);
          }
          if (hb == 1) bar_sync(1 + w, 128);
          const uint32_t tg = xoff & 1u;
#pragma unroll
          for (int c = 0; c < 4; c++) {
            const float i0 = __fdividef(1.f, dn[c][0] + 1e-6f), i1 = __fdividef(1.f, dn[c][2] + 1e-6f);
            aq[c][0] = tagged(pack_bf16(n0[c][0] * i0, n0[c][1] * i0), tg);
            aq[c][1] = tagged(pack_bf16(n0[c][2] * i1, n0[c][3] * i1), tg);
            aq[c][2] = tagged(pack_bf16(n1[c][0] * i0, n1[c][1] * i0), tg);
            aq[c][3] = tagged(pack_bf16(n1[c][2] * i1, n1[c][3] * i1), tg);
          }
#pragma unroll
          for (int c = 0; c < 4; c++) {
            stg_u4(xptr(4 + hb, c), aq[c][0], aq[c][1], aq[c][2], aq[c][3]);
            sts_u4(stash + (4 + hb) * 8192 + c * 2048, aq[c][0], aq[c][1], aq[c][2], aq[c][3]);
          }
        }
      });
      PROF(w, 1 + 2 * t);
    }
    PROF(w, 10);

    const int n_own = odd ? 3 : 6;
    auto load_a = [&](int kb) INL {
      if (kb < n_own) {
#pragma unroll
        for (int jj = 0; jj < 4; jj++) {
          const int i = (kb * 4 + jj) * 4;
          lds_u4(stash + kb * 8192 + jj * 2048, A[i], A[i + 1], A[i + 2], A[i + 3]);
        }
      } else {
        const int xs = odd ? kb - 3 : kb;
#pragma unroll
        for (int jj = 0; jj < 4; jj++) {
          const int i = (kb * 4 + jj) * 4;
          ldg_poll_u4(xptr(xs, jj), A[i], A[i + 1], A[i + 2], A[i + 3]);
        }
      }
    };
    auto fix_a = [&](int kb) INL {
      if (kb >= n_own) {
        const int xs = odd ? kb - 3 : kb;
        recv_group<4>(xptr(xs, 0), &A[kb * 16], xoff & 1u);
      }
    };
#pragma unroll
    for (int kb = 0; kb < 7; kb++) load_a(kb);
    PROF(w, 11);

    const uint32_t ooff = (uint32_t)(m * 128 + w * 64 + wq * 16 + (lane >> 3)) * kD + odd * 256 + p * 64 + (lane & 7) * 8;
    float acc2[2][32];
    uint32_t poff = (uint32_t)((m * 2 + odd) * 24 + w) * 8192u + (uint32_t)t128 * 16u;
    asm volatile("" : "+r"(poff));
    auto pptr = [&](int dest, int sl) INL { return (uint4*)((char*)g_pbuf + (poff + (uint32_t)(dest * 3 + sl) * 16384u)); };
    uint32_t P[3][16];
    uint4 xr[4];
    auto send = [&](float (&acc)[32], int bi) INL {
      uint4* dst = pptr((p + 1 + bi) & 3, bi);
#pragma unroll
      for (int q = 0; q < 4; q++)
        stg_u4(dst + q * 128, tagged(pack_bf16(acc[q * 8], acc[q * 8 + 1]), xoff & 1u), tagged(pack_bf16(acc[q * 8 + 2], acc[q * 8 + 3]), xoff & 1u),
               tagged(pack_bf16(acc[q * 8 + 4], acc[q * 8 + 5]), xoff & 1u), tagged(pack_bf16(acc[q * 8 + 6], acc[q * 8 + 7]), xoff & 1u));
      PROF(w, 12 + 2 * bi);
    };
    auto fetch = [&](int sl) INL {
#pragma unroll
      for (int q = 0; q < 4; q++) ldg_poll_u4(pptr(p, sl) + q * 128, P[sl][q * 4], P[sl][q * 4 + 1], P[sl][q * 4 + 2], P[sl][q * 4 + 3]);
    };
    static_for<36>([&](auto ic) INL {
      constexpr int i = decltype(ic)::value, bi = p2_bi(i), kb = p2_kb(i), j = i >> 1, st = j & 7;
      if (i == 9) { load_a(7); load_a(8); }
      if (i == 14) PROF(w, 2);
      if (bi == 0 && kb >= 3) fix_a(kb);
      if (i == 15) PROF(w, 4);
      if (i == 7) PROF(w, 6);
      if (i == 0 || i == 7 || i == 14 || i == 18 || i == 27) pp_wait();
      if ((i & 1) == 0) mbar_wait(BAR(B_FULL + st), (5 + (j >> 3)) & 1);
      wgmma_fence();
      static_for<4>([&](auto kkc) INL {
        constexpr int kk = decltype(kkc)::value, a = (kb * 4 + kk) * 4;
        wgmma_n64_rs<(kb | kk) != 0, desc_lo(stage_off(st) + (i & 1) * 8192 + kk * 2048, 0), kHi128>(acc2[bi & 1], A[a], A[a + 1], A[a + 2], A[a + 3]);
      });
      wgmma_commit();
      if (i == 4 || i == 11 || i == 15 || i == 24 || (i == 33 && w == 0)) pp_pass();
      if (i > 0) {
        wgmma_wait<1>();
        if ((i & 1) == 0 && j - 1 <= 9) release((j - 1) & 7);
      }
      if constexpr (i == 17) { send(acc2[0], 0); wgmma_wait<0>(); send(acc2[1], 1); }
      if constexpr (i == 26) { wgmma_wait<0>(); send(acc2[0], 2); }
      if constexpr (i == 29) fetch(0);
      if constexpr (i == 30) fetch(1);
      if constexpr (i == 28) {
#pragma unroll
        for (int q = 0; q < 4; q++) xr[q] = __ldg((const uint4*)(x + ooff + q * 4 * kD));
      }
      if constexpr (i == 32) fetch(2);
    });
#pragma unroll
    for (int sl = 0; sl < 3; sl++) { PROF(w, 13 + 2 * sl); recv_group<4>(pptr(p, sl), &P[sl][0], xoff & 1u); }
    wgmma_wait<0>();
    PROF(w, 18);
    {
      const uint32_t tile = area + wq * 4352;
#pragma unroll
      for (int q = 0; q < 8; q++) {
        float rr[4];
#pragma unroll
        for (int e = 0; e < 4; e++) rr[e] = acc2[1][q * 4 + e];
#pragma unroll
        for (int sl = 0; sl < 3; sl++) {
          rr[0] += __uint_as_float(P[sl][2 * q] << 16);
          rr[1] += __uint_as_float(P[sl][2 * q] & 0xffff0000u);
          rr[2] += __uint_as_float(P[sl][2 * q + 1] << 16);
          rr[3] += __uint_as_float(P[sl][2 * q + 1] & 0xffff0000u);
        }
        const uint32_t ad = tile + g * 272 + q * 32 + tq * 8;
        asm volatile("st.shared.v2.f32 [%0], {%1,%2};" ::"r"(ad), "f"(rr[0]), "f"(rr[1]) : "memory");
        asm volatile("st.shared.v2.f32 [%0], {%1,%2};" ::"r"(ad + 8 * 272), "f"(rr[2]), "f"(rr[3]) : "memory");
      }
      __syncwarp();
#pragma unroll
      for (int q = 0; q < 4; q++) {
        const uint32_t ad = tile + ((lane >> 3) + 4 * q) * 272 + (lane & 7) * 32;
        uint32_t v[8];
        lds_u4(ad, v[0], v[1], v[2], v[3]);
        lds_u4(ad + 16, v[4], v[5], v[6], v[7]);
        const uint32_t xv[4] = {xr[q].x, xr[q].y, xr[q].z, xr[q].w};
        uint32_t o[4];
#pragma unroll
        for (int e = 0; e < 4; e++)
          o[e] = pack_bf16(__uint_as_float(v[2 * e]) + __uint_as_float(xv[e] << 16), __uint_as_float(v[2 * e + 1]) + __uint_as_float(xv[e] & 0xffff0000u));
        stg_u4(out + ooff + q * 4 * kD, o[0], o[1], o[2], o[3]);
      }
    }
    PROF(w, 19);
    if (tid == 0) {
      const uint32_t old = atomicAdd(&g_done, 1u);
      if ((old & 127u) == 127u) st_relaxed(&g_epoch, ld_relaxed(&g_epoch) + 1u);
    }
  }
#undef BAR
}

typedef CUresult (*EncodeFn)(CUtensorMap*, CUtensorMapDataType, cuuint32_t, void*, const cuuint64_t*, const cuuint64_t*,
                             const cuuint32_t*, const cuuint32_t*, CUtensorMapInterleave, CUtensorMapSwizzle,
                             CUtensorMapL2promotion, CUtensorMapFloatOOBfill);

void make_map(EncodeFn enc, CUtensorMap* tm, const void* ptr, int rows, int cols, bool narrow) {
  cuuint64_t gd[2] = {(cuuint64_t)cols, (cuuint64_t)rows};
  cuuint64_t gs[1] = {(cuuint64_t)cols * 2};
  cuuint32_t bd[2] = {narrow ? 32u : 64u, narrow ? 128u : 64u};
  cuuint32_t es[2] = {1, 1};
  enc(tm, CU_TENSOR_MAP_DATA_TYPE_BFLOAT16, 2, const_cast<void*>(ptr), gd, gs, bd, es, CU_TENSOR_MAP_INTERLEAVE_NONE,
      narrow ? CU_TENSOR_MAP_SWIZZLE_64B : CU_TENSOR_MAP_SWIZZLE_128B, CU_TENSOR_MAP_L2_PROMOTION_L2_256B, CU_TENSOR_MAP_FLOAT_OOB_FILL_NONE);
}

}

extern "C" void kernel_launch(void* const* d_in, const int* in_sizes, int n_in, void* d_out, int out_size) {
  static EncodeFn enc = nullptr;
  if (!enc) {
    void* fn = nullptr;
    cudaDriverEntryPointQueryResult qr;
    cudaGetDriverEntryPoint("cuTensorMapEncodeTiled", &fn, cudaEnableDefault, &qr);
    enc = (EncodeFn)fn;
    cudaFuncSetAttribute(fused_kernel, cudaFuncAttributeMaxDynamicSharedMemorySize, kSmemBytes);
  }
  CUtensorMap tm_x, tm_wqkv, tm_w1, tm_w3, tm_w2, tm_wo;
  make_map(enc, &tm_x, d_in[0], kS, kD, false);
  make_map(enc, &tm_wqkv, d_in[1], kD, 3 * kD, true);
  make_map(enc, &tm_wo, d_in[2], kD, kD, false);
  make_map(enc, &tm_w1, d_in[4], kD, kF, true);
  make_map(enc, &tm_w3, d_in[5], kD, kF, true);
  make_map(enc, &tm_w2, d_in[6], kF, kD, false);
  fused_kernel<<<128, 384, kSmemBytes>>>(tm_x, tm_wqkv, tm_w1, tm_w3, tm_w2, tm_wo, (const __nv_bfloat16*)d_in[0],
                                         (__nv_bfloat16*)d_out, (const __nv_bfloat16*)d_in[1], (const __nv_bfloat16*)d_in[4],
                                         (const __nv_bfloat16*)d_in[5]);
}
```

```cpp
#include <cuda_runtime.h>
#include <cuda_bf16.h>
#include <cuda.h>
#include <stdint.h>

extern __shared__ __align__(1024) uint8_t smem_raw[];

namespace {

constexpr int kS = 2048, kD = 512, kF = 1792;
#define XPOS 1
constexpr uint32_t kSpinLimit = 1u << 22;

__device__ uint4    g_xbuf[16][4][9][2][4][128];
__device__ uint4    g_pbuf[16][2][4][3][2][4][128];
__device__ float    g_kv[2][32][16][16];
__device__ float    g_z[2][32][16];
__device__ uint32_t g_kvcnt[4][32];
__device__ uint32_t g_epoch;
__device__ uint32_t g_done;
#define PROF(wg, i) do {} while (0)
#define TWAIT(acc, stmt) do { stmt; } while (0)

__device__ __forceinline__ uint32_t smem_u32(const void* p) { return (uint32_t)__cvta_generic_to_shared(p); }
__device__ __forceinline__ void mbar_init(uint32_t bar, uint32_t cnt) {
  asm volatile("mbarrier.init.shared::cta.b64 [%0], %1;" ::"r"(bar), "r"(cnt) : "memory");
}
__device__ __forceinline__ void mbar_expect_tx(uint32_t bar, uint32_t bytes) {
  asm volatile("mbarrier.arrive.expect_tx.shared::cta.b64 _, [%0], %1;" ::"r"(bar), "r"(bytes) : "memory");
}
__device__ __forceinline__ void mbar_arrive(uint32_t bar) {
  asm volatile("mbarrier.arrive.shared::cta.b64 _, [%0];" ::"r"(bar) : "memory");
}
__device__ __forceinline__ void mbar_wait(uint32_t bar, uint32_t parity) {
  asm volatile(
      "{\n.reg .pred p;\n"
      "LAB_WAIT:\n"
      "mbarrier.try_wait.parity.shared::cta.b64 p, [%0], %1;\n"
      "@p bra DONE;\n"
      "bra LAB_WAIT;\n"
      "DONE:\n}" ::"r"(bar), "r"(parity) : "memory");
}
__device__ __forceinline__ void tma_load_2d(uint32_t dst, const CUtensorMap* tm, uint32_t bar, int c0, int c1) {
  asm volatile(
      "cp.async.bulk.tensor.2d.shared::cluster.global.mbarrier::complete_tx::bytes [%0], [%1, {%3, %4}], [%2];" ::"r"(dst),
      "l"(tm), "r"(bar), "r"(c0), "r"(c1)
      : "memory");
}
__device__ __forceinline__ void tma_load_2d_mc(uint32_t dst, const CUtensorMap* tm, uint32_t bar, int c0, int c1) {
  asm volatile(
      "cp.async.bulk.tensor.2d.shared::cluster.global.mbarrier::complete_tx::bytes.multicast::cluster [%0], [%1, {%3, %4}], [%2], %5;" ::"r"(dst),
      "l"(tm), "r"(bar), "r"(c0), "r"(c1), "h"((uint16_t)3)
      : "memory");
}
__device__ __forceinline__ void mbar_arrive_cluster(uint32_t bar, uint32_t cta) {
  asm volatile("{\n.reg .b32 ra;\nmapa.shared::cluster.u32 ra, %0, %1;\nmbarrier.arrive.shared::cluster.b64 _, [ra];\n}" ::"r"(bar), "r"(cta) : "memory");
}
__device__ __forceinline__ void prefetch_tmap(const CUtensorMap* tm) {
  asm volatile("prefetch.tensormap [%0];" ::"l"(tm) : "memory");
}
__device__ __forceinline__ void wgmma_fence() { asm volatile("wgmma.fence.sync.aligned;" ::: "memory"); }
__device__ __forceinline__ void wgmma_commit() { asm volatile("wgmma.commit_group.sync.aligned;" ::: "memory"); }
template <int N>
__device__ __forceinline__ void wgmma_wait() { asm volatile("wgmma.wait_group.sync.aligned %0;" ::"n"(N) : "memory"); }
__device__ __forceinline__ void bar_sync(int id, int n) { asm volatile("bar.sync %0, %1;" ::"r"(id), "r"(n) : "memory"); }
__device__ __forceinline__ void bar_arrive(int id, int n) { asm volatile("bar.arrive %0, %1;" ::"r"(id), "r"(n) : "memory"); }
__device__ __forceinline__ void fence_proxy_async() { asm volatile("fence.proxy.async.shared::cta;" ::: "memory"); }

__device__ __forceinline__ uint32_t ld_acquire(const uint32_t* p) {
  uint32_t v;
  asm volatile("ld.acquire.gpu.global.u32 %0, [%1];" : "=r"(v) : "l"(p) : "memory");
  return v;
}
__device__ __forceinline__ uint32_t ld_relaxed(const uint32_t* p) {
  uint32_t v;
  asm volatile("ld.relaxed.gpu.global.u32 %0, [%1];" : "=r"(v) : "l"(p));
  return v;
}
__device__ __forceinline__ void cluster_wait() { asm volatile("barrier.cluster.wait.aligned;" ::: "memory"); }
__device__ __forceinline__ void st_relaxed(uint32_t* p, uint32_t v) {
  asm volatile("st.relaxed.gpu.global.u32 [%0], %1;" ::"l"(p), "r"(v) : "memory");
}
__device__ __forceinline__ void wait_flag_eq(const uint32_t* p, uint32_t val) {
  uint32_t it = 0;
  while (ld_acquire(p) != val) {
    if (++it > kSpinLimit) break;
  }
}
__device__ __forceinline__ void wait_count_ge(const uint32_t* p, uint32_t val) {
  uint32_t it = 0;
  while ((int32_t)(ld_acquire(p) - val) < 0) {
    __nanosleep(64);
    if (++it > kSpinLimit) break;
  }
}
__device__ __forceinline__ void ldg_poll_u4(const void* p, uint32_t& a, uint32_t& b, uint32_t& c, uint32_t& d) {
  asm volatile("ld.relaxed.gpu.global.v4.u32 {%0,%1,%2,%3}, [%4];" : "=r"(a), "=r"(b), "=r"(c), "=r"(d) : "l"(p) : "memory");
}
template <int N>
__device__ __forceinline__ void recv_group(const uint4* p, uint32_t* r, uint32_t tag) {
  uint32_t it = 0;
  while (true) {
    uint32_t bad = 0u;
#pragma unroll
    for (int i = 0; i < 4 * N; i++) bad |= r[i] ^ tag;
    if (!__any_sync(0xffffffffu, (bad & 1u) != 0u) || ++it > kSpinLimit) break;
#pragma unroll
    for (int q = 0; q < N; q++) ldg_poll_u4(p + q * 128, r[q * 4], r[q * 4 + 1], r[q * 4 + 2], r[q * 4 + 3]);
  }
}
__device__ __forceinline__ uint32_t tagged(uint32_t v, uint32_t tag) { return (v & ~1u) | tag; }
__device__ __forceinline__ float4 ldg_cg_f4(const void* p) {
  float4 v;
  asm volatile("ld.global.cg.v4.f32 {%0,%1,%2,%3}, [%4];" : "=f"(v.x), "=f"(v.y), "=f"(v.z), "=f"(v.w) : "l"(p) : "memory");
  return v;
}
__device__ __forceinline__ void stg_u4(void* p, uint32_t a, uint32_t b, uint32_t c, uint32_t d) {
  asm volatile("st.global.v4.u32 [%0], {%1,%2,%3,%4};" ::"l"(p), "r"(a), "r"(b), "r"(c), "r"(d) : "memory");
}
__device__ __forceinline__ void stg_f4(void* p, float a, float b, float c, float d) {
  asm volatile("st.global.v4.f32 [%0], {%1,%2,%3,%4};" ::"l"(p), "f"(a), "f"(b), "f"(c), "f"(d) : "memory");
}
__device__ __forceinline__ void sts_u4(uint32_t addr, uint32_t a, uint32_t b, uint32_t c, uint32_t d) {
  asm volatile("st.shared.v4.u32 [%0], {%1,%2,%3,%4};" ::"r"(addr), "r"(a), "r"(b), "r"(c), "r"(d) : "memory");
}
__device__ __forceinline__ void lds_u4(uint32_t addr, uint32_t& a, uint32_t& b, uint32_t& c, uint32_t& d) {
  asm volatile("ld.shared.v4.u32 {%0,%1,%2,%3}, [%4];" : "=r"(a), "=r"(b), "=r"(c), "=r"(d) : "r"(addr) : "memory");
}
__device__ __forceinline__ uint32_t lds_u32(uint32_t addr) {
  uint32_t v;
  asm volatile("ld.shared.u32 %0, [%1];" : "=r"(v) : "r"(addr) : "memory");
  return v;
}
__device__ __forceinline__ void ldmatrix_x4(uint32_t addr, uint32_t& a, uint32_t& b, uint32_t& c, uint32_t& d) {
  asm volatile("ldmatrix.sync.aligned.m8n8.x4.shared.b16 {%0,%1,%2,%3}, [%4];" : "=r"(a), "=r"(b), "=r"(c), "=r"(d) : "r"(addr) : "memory");
}
__device__ __forceinline__ void ldmatrix_x4_trans(uint32_t addr, uint32_t& a, uint32_t& b, uint32_t& c, uint32_t& d) {
  asm volatile("ldmatrix.sync.aligned.m8n8.x4.trans.shared.b16 {%0,%1,%2,%3}, [%4];" : "=r"(a), "=r"(b), "=r"(c), "=r"(d) : "r"(addr) : "memory");
}
__device__ __forceinline__ void stmatrix_x4(uint32_t addr, uint32_t a, uint32_t b, uint32_t c, uint32_t d) {
  asm volatile("stmatrix.sync.aligned.m8n8.x4.shared.b16 [%0], {%1,%2,%3,%4};" ::"r"(addr), "r"(a), "r"(b), "r"(c), "r"(d) : "memory");
}
__device__ __forceinline__ void mma_16816(float (&c)[4], uint32_t a0, uint32_t a1, uint32_t a2, uint32_t a3, uint32_t b0, uint32_t b1) {
  asm(
      "mma.sync.aligned.m16n8k16.row.col.f32.bf16.bf16.f32 {%0,%1,%2,%3}, {%4,%5,%6,%7}, {%8,%9}, {%0,%1,%2,%3};"
      : "+f"(c[0]), "+f"(c[1]), "+f"(c[2]), "+f"(c[3])
      : "r"(a0), "r"(a1), "r"(a2), "r"(a3), "r"(b0), "r"(b1));
}
__device__ __forceinline__ uint32_t pack_bf16(float lo, float hi) {
  uint32_t r;
  asm("cvt.rn.bf16x2.f32 %0, %1, %2;" : "=r"(r) : "f"(hi), "f"(lo));
  return r;
}
__device__ __forceinline__ uint32_t hsub2_bf16(uint32_t a, uint32_t b) {
  uint32_t r;
  asm("sub.rn.bf16x2 %0, %1, %2;" : "=r"(r) : "r"(a), "r"(b));
  return r;
}
__device__ __forceinline__ float ex2f(float x) {
  float r;
  asm("ex2.approx.ftz.f32 %0, %1;" : "=f"(r) : "f"(x));
  return r;
}
__device__ __forceinline__ float rcpf(float x) {
  float r;
  asm("rcp.approx.ftz.f32 %0, %1;" : "=f"(r) : "f"(x));
  return r;
}
__device__ __forceinline__ void red_add_v2(float* p, float a, float b) {
  asm volatile("red.relaxed.gpu.global.add.v2.f32 [%0], {%1,%2};" ::"l"(p), "f"(a), "f"(b) : "memory");
}
__device__ __forceinline__ void red_add(float* p, float a) {
  asm volatile("red.relaxed.gpu.global.add.f32 [%0], %1;" ::"l"(p), "f"(a) : "memory");
}
__device__ __forceinline__ float phi_f(float t) {
  float e = ex2f(t * 1.4426950408889634f);
  return (t > 0.f ? t + 1.f : e) + 1e-6f;
}

#define R8(a, o) "+f"(a[o + 0]), "+f"(a[o + 1]), "+f"(a[o + 2]), "+f"(a[o + 3]), "+f"(a[o + 4]), "+f"(a[o + 5]), "+f"(a[o + 6]), "+f"(a[o + 7])

#define W8(a, o) "=f"(a[o + 0]), "=f"(a[o + 1]), "=f"(a[o + 2]), "=f"(a[o + 3]), "=f"(a[o + 4]), "=f"(a[o + 5]), "=f"(a[o + 6]), "=f"(a[o + 7])
#define D32 "{%0,%1,%2,%3,%4,%5,%6,%7,%8,%9,%10,%11,%12,%13,%14,%15,%16,%17,%18,%19,%20,%21,%22,%23,%24,%25,%26,%27,%28,%29,%30,%31}"
#define D36 "{%0,%1,%2,%3,%4,%5,%6,%7,%8,%9,%10,%11,%12,%13,%14,%15,%16,%17,%18,%19,%20,%21,%22,%23,%24,%25,%26,%27,%28,%29,%30,%31,%32,%33,%34,%35}"

constexpr uint32_t kHi128 = (1024u >> 4) | (1u << 30);
constexpr uint32_t kHi64 = (512u >> 4) | (2u << 30);
__host__ __device__ constexpr uint32_t desc_lo(uint32_t off, uint32_t lbo) { return (off >> 4) | ((lbo >> 4) << 16); }

template <bool ACC, uint32_t LO, uint32_t HI>
__device__ __forceinline__ void wgmma_n64_rs(float (&d)[32], uint32_t a0, uint32_t a1, uint32_t a2, uint32_t a3) {
  if (ACC) {
    asm volatile(
        "{\n.reg .pred p;\n.reg .b32 lo;\n.reg .b64 dd;\nsetp.eq.b32 p, 0, 0;\nmov.u32 lo, 64;\nadd.u32 lo, lo, %36;\nmov.b64 dd, {lo, %37};\n"
        "wgmma.mma_async.sync.aligned.m64n64k16.f32.bf16.bf16 " D32 ", {%32,%33,%34,%35}, dd, p, 1, 1, 1;\n}"
        : R8(d, 0), R8(d, 8), R8(d, 16), R8(d, 24)
        : "r"(a0), "r"(a1), "r"(a2), "r"(a3), "n"(LO), "n"(HI));
  } else {
    asm volatile(
        "{\n.reg .pred p;\n.reg .b32 lo;\n.reg .b64 dd;\nsetp.ne.b32 p, 0, 0;\nmov.u32 lo, 64;\nadd.u32 lo, lo, %36;\nmov.b64 dd, {lo, %37};\n"
        "wgmma.mma_async.sync.aligned.m64n64k16.f32.bf16.bf16 " D32 ", {%32,%33,%34,%35}, dd, p, 1, 1, 1;\n}"
        : W8(d, 0), W8(d, 8), W8(d, 16), W8(d, 24)
        : "r"(a0), "r"(a1), "r"(a2), "r"(a3), "n"(LO), "n"(HI));
  }
}
template <bool ACC, uint32_t LOA, uint32_t LOB>
__device__ __forceinline__ void wgmma_n72_ss_tt(float (&d)[36], uint32_t base) {
  if (ACC) {
    asm volatile(
        "{\n.reg .pred p;\n.reg .b32 lo;\n.reg .b64 da, db;\nsetp.eq.b32 p, 0, 0;\n"
        "add.u32 lo, %36, %37;\nmov.b64 da, {lo, %39};\nadd.u32 lo, %36, %38;\nmov.b64 db, {lo, %39};\n"
        "wgmma.mma_async.sync.aligned.m64n72k16.f32.bf16.bf16 " D36 ", da, db, p, 1, 1, 1, 1;\n}"
        : R8(d, 0), R8(d, 8), R8(d, 16), R8(d, 24), "+f"(d[32]), "+f"(d[33]), "+f"(d[34]), "+f"(d[35])
        : "r"(base), "n"(LOA), "n"(LOB), "n"(kHi128));
  } else {
    asm volatile(
        "{\n.reg .pred p;\n.reg .b32 lo;\n.reg .b64 da, db;\nsetp.ne.b32 p, 0, 0;\n"
        "add.u32 lo, %36, %37;\nmov.b64 da, {lo, %39};\nadd.u32 lo, %36, %38;\nmov.b64 db, {lo, %39};\n"
        "wgmma.mma_async.sync.aligned.m64n72k16.f32.bf16.bf16 " D36 ", da, db, p, 1, 1, 1, 1;\n}"
        : W8(d, 0), W8(d, 8), W8(d, 16), W8(d, 24), "=f"(d[32]), "=f"(d[33]), "=f"(d[34]), "=f"(d[35])
        : "r"(base), "n"(LOA), "n"(LOB), "n"(kHi128));
  }
}

#define INL __attribute__((always_inline))
template <int V> struct IC { static constexpr int value = V; };
template <int N, int I = 0, typename F>
__device__ __forceinline__ void static_for(F&& f) {
  if constexpr (I < N) { f(IC<I>{}); static_for<N, I + 1>(f); }
}

__host__ __device__ constexpr uint32_t stage_off(int st) {
  return st < 6 ? 131072u + (uint32_t)st * 16384u : (uint32_t)(st - 6) * 65536u + 49152u;
}

constexpr int B_FULL = 0, B_EMPTY = 8, B_XFULL = 16, B_XDONE = 32, B_KVREADY = 33, B_EV = 34, B_COUNT = 38;
constexpr uint32_t kBarOff = 229376;
constexpr int kSmemBytes = 229376 + 1024;

__host__ __device__ constexpr int p2_bi(int i) { return i < 7 ? 0 : i < 14 ? 1 : i < 16 ? 0 : i < 18 ? 1 : i / 9; }
__host__ __device__ constexpr int p2_kb(int i) { return i < 7 ? i : i < 14 ? i - 7 : i < 16 ? i - 7 : i < 18 ? i - 9 : i % 9; }

enum { K_NONE = 0, K_GU = 1, K_KV = 2, K_Q = 3 };

__global__ void __cluster_dims__(2, 1, 1) __launch_bounds__(384, 1)
fused_kernel(const __grid_constant__ CUtensorMap tm_x, const __grid_constant__ CUtensorMap tm_wqkv,
             const __grid_constant__ CUtensorMap tm_w1, const __grid_constant__ CUtensorMap tm_w3,
             const __grid_constant__ CUtensorMap tm_w2, const __grid_constant__ CUtensorMap tm_wo,
             const __nv_bfloat16* __restrict__ x, __nv_bfloat16* __restrict__ out,
             const __nv_bfloat16* __restrict__ wqkv, const __nv_bfloat16* __restrict__ w1, const __nv_bfloat16* __restrict__ w3) {
  const uint32_t sbase = smem_u32(smem_raw);
  const uint32_t bars = sbase + kBarOff;
  const int tid = threadIdx.x, lane = tid & 31;
  const int warp = __shfl_sync(0xffffffffu, tid >> 5, 0);
  const int cr = blockIdx.x & 1;
  const int r = (blockIdx.x >> 1) & 7, m = ((blockIdx.x >> 4) << 1) | cr, p = r >> 1, odd = r & 1;
#define BAR(i) (bars + 8u * (uint32_t)(i))
  if (tid < 128) {
    asm volatile("prefetch.global.L2 [%0];" ::"l"((const char*)(x + (size_t)(m * 128) * kD) + (r * 128 + tid) * 128));
  } else if (tid < 192) {
    const __nv_bfloat16* wp = odd ? wqkv + 512 + cr * 512 + 128 * p : (cr ? w3 : w1) + 7 * p * 64;
    const int ld = odd ? 3 * kD : kF;
    asm volatile("prefetch.global.L2 [%0];" ::"l"(wp + (size_t)((m >> 1) * 64 + tid - 128) * ld));
  }
  if (tid == 256) {
    if ((sbase & 0x3FFFFu) != 1024u) __trap();
#pragma unroll
    for (int i = 0; i < 16; i++) mbar_init(BAR(B_XFULL + i), 1);
    fence_proxy_async();
#pragma unroll
    for (int b = 0; b < 8; b++) {
      mbar_expect_tx(BAR(B_XFULL + b), 8192);
      tma_load_2d(sbase + (b >> 3) * 65536 + (b & 7) * 8192, &tm_x, BAR(B_XFULL + b), (b & 7) * 64, m * 128 + (b >> 3) * 64);
    }
#pragma unroll
    for (int i = 0; i < 8; i++) { mbar_init(BAR(B_FULL + i), 1); mbar_init(BAR(B_EMPTY + i), 4); }
#pragma unroll
    for (int i = 0; i < 4; i++) mbar_init(BAR(B_EV + i), 4);
    mbar_init(BAR(B_XDONE), 2);
    mbar_init(BAR(B_KVREADY), 3);
    asm volatile("fence.mbarrier_init.release.cluster;" ::: "memory");
    fence_proxy_async();
  } else if (tid == 288) {
    prefetch_tmap(odd ? &tm_wqkv : (cr ? &tm_w3 : &tm_w1));
  }
  __syncwarp();
  asm volatile("barrier.cluster.arrive.relaxed.aligned;" ::: "memory");
  PROF((tid >> 7), 21);
  __syncthreads();

  if (warp >= 8) {
    asm volatile("setmaxnreg.dec.sync.aligned.u32 24;");
    PROF(2, 3);
    cluster_wait();
    PROF(2, 2);
    const uint32_t epoch = warp == 8 ? 0u : ld_relaxed(&g_epoch);
    const uint32_t tag = epoch + 1u;
    const int par = epoch & 1;
    if (warp == 8) {
      if (lane == 0) {
        int twp = 0;
        for (int j = 0; j < 10; j++) {
          const CUtensorMap* tm;
          int col;
          if (!odd) {
            if (j < 8) { tm = cr ? &tm_w3 : &tm_w1; col = 7 * p * 64 + j * 32; }
            else { tm = &tm_wqkv; col = 128 * p + (j - 8) * 64 + cr * 32; }
          } else {
            if (j < 4) { tm = &tm_wqkv; col = 512 + cr * 512 + 128 * p + j * 32; }
            else { tm = cr ? &tm_w3 : &tm_w1; col = (7 * p + 4) * 64 + (j - 4) * 32; }
          }
          const int t = j >> 1;
          for (int kq = 0; kq < 4; kq++) {
            if (j == 0 && kq == XPOS) {
              for (int b = 8; b < 16; b++) {
                mbar_expect_tx(BAR(B_XFULL + b), 8192);
                tma_load_2d(sbase + 65536 + (b & 7) * 8192, &tm_x, BAR(B_XFULL + b), (b & 7) * 64, m * 128 + 64);
              }
            }
            const int k = (j & 1) * 4 + kq;
            TWAIT(twp, mbar_wait(BAR(B_EMPTY + k), k < 6 ? ((t & 1) ^ 1) : (t & 1)));
            mbar_expect_tx(BAR(B_FULL + k), 16384);
            tma_load_2d_mc(sbase + stage_off(k) + cr * 8192, tm, BAR(B_FULL + k), col, kq * 128);
          }
        }
        for (int j = 0; j < 18; j++) {
          const int st = j & 7, n = 5 + (j >> 3);
          const int i = 2 * j + cr;
          const int bi = p2_bi(i), kb = p2_kb(i);
          const int col = odd * 256 + ((p + 1 + bi) & 3) * 64;
          const CUtensorMap* tmk;
          int row;
          if (!odd) {
            if (kb < 4) { tmk = &tm_w2; row = (7 * p + kb) * 64; }
            else if (kb < 6) { tmk = &tm_wo; row = (2 * p + kb - 4) * 64; }
            else { tmk = &tm_w2; row = (7 * p + 4 + kb - 6) * 64; }
          } else {
            if (kb < 3) { tmk = &tm_w2; row = (7 * p + 4 + kb) * 64; }
            else if (kb < 7) { tmk = &tm_w2; row = (7 * p + kb - 3) * 64; }
            else { tmk = &tm_wo; row = (2 * p + kb - 7) * 64; }
          }
          mbar_wait(BAR(B_EMPTY + st), st < 6 ? ((n & 1) ^ 1) : (n & 1));
          mbar_expect_tx(BAR(B_FULL + st), 16384);
          tma_load_2d_mc(sbase + stage_off(st) + cr * 8192, tmk, BAR(B_FULL + st), col, row);
        }
      }
    } else if (odd) {
      if (lane == 0 && warp <= 10) {
        const int w = warp - 9;
        for (int e = 0; e < 2; e++) {
          mbar_wait(BAR(B_EV + w * 2 + e), 0);
          __threadfence();
          atomicAdd(&g_kvcnt[p][0], 1u);
        }
      }
    } else {
      const int hl = tid - 288;
      {
        const int ce = m * 4 + p;
        if (hl < 32) *(float4*)(&g_kv[par ^ 1][0][0][0] + ce * 128 + hl * 4) = make_float4(0.f, 0.f, 0.f, 0.f);
        else if (hl < 40) (&g_z[par ^ 1][0][0])[ce * 8 + hl - 32] = 0.f;
      }
      mbar_wait(BAR(B_XDONE), 0);
      wait_count_ge(&g_kvcnt[p][0], 64u * tag);
      const float* kvp = &g_kv[par][8 * p][0][0];
      const float* zp = &g_z[par][8 * p][0];
      const uint32_t dst0 = sbase + 5 * 8192, dst1 = dst0 + 65536;
#pragma unroll
      for (int h2 = 0; h2 < 2; h2++) {
        float4 v[3];
#pragma unroll
        for (int i = 0; i < 3; i++) {
          const int c = (h2 * 3 + i) * 96 + hl;
          v[i] = c < 512 ? ldg_cg_f4(kvp + c * 4) : (c < 544 ? ldg_cg_f4(zp + (c - 512) * 4) : make_float4(0.f, 0.f, 0.f, 0.f));
        }
#pragma unroll
        for (int i = 0; i < 3; i++) {
          const int c = (h2 * 3 + i) * 96 + hl;
          if (c < 544) {
            const uint32_t lo = pack_bf16(v[i].x, v[i].y), hi = pack_bf16(v[i].z, v[i].w);
            asm volatile("st.shared.v2.u32 [%0], {%1,%2};" ::"r"(dst0 + c * 8), "r"(lo), "r"(hi) : "memory");
            asm volatile("st.shared.v2.u32 [%0], {%1,%2};" ::"r"(dst1 + c * 8), "r"(lo), "r"(hi) : "memory");
          }
        }
      }
      __syncwarp();
      if (lane == 0) mbar_arrive(BAR(B_KVREADY));
    }
  } else {
    asm volatile("setmaxnreg.inc.sync.aligned.u32 240;");
    const int w = warp >> 2, wq = warp & 3, t128 = tid & 127;
    const int g = lane >> 2, tq = lane & 3;
    const uint32_t area = sbase + (uint32_t)w * 65536u;
    const bool elect = (t128 == 0);
    PROF(w, 22);
    const uint32_t dbase = (sbase & 0x3FFFFu) >> 4;
    uint32_t xoff = (uint32_t)((m * 4 + p) * 18 + w) * 8192u + (uint32_t)t128 * 16u;
    uint32_t stash = area + (uint32_t)t128 * 16u;
    const uint32_t epoch_c = ld_relaxed(&g_epoch);
    auto xptr = [&](int slot, int jj) INL { return (uint4*)((char*)g_xbuf + ((xoff & ~1u) + (uint32_t)slot * 16384u + (uint32_t)jj * 2048u)); };
    uint32_t A[144];
    float rs0, rs1;
    auto release = [&](int st) INL {
      if (elect) { mbar_arrive_cluster(BAR(B_EMPTY + st), 0); mbar_arrive_cluster(BAR(B_EMPTY + st), 1); }
    };

    {
      const int row = wq * 16 + (lane & 7) + ((lane >> 3) & 1) * 8;
      const uint32_t rbase = area + row * 128;
      float s0[2][4] = {}, q0[2][4] = {}, q1[2][4] = {};
      const uint32_t ones = 0x3F803F80u;
#pragma unroll
      for (int b = 0; b < 8; b++) {
        mbar_wait(BAR(B_XFULL + w * 8 + b), 0);
        if (b == 0) PROF(w, 23);
        if (b == 7) PROF(w, 24);
#pragma unroll
        for (int kk = 0; kk < 4; kk++) {
          const int i = (b * 4 + kk) * 4;
          ldmatrix_x4(rbase + b * 8192 + (((kk * 2 + (lane >> 4)) ^ (row & 7)) << 4), A[i], A[i + 1], A[i + 2], A[i + 3]);
        }
#pragma unroll
        for (int kk = 0; kk < 4; kk++) {
          const int i = (b * 4 + kk) * 4;
          mma_16816(s0[kk & 1], A[i], A[i + 1], A[i + 2], A[i + 3], ones, ones);
          mma_16816(q0[kk & 1], A[i], A[i + 1], A[i + 2], A[i + 3], A[i], A[i + 2]);
          mma_16816(q1[kk & 1], A[i], A[i + 1], A[i + 2], A[i + 3], A[i + 1], A[i + 3]);
        }
      }
      const float mean0 = (s0[0][0] + s0[1][0]) * (1.f / 512.f), mean1 = (s0[0][2] + s0[1][2]) * (1.f / 512.f);
      const uint32_t m0 = pack_bf16(mean0, mean0), m1 = pack_bf16(mean1, mean1);
#pragma unroll
      for (int i = 0; i < 128; i += 2) {
        A[i] = hsub2_bf16(A[i], m0);
        A[i + 1] = hsub2_bf16(A[i + 1], m1);
      }
      float v0 = (g & 1) ? q0[0][1] + q0[1][1] : q0[0][0] + q0[1][0];
      float v1 = (g & 1) ? q1[0][3] + q1[1][3] : q1[0][2] + q1[1][2];
      const int src = 4 * g + (g >> 1);
      v0 = __shfl_sync(0xffffffffu, v0, src);
      v1 = __shfl_sync(0xffffffffu, v1, src);
      v0 = fmaxf(v0 * (1.f / 512.f) - mean0 * mean0, 0.f);
      v1 = fmaxf(v1 * (1.f / 512.f) - mean1 * mean1, 0.f);
      rs0 = rsqrtf(v0 + 1e-5f);
      rs1 = rsqrtf(v1 + 1e-5f);
      bar_sync(1 + w, 128);
      cluster_wait();
      asm volatile("" : "+r"(xoff), "+r"(stash));
      PROF(w, 0);
      release(6); release(7);
      if (elect) mbar_arrive(BAR(B_XDONE));
    }

    auto gu_chunk = [&](float (&acc)[32], int f, int slot, int xslot, int hb) INL {
      const float c0 = rs0 * -1.4426950408889634f, c1 = rs1 * -1.4426950408889634f;
      const float q0 = rs0 * rs0, q1 = rs1 * rs1;
      uint32_t h[4];
#pragma unroll
      for (int i = 0; i < 4; i++) {
        const float ga = acc[f * 8 + 2 * i], gb = acc[f * 8 + 2 * i + 1];
        const float ua = acc[16 + f * 8 + 2 * i], ub = acc[16 + f * 8 + 2 * i + 1];
        const float c = (i & 1) ? c1 : c0, q = (i & 1) ? q1 : q0;
        const float da = 1.f + ex2f(fminf(ga * c, 60.f)), db = 1.f + ex2f(fminf(gb * c, 60.f));
        const float rq = rcpf(da * db) * q;
        h[i] = tagged(pack_bf16(ga * ua * (db * rq), gb * ub * (da * rq)), xoff & 1u);
      }
      const int jj = hb * 2 + f;
      sts_u4(stash + slot * 8192 + jj * 2048, h[0], h[1], h[2], h[3]);
      stg_u4(xptr(xslot, jj), h[0], h[1], h[2], h[3]);
    };
    auto kv_stage = [&](float (&acc)[32], int c, int hb) INL {
      const int srow = wq * 16 + (lane & 7) + ((lane >> 3) & 1) * 8;
      const uint32_t base = area + (3 + c) * 8192 + srow * 128;
#pragma unroll
      for (int jj = 0; jj < 2; jj++) {
        const int a = c * 16 + jj * 8;
        uint32_t r0, r1, r2, r3;
        if (c == 0) {
          r0 = pack_bf16(phi_f(acc[a] * rs0), phi_f(acc[a + 1] * rs0));
          r1 = pack_bf16(phi_f(acc[a + 2] * rs1), phi_f(acc[a + 3] * rs1));
          r2 = pack_bf16(phi_f(acc[a + 4] * rs0), phi_f(acc[a + 5] * rs0));
          r3 = pack_bf16(phi_f(acc[a + 6] * rs1), phi_f(acc[a + 7] * rs1));
        } else {
          r0 = pack_bf16(acc[a] * rs0, acc[a + 1] * rs0);
          r1 = pack_bf16(acc[a + 2] * rs1, acc[a + 3] * rs1);
          r2 = pack_bf16(acc[a + 4] * rs0, acc[a + 5] * rs0);
          r3 = pack_bf16(acc[a + 6] * rs1, acc[a + 7] * rs1);
        }
        stmatrix_x4(base + (((hb * 4 + jj * 2 + (lane >> 4)) ^ (srow & 7)) << 4), r0, r1, r2, r3);
      }
    };
    const uint32_t kvb = area + 5 * 8192;
    const uint32_t kvfrag = kvb + ((lane & 7) + ((lane >> 3) & 1) * 8) * 32 + (lane >> 4) * 16;
    auto signal = [&](int e) INL {
      __syncwarp();
      if (lane == 0) mbar_arrive(BAR(B_EV + w * 2 + e));
    };

    auto pp_wait = [&]() INL { bar_sync(3 + w, 256); };
    auto pp_pass = [&]() INL { bar_arrive(3 + (w ^ 1), 256); };
    if (w == 1) pp_pass();
    int tw1 = 0, tw2 = 0, tw3 = 0;
#pragma unroll 1
    for (int t = 0; t < 5; t++) {
      const uint32_t ph = t & 1;
      const int kind = odd ? (t < 2 ? K_KV : K_GU) : (t < 4 ? K_GU : K_Q);
      const int slot = odd ? t - 2 : t, xslot = odd ? t + 4 : t;
      static_for<2>([&](auto hc) INL {
        constexpr int hb = decltype(hc)::value;
        float acc[32];
        TWAIT(tw2, pp_wait());
        static_for<4>([&](auto kc) INL {
          constexpr int kq = decltype(kc)::value, k = hb * 4 + kq;
          TWAIT(tw1, mbar_wait(BAR(B_FULL + k), ph));
          wgmma_fence();
          static_for<8>([&](auto kkc) INL {
            constexpr int kk = decltype(kkc)::value, i = (kq * 8 + kk) * 4;
            wgmma_n64_rs<(kq | kk) != 0, desc_lo(stage_off(k) + kk * 1024, 8192), kHi64>(acc, A[i], A[i + 1], A[i + 2], A[i + 3]);
          });
          wgmma_commit();
          if (kq == 2) pp_pass();
          if (kq > 0) {
            wgmma_wait<1>();
            release(k - 1);
          }
        });
        TWAIT(tw3, wgmma_wait<0>());
        release(hb * 4 + 3);
        if (hb == 0 && t == 0) xoff |= (epoch_c & 1u) ^ 1u;
        if (kind == K_GU) {
          gu_chunk(acc, 0, slot, xslot, hb);
          gu_chunk(acc, 1, slot, xslot, hb);
        } else if (kind == K_KV) {
          if (hb == 0 && t == 0) sts_u4(stash + 5 * 8192, 0x3F803F80u, 0x3F803F80u, 0x3F803F80u, 0x3F803F80u);
          kv_stage(acc, 0, hb);
          kv_stage(acc, 1, hb);
          if (hb == 1) {
            float kvacc[36];
            const int par = (xoff & 1u) ^ 1u;
            fence_proxy_async();
            bar_sync(1 + w, 128);
            wgmma_fence();
            static_for<4>([&](auto kkc) INL {
              constexpr int kk = decltype(kkc)::value;
              wgmma_n72_ss_tt<kk != 0, desc_lo(3 * 8192 + kk * 2048, 0), desc_lo(4 * 8192 + kk * 2048, 8192 - kk * 2048)>(kvacc, dbase + w * 4096);
            });
            wgmma_commit();
            wgmma_wait<0>();
            float c[8];
#pragma unroll
            for (int i = 0; i < 8; i++)
              c[i] = wq == 0 ? kvacc[i] : (wq == 1 ? kvacc[8 + i] : (wq == 2 ? kvacc[16 + i] : kvacc[24 + i]));
            const int head = (2 * p + t) * 4 + wq;
            float* kvp = &g_kv[par][head][0][0];
            red_add_v2(kvp + g * 16 + 2 * tq, c[0], c[1]);
            red_add_v2(kvp + (g + 8) * 16 + 2 * tq, c[2], c[3]);
            red_add_v2(kvp + g * 16 + 8 + 2 * tq, c[4], c[5]);
            red_add_v2(kvp + (g + 8) * 16 + 8 + 2 * tq, c[6], c[7]);
            if (tq == 0) {
              red_add(&g_z[par][head][g], kvacc[32]);
              red_add(&g_z[par][head][g + 8], kvacc[34]);
            }
            signal(t);
          }
        } else {
          uint32_t aq[4][4];
#pragma unroll
          for (int c = 0; c < 4; c++) {
            const int a = c * 8;
            aq[c][0] = pack_bf16(phi_f(acc[a] * rs0), phi_f(acc[a + 1] * rs0));
            aq[c][1] = pack_bf16(phi_f(acc[a + 2] * rs1), phi_f(acc[a + 3] * rs1));
            aq[c][2] = pack_bf16(phi_f(acc[a + 4] * rs0), phi_f(acc[a + 5] * rs0));
            aq[c][3] = pack_bf16(phi_f(acc[a + 6] * rs1), phi_f(acc[a + 7] * rs1));
          }
          if (hb == 0) mbar_wait(BAR(B_KVREADY), 0);
          uint32_t Bf[4][6];
#pragma unroll
          for (int c = 0; c < 4; c++) {
            ldmatrix_x4_trans(kvfrag + (hb * 4 + c) * 512, Bf[c][0], Bf[c][1], Bf[c][2], Bf[c][3]);
            Bf[c][4] = lds_u32(kvb + 4096 + (hb * 4 + c) * 32 + tq * 4);
            Bf[c][5] = lds_u32(kvb + 4096 + (hb * 4 + c) * 32 + 16 + tq * 4);
          }
          float n0[4][4] = {}, n1[4][4] = {}, dn[4][4] = {};
#pragma unroll
          for (int c = 0; c < 4; c++) {
            mma_16816(dn[c], aq[c][0], aq[c][1], aq[c][2], aq[c][3], Bf[c][4], Bf[c][5]);
            mma_16816(n0[c], aq[c][0], aq[c][1], aq[c][2], aq[c][3], Bf[c][0], Bf[c][1]);
            mma_16816(n1[c], aq[c][0], aq[c][1], aq[c][2], aq[c][3], Bf[c][2], Bf[c][3]);
          }
          if (hb == 1) bar_sync(1 + w, 128);
          const uint32_t tg = xoff & 1u;
#pragma unroll
          for (int c = 0; c < 4; c++) {
            const float i0 = __fdividef(1.f, dn[c][0] + 1e-6f), i1 = __fdividef(1.f, dn[c][2] + 1e-6f);
            aq[c][0] = tagged(pack_bf16(n0[c][0] * i0, n0[c][1] * i0), tg);
            aq[c][1] = tagged(pack_bf16(n0[c][2] * i1, n0[c][3] * i1), tg);
            aq[c][2] = tagged(pack_bf16(n1[c][0] * i0, n1[c][1] * i0), tg);
            aq[c][3] = tagged(pack_bf16(n1[c][2] * i1, n1[c][3] * i1), tg);
          }
#pragma unroll
          for (int c = 0; c < 4; c++) {
            stg_u4(xptr(4 + hb, c), aq[c][0], aq[c][1], aq[c][2], aq[c][3]);
            sts_u4(stash + (4 + hb) * 8192 + c * 2048, aq[c][0], aq[c][1], aq[c][2], aq[c][3]);
          }
        }
      });
      PROF(w, 1 + 2 * t);
    }
    PROF(w, 10);

    const int n_own = odd ? 3 : 6;
    auto load_a = [&](int kb) INL {
      if (kb < n_own) {
#pragma unroll
        for (int jj = 0; jj < 4; jj++) {
          const int i = (kb * 4 + jj) * 4;
          lds_u4(stash + kb * 8192 + jj * 2048, A[i], A[i + 1], A[i + 2], A[i + 3]);
        }
      } else {
        const int xs = odd ? kb - 3 : kb;
#pragma unroll
        for (int jj = 0; jj < 4; jj++) {
          const int i = (kb * 4 + jj) * 4;
          ldg_poll_u4(xptr(xs, jj), A[i], A[i + 1], A[i + 2], A[i + 3]);
        }
      }
    };
    auto fix_a = [&](int kb) INL {
      if (kb >= n_own) {
        const int xs = odd ? kb - 3 : kb;
        recv_group<4>(xptr(xs, 0), &A[kb * 16], xoff & 1u);
      }
    };
#pragma unroll
    for (int kb = 0; kb < 7; kb++) load_a(kb);
    PROF(w, 11);

    const uint32_t ooff = (uint32_t)(m * 128 + w * 64 + wq * 16 + (lane >> 3)) * kD + odd * 256 + p * 64 + (lane & 7) * 8;
    float acc2[2][32];
    uint32_t poff = (uint32_t)((m * 2 + odd) * 24 + w) * 8192u + (uint32_t)t128 * 16u;
    asm volatile("" : "+r"(poff));
    auto pptr = [&](int dest, int sl) INL { return (uint4*)((char*)g_pbuf + (poff + (uint32_t)(dest * 3 + sl) * 16384u)); };
    uint32_t P[3][16];
    uint4 xr[4];
    auto send = [&](float (&acc)[32], int bi) INL {
      uint4* dst = pptr((p + 1 + bi) & 3, bi);
#pragma unroll
      for (int q = 0; q < 4; q++)
        stg_u4(dst + q * 128, tagged(pack_bf16(acc[q * 8], acc[q * 8 + 1]), xoff & 1u), tagged(pack_bf16(acc[q * 8 + 2], acc[q * 8 + 3]), xoff & 1u),
               tagged(pack_bf16(acc[q * 8 + 4], acc[q * 8 + 5]), xoff & 1u), tagged(pack_bf16(acc[q * 8 + 6], acc[q * 8 + 7]), xoff & 1u));
      PROF(w, 12 + 2 * bi);
    };
    auto fetch = [&](int sl) INL {
#pragma unroll
      for (int q = 0; q < 4; q++) ldg_poll_u4(pptr(p, sl) + q * 128, P[sl][q * 4], P[sl][q * 4 + 1], P[sl][q * 4 + 2], P[sl][q * 4 + 3]);
    };
    static_for<36>([&](auto ic) INL {
      constexpr int i = decltype(ic)::value, bi = p2_bi(i), kb = p2_kb(i), j = i >> 1, st = j & 7;
      if (i == 9) { load_a(7); load_a(8); }
      if (i == 14) PROF(w, 2);
      if (bi == 0 && kb >= 3) fix_a(kb);
      if (i == 15) PROF(w, 4);
      if (i == 7) PROF(w, 6);
      if (i == 0 || i == 7 || i == 14 || i == 18 || i == 27) pp_wait();
      if ((i & 1) == 0) mbar_wait(BAR(B_FULL + st), (5 + (j >> 3)) & 1);
      wgmma_fence();
      static_for<4>([&](auto kkc) INL {
        constexpr int kk = decltype(kkc)::value, a = (kb * 4 + kk) * 4;
        wgmma_n64_rs<(kb | kk) != 0, desc_lo(stage_off(st) + (i & 1) * 8192 + kk * 2048, 0), kHi128>(acc2[bi & 1], A[a], A[a + 1], A[a + 2], A[a + 3]);
      });
      wgmma_commit();
      if (i == 4 || i == 11 || i == 15 || i == 24 || (i == 33 && w == 0)) pp_pass();
      if (i > 0) {
        wgmma_wait<1>();
        if ((i & 1) == 0 && j - 1 <= 9) release((j - 1) & 7);
      }
      if constexpr (i == 17) { send(acc2[0], 0); wgmma_wait<0>(); send(acc2[1], 1); }
      if constexpr (i == 26) { wgmma_wait<0>(); send(acc2[0], 2); }
      if constexpr (i == 29) fetch(0);
      if constexpr (i == 30) fetch(1);
      if constexpr (i == 28) {
#pragma unroll
        for (int q = 0; q < 4; q++) xr[q] = __ldg((const uint4*)(x + ooff + q * 4 * kD));
      }
      if constexpr (i == 32) fetch(2);
    });
#pragma unroll
    for (int sl = 0; sl < 3; sl++) { PROF(w, 13 + 2 * sl); recv_group<4>(pptr(p, sl), &P[sl][0], xoff & 1u); }
    wgmma_wait<0>();
    PROF(w, 18);
    {
      const uint32_t tile = area + wq * 4352;
#pragma unroll
      for (int q = 0; q < 8; q++) {
        float rr[4];
#pragma unroll
        for (int e = 0; e < 4; e++) rr[e] = acc2[1][q * 4 + e];
#pragma unroll
        for (int sl = 0; sl < 3; sl++) {
          rr[0] += __uint_as_float(P[sl][2 * q] << 16);
          rr[1] += __uint_as_float(P[sl][2 * q] & 0xffff0000u);
          rr[2] += __uint_as_float(P[sl][2 * q + 1] << 16);
          rr[3] += __uint_as_float(P[sl][2 * q + 1] & 0xffff0000u);
        }
        const uint32_t ad = tile + g * 272 + q * 32 + tq * 8;
        asm volatile("st.shared.v2.f32 [%0], {%1,%2};" ::"r"(ad), "f"(rr[0]), "f"(rr[1]) : "memory");
        asm volatile("st.shared.v2.f32 [%0], {%1,%2};" ::"r"(ad + 8 * 272), "f"(rr[2]), "f"(rr[3]) : "memory");
      }
      __syncwarp();
#pragma unroll
      for (int q = 0; q < 4; q++) {
        const uint32_t ad = tile + ((lane >> 3) + 4 * q) * 272 + (lane & 7) * 32;
        uint32_t v[8];
        lds_u4(ad, v[0], v[1], v[2], v[3]);
        lds_u4(ad + 16, v[4], v[5], v[6], v[7]);
        const uint32_t xv[4] = {xr[q].x, xr[q].y, xr[q].z, xr[q].w};
        uint32_t o[4];
#pragma unroll
        for (int e = 0; e < 4; e++)
          o[e] = pack_bf16(__uint_as_float(v[2 * e]) + __uint_as_float(xv[e] << 16), __uint_as_float(v[2 * e + 1]) + __uint_as_float(xv[e] & 0xffff0000u));
        stg_u4(out + ooff + q * 4 * kD, o[0], o[1], o[2], o[3]);
      }
    }
    PROF(w, 19);
    if (tid == 0) {
      const uint32_t old = atomicAdd(&g_done, 1u);
      if ((old & 127u) == 127u) st_relaxed(&g_epoch, ld_relaxed(&g_epoch) + 1u);
    }
  }
#undef BAR
}

typedef CUresult (*EncodeFn)(CUtensorMap*, CUtensorMapDataType, cuuint32_t, void*, const cuuint64_t*, const cuuint64_t*,
                             const cuuint32_t*, const cuuint32_t*, CUtensorMapInterleave, CUtensorMapSwizzle,
                             CUtensorMapL2promotion, CUtensorMapFloatOOBfill);

void make_map(EncodeFn enc, CUtensorMap* tm, const void* ptr, int rows, int cols, bool narrow) {
  cuuint64_t gd[2] = {(cuuint64_t)cols, (cuuint64_t)rows};
  cuuint64_t gs[1] = {(cuuint64_t)cols * 2};
  cuuint32_t bd[2] = {narrow ? 32u : 64u, narrow ? 128u : 64u};
  cuuint32_t es[2] = {1, 1};
  enc(tm, CU_TENSOR_MAP_DATA_TYPE_BFLOAT16, 2, const_cast<void*>(ptr), gd, gs, bd, es, CU_TENSOR_MAP_INTERLEAVE_NONE,
      narrow ? CU_TENSOR_MAP_SWIZZLE_64B : CU_TENSOR_MAP_SWIZZLE_128B, CU_TENSOR_MAP_L2_PROMOTION_L2_256B, CU_TENSOR_MAP_FLOAT_OOB_FILL_NONE);
}

}

extern "C" void kernel_launch(void* const* d_in, const int* in_sizes, int n_in, void* d_out, int out_size) {
  static EncodeFn enc = nullptr;
  if (!enc) {
    void* fn = nullptr;
    cudaDriverEntryPointQueryResult qr;
    cudaGetDriverEntryPoint("cuTensorMapEncodeTiled", &fn, cudaEnableDefault, &qr);
    enc = (EncodeFn)fn;
    cudaFuncSetAttribute(fused_kernel, cudaFuncAttributeMaxDynamicSharedMemorySize, kSmemBytes);
  }
  CUtensorMap tm_x, tm_wqkv, tm_w1, tm_w3, tm_w2, tm_wo;
  make_map(enc, &tm_x, d_in[0], kS, kD, false);
  make_map(enc, &tm_wqkv, d_in[1], kD, 3 * kD, true);
  make_map(enc, &tm_wo, d_in[2], kD, kD, false);
  make_map(enc, &tm_w1, d_in[4], kD, kF, true);
  make_map(enc, &tm_w3, d_in[5], kD, kF, true);
  make_map(enc, &tm_w2, d_in[6], kF, kD, false);
  fused_kernel<<<128, 384, kSmemBytes>>>(tm_x, tm_wqkv, tm_w1, tm_w3, tm_w2, tm_wo, (const __nv_bfloat16*)d_in[0],
                                         (__nv_bfloat16*)d_out, (const __nv_bfloat16*)d_in[1], (const __nv_bfloat16*)d_in[4],
                                         (const __nv_bfloat16*)d_in[5]);
}
```

```cpp
#include <cuda_runtime.h>
#include <cuda_bf16.h>
#include <cuda.h>
#include <stdint.h>

extern __shared__ __align__(1024) uint8_t smem_raw[];

namespace {

constexpr int kS = 2048, kD = 512, kF = 1792;
#define XPOS 1
#define XUP 16
constexpr uint32_t kSpinLimit = 1u << 22;

__device__ uint4    g_xbuf[16][4][9][2][4][128];
__device__ uint4    g_pbuf[16][2][4][3][2][4][128];
__device__ float    g_kv[2][32][16][16];
__device__ float    g_z[2][32][16];
__device__ uint32_t g_kvcnt[4][32];
__device__ uint32_t g_epoch;
__device__ uint32_t g_done;
#define PROF(wg, i) do {} while (0)
#define TWAIT(acc, stmt) do { stmt; } while (0)

__device__ __forceinline__ uint32_t smem_u32(const void* p) { return (uint32_t)__cvta_generic_to_shared(p); }
__device__ __forceinline__ void mbar_init(uint32_t bar, uint32_t cnt) {
  asm volatile("mbarrier.init.shared::cta.b64 [%0], %1;" ::"r"(bar), "r"(cnt) : "memory");
}
__device__ __forceinline__ void mbar_expect_tx(uint32_t bar, uint32_t bytes) {
  asm volatile("mbarrier.arrive.expect_tx.shared::cta.b64 _, [%0], %1;" ::"r"(bar), "r"(bytes) : "memory");
}
__device__ __forceinline__ void mbar_arrive(uint32_t bar) {
  asm volatile("mbarrier.arrive.shared::cta.b64 _, [%0];" ::"r"(bar) : "memory");
}
__device__ __forceinline__ void mbar_wait(uint32_t bar, uint32_t parity) {
  asm volatile(
      "{\n.reg .pred p;\n"
      "LAB_WAIT:\n"
      "mbarrier.try_wait.parity.shared::cta.b64 p, [%0], %1;\n"
      "@p bra DONE;\n"
      "bra LAB_WAIT;\n"
      "DONE:\n}" ::"r"(bar), "r"(parity) : "memory");
}
__device__ __forceinline__ void tma_load_2d(uint32_t dst, const CUtensorMap* tm, uint32_t bar, int c0, int c1) {
  asm volatile(
      "cp.async.bulk.tensor.2d.shared::cluster.global.mbarrier::complete_tx::bytes [%0], [%1, {%3, %4}], [%2];" ::"r"(dst),
      "l"(tm), "r"(bar), "r"(c0), "r"(c1)
      : "memory");
}
__device__ __forceinline__ void tma_load_2d_mc(uint32_t dst, const CUtensorMap* tm, uint32_t bar, int c0, int c1) {
  asm volatile(
      "cp.async.bulk.tensor.2d.shared::cluster.global.mbarrier::complete_tx::bytes.multicast::cluster [%0], [%1, {%3, %4}], [%2], %5;" ::"r"(dst),
      "l"(tm), "r"(bar), "r"(c0), "r"(c1), "h"((uint16_t)3)
      : "memory");
}
__device__ __forceinline__ void mbar_arrive_cluster(uint32_t bar, uint32_t cta) {
  asm volatile("{\n.reg .b32 ra;\nmapa.shared::cluster.u32 ra, %0, %1;\nmbarrier.arrive.shared::cluster.b64 _, [ra];\n}" ::"r"(bar), "r"(cta) : "memory");
}
__device__ __forceinline__ void prefetch_tmap(const CUtensorMap* tm) {
  asm volatile("prefetch.tensormap [%0];" ::"l"(tm) : "memory");
}
__device__ __forceinline__ void wgmma_fence() { asm volatile("wgmma.fence.sync.aligned;" ::: "memory"); }
__device__ __forceinline__ void wgmma_commit() { asm volatile("wgmma.commit_group.sync.aligned;" ::: "memory"); }
template <int N>
__device__ __forceinline__ void wgmma_wait() { asm volatile("wgmma.wait_group.sync.aligned %0;" ::"n"(N) : "memory"); }
__device__ __forceinline__ void bar_sync(int id, int n) { asm volatile("bar.sync %0, %1;" ::"r"(id), "r"(n) : "memory"); }
__device__ __forceinline__ void bar_arrive(int id, int n) { asm volatile("bar.arrive %0, %1;" ::"r"(id), "r"(n) : "memory"); }
__device__ __forceinline__ void fence_proxy_async() { asm volatile("fence.proxy.async.shared::cta;" ::: "memory"); }

__device__ __forceinline__ uint32_t ld_acquire(const uint32_t* p) {
  uint32_t v;
  asm volatile("ld.acquire.gpu.global.u32 %0, [%1];" : "=r"(v) : "l"(p) : "memory");
  return v;
}
__device__ __forceinline__ uint32_t ld_relaxed(const uint32_t* p) {
  uint32_t v;
  asm volatile("ld.relaxed.gpu.global.u32 %0, [%1];" : "=r"(v) : "l"(p));
  return v;
}
__device__ __forceinline__ void cluster_wait() { asm volatile("barrier.cluster.wait.aligned;" ::: "memory"); }
__device__ __forceinline__ void st_relaxed(uint32_t* p, uint32_t v) {
  asm volatile("st.relaxed.gpu.global.u32 [%0], %1;" ::"l"(p), "r"(v) : "memory");
}
__device__ __forceinline__ void wait_flag_eq(const uint32_t* p, uint32_t val) {
  uint32_t it = 0;
  while (ld_acquire(p) != val) {
    if (++it > kSpinLimit) break;
  }
}
__device__ __forceinline__ void wait_count_ge(const uint32_t* p, uint32_t val) {
  uint32_t it = 0;
  while ((int32_t)(ld_acquire(p) - val) < 0) {
    __nanosleep(64);
    if (++it > kSpinLimit) break;
  }
}
__device__ __forceinline__ void ldg_poll_u4(const void* p, uint32_t& a, uint32_t& b, uint32_t& c, uint32_t& d) {
  asm volatile("ld.relaxed.gpu.global.v4.u32 {%0,%1,%2,%3}, [%4];" : "=r"(a), "=r"(b), "=r"(c), "=r"(d) : "l"(p) : "memory");
}
template <int N>
__device__ __forceinline__ void recv_group(const uint4* p, uint32_t* r, uint32_t tag) {
  uint32_t it = 0;
  while (true) {
    uint32_t bad = 0u;
#pragma unroll
    for (int i = 0; i < 4 * N; i++) bad |= r[i] ^ tag;
    if (!__any_sync(0xffffffffu, (bad & 1u) != 0u) || ++it > kSpinLimit) break;
#pragma unroll
    for (int q = 0; q < N; q++) ldg_poll_u4(p + q * 128, r[q * 4], r[q * 4 + 1], r[q * 4 + 2], r[q * 4 + 3]);
  }
}
__device__ __forceinline__ uint32_t tagged(uint32_t v, uint32_t tag) { return (v & ~1u) | tag; }
__device__ __forceinline__ float4 ldg_cg_f4(const void* p) {
  float4 v;
  asm volatile("ld.global.cg.v4.f32 {%0,%1,%2,%3}, [%4];" : "=f"(v.x), "=f"(v.y), "=f"(v.z), "=f"(v.w) : "l"(p) : "memory");
  return v;
}
__device__ __forceinline__ void stg_u4(void* p, uint32_t a, uint32_t b, uint32_t c, uint32_t d) {
  asm volatile("st.global.v4.u32 [%0], {%1,%2,%3,%4};" ::"l"(p), "r"(a), "r"(b), "r"(c), "r"(d) : "memory");
}
__device__ __forceinline__ void stg_f4(void* p, float a, float b, float c, float d) {
  asm volatile("st.global.v4.f32 [%0], {%1,%2,%3,%4};" ::"l"(p), "f"(a), "f"(b), "f"(c), "f"(d) : "memory");
}
__device__ __forceinline__ void sts_u4(uint32_t addr, uint32_t a, uint32_t b, uint32_t c, uint32_t d) {
  asm volatile("st.shared.v4.u32 [%0], {%1,%2,%3,%4};" ::"r"(addr), "r"(a), "r"(b), "r"(c), "r"(d) : "memory");
}
__device__ __forceinline__ void lds_u4(uint32_t addr, uint32_t& a, uint32_t& b, uint32_t& c, uint32_t& d) {
  asm volatile("ld.shared.v4.u32 {%0,%1,%2,%3}, [%4];" : "=r"(a), "=r"(b), "=r"(c), "=r"(d) : "r"(addr) : "memory");
}
__device__ __forceinline__ uint32_t lds_u32(uint32_t addr) {
  uint32_t v;
  asm volatile("ld.shared.u32 %0, [%1];" : "=r"(v) : "r"(addr) : "memory");
  return v;
}
__device__ __forceinline__ void ldmatrix_x4(uint32_t addr, uint32_t& a, uint32_t& b, uint32_t& c, uint32_t& d) {
  asm volatile("ldmatrix.sync.aligned.m8n8.x4.shared.b16 {%0,%1,%2,%3}, [%4];" : "=r"(a), "=r"(b), "=r"(c), "=r"(d) : "r"(addr) : "memory");
}
__device__ __forceinline__ void ldmatrix_x4_trans(uint32_t addr, uint32_t& a, uint32_t& b, uint32_t& c, uint32_t& d) {
  asm volatile("ldmatrix.sync.aligned.m8n8.x4.trans.shared.b16 {%0,%1,%2,%3}, [%4];" : "=r"(a), "=r"(b), "=r"(c), "=r"(d) : "r"(addr) : "memory");
}
__device__ __forceinline__ void stmatrix_x4(uint32_t addr, uint32_t a, uint32_t b, uint32_t c, uint32_t d) {
  asm volatile("stmatrix.sync.aligned.m8n8.x4.shared.b16 [%0], {%1,%2,%3,%4};" ::"r"(addr), "r"(a), "r"(b), "r"(c), "r"(d) : "memory");
}
__device__ __forceinline__ void mma_16816(float (&c)[4], uint32_t a0, uint32_t a1, uint32_t a2, uint32_t a3, uint32_t b0, uint32_t b1) {
  asm(
      "mma.sync.aligned.m16n8k16.row.col.f32.bf16.bf16.f32 {%0,%1,%2,%3}, {%4,%5,%6,%7}, {%8,%9}, {%0,%1,%2,%3};"
      : "+f"(c[0]), "+f"(c[1]), "+f"(c[2]), "+f"(c[3])
      : "r"(a0), "r"(a1), "r"(a2), "r"(a3), "r"(b0), "r"(b1));
}
__device__ __forceinline__ uint32_t pack_bf16(float lo, float hi) {
  uint32_t r;
  asm("cvt.rn.bf16x2.f32 %0, %1, %2;" : "=r"(r) : "f"(hi), "f"(lo));
  return r;
}
__device__ __forceinline__ uint32_t hsub2_bf16(uint32_t a, uint32_t b) {
  uint32_t r;
  asm("sub.rn.bf16x2 %0, %1, %2;" : "=r"(r) : "r"(a), "r"(b));
  return r;
}
__device__ __forceinline__ float ex2f(float x) {
  float r;
  asm("ex2.approx.ftz.f32 %0, %1;" : "=f"(r) : "f"(x));
  return r;
}
__device__ __forceinline__ float rcpf(float x) {
  float r;
  asm("rcp.approx.ftz.f32 %0, %1;" : "=f"(r) : "f"(x));
  return r;
}
__device__ __forceinline__ void red_add_v2(float* p, float a, float b) {
  asm volatile("red.relaxed.gpu.global.add.v2.f32 [%0], {%1,%2};" ::"l"(p), "f"(a), "f"(b) : "memory");
}
__device__ __forceinline__ void red_add(float* p, float a) {
  asm volatile("red.relaxed.gpu.global.add.f32 [%0], %1;" ::"l"(p), "f"(a) : "memory");
}
__device__ __forceinline__ float phi_f(float t) {
  float e = ex2f(t * 1.4426950408889634f);
  return (t > 0.f ? t + 1.f : e) + 1e-6f;
}

#define R8(a, o) "+f"(a[o + 0]), "+f"(a[o + 1]), "+f"(a[o + 2]), "+f"(a[o + 3]), "+f"(a[o + 4]), "+f"(a[o + 5]), "+f"(a[o + 6]), "+f"(a[o + 7])

#define W8(a, o) "=f"(a[o + 0]), "=f"(a[o + 1]), "=f"(a[o + 2]), "=f"(a[o + 3]), "=f"(a[o + 4]), "=f"(a[o + 5]), "=f"(a[o + 6]), "=f"(a[o + 7])
#define D32 "{%0,%1,%2,%3,%4,%5,%6,%7,%8,%9,%10,%11,%12,%13,%14,%15,%16,%17,%18,%19,%20,%21,%22,%23,%24,%25,%26,%27,%28,%29,%30,%31}"
#define D36 "{%0,%1,%2,%3,%4,%5,%6,%7,%8,%9,%10,%11,%12,%13,%14,%15,%16,%17,%18,%19,%20,%21,%22,%23,%24,%25,%26,%27,%28,%29,%30,%31,%32,%33,%34,%35}"

constexpr uint32_t kHi128 = (1024u >> 4) | (1u << 30);
constexpr uint32_t kHi64 = (512u >> 4) | (2u << 30);
__host__ __device__ constexpr uint32_t desc_lo(uint32_t off, uint32_t lbo) { return (off >> 4) | ((lbo >> 4) << 16); }

template <bool ACC, uint32_t LO, uint32_t HI>
__device__ __forceinline__ void wgmma_n64_rs(float (&d)[32], uint32_t a0, uint32_t a1, uint32_t a2, uint32_t a3) {
  if (ACC) {
    asm volatile(
        "{\n.reg .pred p;\n.reg .b32 lo;\n.reg .b64 dd;\nsetp.eq.b32 p, 0, 0;\nmov.u32 lo, 64;\nadd.u32 lo, lo, %36;\nmov.b64 dd, {lo, %37};\n"
        "wgmma.mma_async.sync.aligned.m64n64k16.f32.bf16.bf16 " D32 ", {%32,%33,%34,%35}, dd, p, 1, 1, 1;\n}"
        : R8(d, 0), R8(d, 8), R8(d, 16), R8(d, 24)
        : "r"(a0), "r"(a1), "r"(a2), "r"(a3), "n"(LO), "n"(HI));
  } else {
    asm volatile(
        "{\n.reg .pred p;\n.reg .b32 lo;\n.reg .b64 dd;\nsetp.ne.b32 p, 0, 0;\nmov.u32 lo, 64;\nadd.u32 lo, lo, %36;\nmov.b64 dd, {lo, %37};\n"
        "wgmma.mma_async.sync.aligned.m64n64k16.f32.bf16.bf16 " D32 ", {%32,%33,%34,%35}, dd, p, 1, 1, 1;\n}"
        : W8(d, 0), W8(d, 8), W8(d, 16), W8(d, 24)
        : "r"(a0), "r"(a1), "r"(a2), "r"(a3), "n"(LO), "n"(HI));
  }
}
template <bool ACC, uint32_t LOA, uint32_t LOB>
__device__ __forceinline__ void wgmma_n72_ss_tt(float (&d)[36], uint32_t base) {
  if (ACC) {
    asm volatile(
        "{\n.reg .pred p;\n.reg .b32 lo;\n.reg .b64 da, db;\nsetp.eq.b32 p, 0, 0;\n"
        "add.u32 lo, %36, %37;\nmov.b64 da, {lo, %39};\nadd.u32 lo, %36, %38;\nmov.b64 db, {lo, %39};\n"
        "wgmma.mma_async.sync.aligned.m64n72k16.f32.bf16.bf16 " D36 ", da, db, p, 1, 1, 1, 1;\n}"
        : R8(d, 0), R8(d, 8), R8(d, 16), R8(d, 24), "+f"(d[32]), "+f"(d[33]), "+f"(d[34]), "+f"(d[35])
        : "r"(base), "n"(LOA), "n"(LOB), "n"(kHi128));
  } else {
    asm volatile(
        "{\n.reg .pred p;\n.reg .b32 lo;\n.reg .b64 da, db;\nsetp.ne.b32 p, 0, 0;\n"
        "add.u32 lo, %36, %37;\nmov.b64 da, {lo, %39};\nadd.u32 lo, %36, %38;\nmov.b64 db, {lo, %39};\n"
        "wgmma.mma_async.sync.aligned.m64n72k16.f32.bf16.bf16 " D36 ", da, db, p, 1, 1, 1, 1;\n}"
        : W8(d, 0), W8(d, 8), W8(d, 16), W8(d, 24), "=f"(d[32]), "=f"(d[33]), "=f"(d[34]), "=f"(d[35])
        : "r"(base), "n"(LOA), "n"(LOB), "n"(kHi128));
  }
}

#define INL __attribute__((always_inline))
template <uint32_t LO>
__device__ __forceinline__ void wgmma_n24_rs(float (&d)[12], uint32_t a0, uint32_t a1, uint32_t a2, uint32_t a3, uint32_t base) {
  asm volatile(
      "{\n.reg .pred p;\n.reg .b32 lo;\n.reg .b64 dd;\nsetp.ne.b32 p, 0, 0;\nadd.u32 lo, %16, %17;\nmov.b64 dd, {lo, %18};\n"
      "wgmma.mma_async.sync.aligned.m64n24k16.f32.bf16.bf16 {%0,%1,%2,%3,%4,%5,%6,%7,%8,%9,%10,%11}, {%12,%13,%14,%15}, dd, p, 1, 1, 1;\n}"
      : W8(d, 0), "=f"(d[8]), "=f"(d[9]), "=f"(d[10]), "=f"(d[11])
      : "r"(a0), "r"(a1), "r"(a2), "r"(a3), "r"(base), "n"(LO), "n"(256u >> 4));
}

template <int V> struct IC { static constexpr int value = V; };
template <int N, int I = 0, typename F>
__device__ __forceinline__ void static_for(F&& f) {
  if constexpr (I < N) { f(IC<I>{}); static_for<N, I + 1>(f); }
}

__host__ __device__ constexpr uint32_t stage_off(int st) {
  return st < 6 ? 131072u + (uint32_t)st * 16384u : (uint32_t)(st - 6) * 65536u + 49152u;
}

constexpr int B_FULL = 0, B_EMPTY = 8, B_XFULL = 16, B_XDONE = 32, B_KVREADY = 33, B_EV = 34, B_COUNT = 38;
constexpr uint32_t kBarOff = 229376;
constexpr int kSmemBytes = 229376 + 1024;

__host__ __device__ constexpr int p2_bi(int i) { return i < 7 ? 0 : i < 14 ? 1 : i < 16 ? 0 : i < 18 ? 1 : i / 9; }
__host__ __device__ constexpr int p2_kb(int i) { return i < 7 ? i : i < 14 ? i - 7 : i < 16 ? i - 7 : i < 18 ? i - 9 : i % 9; }

enum { K_NONE = 0, K_GU = 1, K_KV = 2, K_Q = 3 };

__global__ void __cluster_dims__(2, 1, 1) __launch_bounds__(384, 1)
fused_kernel(const __grid_constant__ CUtensorMap tm_x, const __grid_constant__ CUtensorMap tm_wqkv,
             const __grid_constant__ CUtensorMap tm_w1, const __grid_constant__ CUtensorMap tm_w3,
             const __grid_constant__ CUtensorMap tm_w2, const __grid_constant__ CUtensorMap tm_wo,
             const __nv_bfloat16* __restrict__ x, __nv_bfloat16* __restrict__ out) {
  const uint32_t sbase = smem_u32(smem_raw);
  const uint32_t bars = sbase + kBarOff;
  const int tid = threadIdx.x, lane = tid & 31;
  const int warp = __shfl_sync(0xffffffffu, tid >> 5, 0);
  const int cr = blockIdx.x & 1;
  const int r = (blockIdx.x >> 1) & 7, m = ((blockIdx.x >> 4) << 1) | cr, p = r >> 1, odd = r & 1;
#define BAR(i) (bars + 8u * (uint32_t)(i))
  if (tid == 256) {
    if ((sbase & 0x3FFFFu) != 1024u) __trap();
#pragma unroll
    for (int i = 0; i < 16; i++) mbar_init(BAR(B_XFULL + i), 1);
    fence_proxy_async();
#pragma unroll
    for (int b = 0; b < XUP; b++) {
      mbar_expect_tx(BAR(B_XFULL + b), 8192);
      tma_load_2d(sbase + (b >> 3) * 65536 + (b & 7) * 8192, &tm_x, BAR(B_XFULL + b), (b & 7) * 64, m * 128 + (b >> 3) * 64);
    }
#pragma unroll
    for (int i = 0; i < 8; i++) { mbar_init(BAR(B_FULL + i), 1); mbar_init(BAR(B_EMPTY + i), 4); }
#pragma unroll
    for (int i = 0; i < 4; i++) mbar_init(BAR(B_EV + i), 4);
    mbar_init(BAR(B_XDONE), 2);
    mbar_init(BAR(B_KVREADY), 3);
    asm volatile("fence.mbarrier_init.release.cluster;" ::: "memory");
    fence_proxy_async();
  } else if (tid == 288) {
    prefetch_tmap(odd ? &tm_wqkv : (cr ? &tm_w3 : &tm_w1));
  }
  __syncwarp();
  asm volatile("barrier.cluster.arrive.relaxed.aligned;" ::: "memory");
  PROF((tid >> 7), 21);
  __syncthreads();

  if (warp >= 8) {
    asm volatile("setmaxnreg.dec.sync.aligned.u32 24;");
    PROF(2, 3);
    cluster_wait();
    PROF(2, 2);
    const uint32_t epoch = warp == 8 ? 0u : ld_relaxed(&g_epoch);
    const uint32_t tag = epoch + 1u;
    const int par = epoch & 1;
    if (warp == 8) {
      if (lane == 0) {
        int twp = 0;
        for (int j = 0; j < 10; j++) {
          const CUtensorMap* tm;
          int col;
          if (!odd) {
            if (j < 8) { tm = cr ? &tm_w3 : &tm_w1; col = 7 * p * 64 + j * 32; }
            else { tm = &tm_wqkv; col = 128 * p + (j - 8) * 64 + cr * 32; }
          } else {
            if (j < 4) { tm = &tm_wqkv; col = 512 + cr * 512 + 128 * p + j * 32; }
            else { tm = cr ? &tm_w3 : &tm_w1; col = (7 * p + 4) * 64 + (j - 4) * 32; }
          }
          const int t = j >> 1;
          for (int kq = 0; kq < 4; kq++) {
            if (j == 0 && kq == XPOS) {
              for (int b = XUP; b < 16; b++) {
                mbar_expect_tx(BAR(B_XFULL + b), 8192);
                tma_load_2d(sbase + 65536 + (b & 7) * 8192, &tm_x, BAR(B_XFULL + b), (b & 7) * 64, m * 128 + 64);
              }
            }
            const int k = (j & 1) * 4 + kq;
            TWAIT(twp, mbar_wait(BAR(B_EMPTY + k), k < 6 ? ((t & 1) ^ 1) : (t & 1)));
            mbar_expect_tx(BAR(B_FULL + k), 16384);
            tma_load_2d_mc(sbase + stage_off(k) + cr * 8192, tm, BAR(B_FULL + k), col, kq * 128);
          }
        }
        for (int j = 0; j < 18; j++) {
          const int st = j & 7, n = 5 + (j >> 3);
          const int i = 2 * j + cr;
          const int bi = p2_bi(i), kb = p2_kb(i);
          const int col = odd * 256 + ((p + 1 + bi) & 3) * 64;
          const CUtensorMap* tmk;
          int row;
          if (!odd) {
            if (kb < 4) { tmk = &tm_w2; row = (7 * p + kb) * 64; }
            else if (kb < 6) { tmk = &tm_wo; row = (2 * p + kb - 4) * 64; }
            else { tmk = &tm_w2; row = (7 * p + 4 + kb - 6) * 64; }
          } else {
            if (kb < 3) { tmk = &tm_w2; row = (7 * p + 4 + kb) * 64; }
            else if (kb < 7) { tmk = &tm_w2; row = (7 * p + kb - 3) * 64; }
            else { tmk = &tm_wo; row = (2 * p + kb - 7) * 64; }
          }
          mbar_wait(BAR(B_EMPTY + st), st < 6 ? ((n & 1) ^ 1) : (n & 1));
          mbar_expect_tx(BAR(B_FULL + st), 16384);
          tma_load_2d_mc(sbase + stage_off(st) + cr * 8192, tmk, BAR(B_FULL + st), col, row);
        }
      }
    } else if (odd) {
      if (lane == 0 && warp <= 10) {
        const int w = warp - 9;
        for (int e = 0; e < 2; e++) {
          mbar_wait(BAR(B_EV + w * 2 + e), 0);
          __threadfence();
          atomicAdd(&g_kvcnt[p][0], 1u);
        }
      }
    } else {
      const int hl = tid - 288;
      {
        const int ce = m * 4 + p;
        if (hl < 32) *(float4*)(&g_kv[par ^ 1][0][0][0] + ce * 128 + hl * 4) = make_float4(0.f, 0.f, 0.f, 0.f);
        else if (hl < 40) (&g_z[par ^ 1][0][0])[ce * 8 + hl - 32] = 0.f;
      }
      mbar_wait(BAR(B_XDONE), 0);
      wait_count_ge(&g_kvcnt[p][0], 64u * tag);
      const float* kvp = &g_kv[par][8 * p][0][0];
      const float* zp = &g_z[par][8 * p][0];
      const uint32_t dst0 = sbase + 5 * 8192, dst1 = dst0 + 65536;
#pragma unroll
      for (int h2 = 0; h2 < 2; h2++) {
        float4 v[3];
#pragma unroll
        for (int i = 0; i < 3; i++) {
          const int c = (h2 * 3 + i) * 96 + hl;
          v[i] = c < 512 ? ldg_cg_f4(kvp + c * 4) : (c < 544 ? ldg_cg_f4(zp + (c - 512) * 4) : make_float4(0.f, 0.f, 0.f, 0.f));
        }
#pragma unroll
        for (int i = 0; i < 3; i++) {
          const int c = (h2 * 3 + i) * 96 + hl;
          if (c < 512) {
            const int h = c >> 6, d = (c >> 2) & 15, e = (c & 3) * 4;
            const uint32_t off = h * 768 + ((e >> 3) * 2 + (d >> 3)) * 128 + (d & 7) * 16 + (e & 7) * 2;
            const uint32_t lo = pack_bf16(v[i].x, v[i].y), hi = pack_bf16(v[i].z, v[i].w);
            asm volatile("st.shared.v2.u32 [%0], {%1,%2};" ::"r"(dst0 + off), "r"(lo), "r"(hi) : "memory");
            asm volatile("st.shared.v2.u32 [%0], {%1,%2};" ::"r"(dst1 + off), "r"(lo), "r"(hi) : "memory");
          } else if (c < 544) {
            const int h = (c - 512) >> 2, d = ((c - 512) & 3) * 4;
            const uint32_t off = h * 768 + (4 + (d >> 3)) * 128 + (d & 7) * 16;
            const float zz[4] = {v[i].x, v[i].y, v[i].z, v[i].w};
#pragma unroll
            for (int q = 0; q < 4; q++) {
              const uint32_t zq = pack_bf16(zz[q], zz[q]);
              sts_u4(dst0 + off + q * 16, zq, zq, zq, zq);
              sts_u4(dst1 + off + q * 16, zq, zq, zq, zq);
            }
          }
        }
      }
      fence_proxy_async();
      __syncwarp();
      if (lane == 0) mbar_arrive(BAR(B_KVREADY));
    }
  } else {
    asm volatile("setmaxnreg.inc.sync.aligned.u32 240;");
    const int w = warp >> 2, wq = warp & 3, t128 = tid & 127;
    const int g = lane >> 2, tq = lane & 3;
    const uint32_t area = sbase + (uint32_t)w * 65536u;
    const bool elect = (t128 == 0);
    PROF(w, 22);
    const uint32_t dbase = (sbase & 0x3FFFFu) >> 4;
    uint32_t xoff = (uint32_t)((m * 4 + p) * 18 + w) * 8192u + (uint32_t)t128 * 16u;
    uint32_t stash = area + (uint32_t)t128 * 16u;
    const uint32_t epoch_c = ld_relaxed(&g_epoch);
    auto xptr = [&](int slot, int jj) INL { return (uint4*)((char*)g_xbuf + ((xoff & ~1u) + (uint32_t)slot * 16384u + (uint32_t)jj * 2048u)); };
    uint32_t A[144];
    float rs0, rs1;
    auto release = [&](int st) INL {
      if (elect) { mbar_arrive_cluster(BAR(B_EMPTY + st), 0); mbar_arrive_cluster(BAR(B_EMPTY + st), 1); }
    };

    {
      const int row = wq * 16 + (lane & 7) + ((lane >> 3) & 1) * 8;
      const uint32_t rbase = area + row * 128;
      float s0[2][4] = {}, q0[2][4] = {}, q1[2][4] = {};
      const uint32_t ones = 0x3F803F80u;
#pragma unroll
      for (int b = 0; b < 8; b++) {
        mbar_wait(BAR(B_XFULL + w * 8 + b), 0);
        if (b == 0) PROF(w, 23);
        if (b == 7) PROF(w, 24);
#pragma unroll
        for (int kk = 0; kk < 4; kk++) {
          const int i = (b * 4 + kk) * 4;
          ldmatrix_x4(rbase + b * 8192 + (((kk * 2 + (lane >> 4)) ^ (row & 7)) << 4), A[i], A[i + 1], A[i + 2], A[i + 3]);
        }
#pragma unroll
        for (int kk = 0; kk < 4; kk++) {
          const int i = (b * 4 + kk) * 4;
          mma_16816(s0[kk & 1], A[i], A[i + 1], A[i + 2], A[i + 3], ones, ones);
          mma_16816(q0[kk & 1], A[i], A[i + 1], A[i + 2], A[i + 3], A[i], A[i + 2]);
          mma_16816(q1[kk & 1], A[i], A[i + 1], A[i + 2], A[i + 3], A[i + 1], A[i + 3]);
        }
      }
      const float mean0 = (s0[0][0] + s0[1][0]) * (1.f / 512.f), mean1 = (s0[0][2] + s0[1][2]) * (1.f / 512.f);
      const uint32_t m0 = pack_bf16(mean0, mean0), m1 = pack_bf16(mean1, mean1);
#pragma unroll
      for (int i = 0; i < 128; i += 2) {
        A[i] = hsub2_bf16(A[i], m0);
        A[i + 1] = hsub2_bf16(A[i + 1], m1);
      }
      float v0 = (g & 1) ? q0[0][1] + q0[1][1] : q0[0][0] + q0[1][0];
      float v1 = (g & 1) ? q1[0][3] + q1[1][3] : q1[0][2] + q1[1][2];
      const int src = 4 * g + (g >> 1);
      v0 = __shfl_sync(0xffffffffu, v0, src);
      v1 = __shfl_sync(0xffffffffu, v1, src);
      v0 = fmaxf(v0 * (1.f / 512.f) - mean0 * mean0, 0.f);
      v1 = fmaxf(v1 * (1.f / 512.f) - mean1 * mean1, 0.f);
      rs0 = rsqrtf(v0 + 1e-5f);
      rs1 = rsqrtf(v1 + 1e-5f);
      bar_sync(1 + w, 128);
      cluster_wait();
      asm volatile("" : "+r"(xoff), "+r"(stash));
      PROF(w, 0);
      release(6); release(7);
      if (elect) mbar_arrive(BAR(B_XDONE));
    }

    auto gu_chunk = [&](float (&acc)[32], int f, int slot, int xslot, int hb) INL {
      const float c0 = rs0 * -1.4426950408889634f, c1 = rs1 * -1.4426950408889634f;
      const float q0 = rs0 * rs0, q1 = rs1 * rs1;
      uint32_t h[4];
#pragma unroll
      for (int i = 0; i < 4; i++) {
        const float ga = acc[f * 8 + 2 * i], gb = acc[f * 8 + 2 * i + 1];
        const float ua = acc[16 + f * 8 + 2 * i], ub = acc[16 + f * 8 + 2 * i + 1];
        const float c = (i & 1) ? c1 : c0, q = (i & 1) ? q1 : q0;
        const float da = 1.f + ex2f(fminf(ga * c, 60.f)), db = 1.f + ex2f(fminf(gb * c, 60.f));
        const float rq = rcpf(da * db) * q;
        h[i] = tagged(pack_bf16(ga * ua * (db * rq), gb * ub * (da * rq)), xoff & 1u);
      }
      const int jj = hb * 2 + f;
      sts_u4(stash + slot * 8192 + jj * 2048, h[0], h[1], h[2], h[3]);
      stg_u4(xptr(xslot, jj), h[0], h[1], h[2], h[3]);
    };
    auto kv_stage = [&](float (&acc)[32], int c, int hb) INL {
      const int srow = wq * 16 + (lane & 7) + ((lane >> 3) & 1) * 8;
      const uint32_t base = area + (3 + c) * 8192 + srow * 128;
#pragma unroll
      for (int jj = 0; jj < 2; jj++) {
        const int a = c * 16 + jj * 8;
        uint32_t r0, r1, r2, r3;
        if (c == 0) {
          r0 = pack_bf16(phi_f(acc[a] * rs0), phi_f(acc[a + 1] * rs0));
          r1 = pack_bf16(phi_f(acc[a + 2] * rs1), phi_f(acc[a + 3] * rs1));
          r2 = pack_bf16(phi_f(acc[a + 4] * rs0), phi_f(acc[a + 5] * rs0));
          r3 = pack_bf16(phi_f(acc[a + 6] * rs1), phi_f(acc[a + 7] * rs1));
        } else {
          r0 = pack_bf16(acc[a] * rs0, acc[a + 1] * rs0);
          r1 = pack_bf16(acc[a + 2] * rs1, acc[a + 3] * rs1);
          r2 = pack_bf16(acc[a + 4] * rs0, acc[a + 5] * rs0);
          r3 = pack_bf16(acc[a + 6] * rs1, acc[a + 7] * rs1);
        }
        stmatrix_x4(base + (((hb * 4 + jj * 2 + (lane >> 4)) ^ (srow & 7)) << 4), r0, r1, r2, r3);
      }
    };
    auto signal = [&](int e) INL {
      __syncwarp();
      if (lane == 0) mbar_arrive(BAR(B_EV + w * 2 + e));
    };

    auto pp_wait = [&]() INL { bar_sync(3 + w, 256); };
    auto pp_pass = [&]() INL { bar_arrive(3 + (w ^ 1), 256); };
    if (w == 1) pp_pass();
    int tw1 = 0, tw2 = 0, tw3 = 0;
#pragma unroll 1
    for (int t = 0; t < 5; t++) {
      const uint32_t ph = t & 1;
      const int kind = odd ? (t < 2 ? K_KV : K_GU) : (t < 4 ? K_GU : K_Q);
      const int slot = odd ? t - 2 : t, xslot = odd ? t + 4 : t;
      static_for<2>([&](auto hc) INL {
        constexpr int hb = decltype(hc)::value;
        float acc[32];
        TWAIT(tw2, pp_wait());
        static_for<4>([&](auto kc) INL {
          constexpr int kq = decltype(kc)::value, k = hb * 4 + kq;
          TWAIT(tw1, mbar_wait(BAR(B_FULL + k), ph));
          wgmma_fence();
          static_for<8>([&](auto kkc) INL {
            constexpr int kk = decltype(kkc)::value, i = (kq * 8 + kk) * 4;
            wgmma_n64_rs<(kq | kk) != 0, desc_lo(stage_off(k) + kk * 1024, 8192), kHi64>(acc, A[i], A[i + 1], A[i + 2], A[i + 3]);
          });
          wgmma_commit();
          if (kq == 2) pp_pass();
          if (kq > 0) {
            wgmma_wait<1>();
            release(k - 1);
          }
        });
        TWAIT(tw3, wgmma_wait<0>());
        release(hb * 4 + 3);
        if (hb == 0 && t == 0) xoff |= (epoch_c & 1u) ^ 1u;
        if (kind == K_GU) {
          gu_chunk(acc, 0, slot, xslot, hb);
          gu_chunk(acc, 1, slot, xslot, hb);
        } else if (kind == K_KV) {
          if (hb == 0 && t == 0) sts_u4(stash + 5 * 8192, 0x3F803F80u, 0x3F803F80u, 0x3F803F80u, 0x3F803F80u);
          kv_stage(acc, 0, hb);
          kv_stage(acc, 1, hb);
          if (hb == 1) {
            float kvacc[36];
            const int par = (xoff & 1u) ^ 1u;
            fence_proxy_async();
            bar_sync(1 + w, 128);
            wgmma_fence();
            static_for<4>([&](auto kkc) INL {
              constexpr int kk = decltype(kkc)::value;
              wgmma_n72_ss_tt<kk != 0, desc_lo(3 * 8192 + kk * 2048, 0), desc_lo(4 * 8192 + kk * 2048, 8192 - kk * 2048)>(kvacc, dbase + w * 4096);
            });
            wgmma_commit();
            wgmma_wait<0>();
            float c[8];
#pragma unroll
            for (int i = 0; i < 8; i++)
              c[i] = wq == 0 ? kvacc[i] : (wq == 1 ? kvacc[8 + i] : (wq == 2 ? kvacc[16 + i] : kvacc[24 + i]));
            const int head = (2 * p + t) * 4 + wq;
            float* kvp = &g_kv[par][head][0][0];
            red_add_v2(kvp + g * 16 + 2 * tq, c[0], c[1]);
            red_add_v2(kvp + (g + 8) * 16 + 2 * tq, c[2], c[3]);
            red_add_v2(kvp + g * 16 + 8 + 2 * tq, c[4], c[5]);
            red_add_v2(kvp + (g + 8) * 16 + 8 + 2 * tq, c[6], c[7]);
            if (tq == 0) {
              red_add(&g_z[par][head][g], kvacc[32]);
              red_add(&g_z[par][head][g + 8], kvacc[34]);
            }
            signal(t);
          }
        } else {
          uint32_t aq[4][4];
#pragma unroll
          for (int c = 0; c < 4; c++) {
            const int a = c * 8;
            aq[c][0] = pack_bf16(phi_f(acc[a] * rs0), phi_f(acc[a + 1] * rs0));
            aq[c][1] = pack_bf16(phi_f(acc[a + 2] * rs1), phi_f(acc[a + 3] * rs1));
            aq[c][2] = pack_bf16(phi_f(acc[a + 4] * rs0), phi_f(acc[a + 5] * rs0));
            aq[c][3] = pack_bf16(phi_f(acc[a + 6] * rs1), phi_f(acc[a + 7] * rs1));
          }
          if (hb == 0) mbar_wait(BAR(B_KVREADY), 0);
          float nd[4][12];
          wgmma_fence();
          static_for<4>([&](auto cc) INL {
            constexpr int c = decltype(cc)::value;
            wgmma_n24_rs<desc_lo(5 * 8192 + (hb * 4 + c) * 768, 128)>(nd[c], aq[c][0], aq[c][1], aq[c][2], aq[c][3], dbase + w * 4096);
          });
          wgmma_commit();
          wgmma_wait<0>();
          if (hb == 1) bar_sync(1 + w, 128);
          const uint32_t tg = xoff & 1u;
#pragma unroll
          for (int c = 0; c < 4; c++) {
            const float i0 = __fdividef(1.f, nd[c][8] + 1e-6f), i1 = __fdividef(1.f, nd[c][10] + 1e-6f);
            aq[c][0] = tagged(pack_bf16(nd[c][0] * i0, nd[c][1] * i0), tg);
            aq[c][1] = tagged(pack_bf16(nd[c][2] * i1, nd[c][3] * i1), tg);
            aq[c][2] = tagged(pack_bf16(nd[c][4] * i0, nd[c][5] * i0), tg);
            aq[c][3] = tagged(pack_bf16(nd[c][6] * i1, nd[c][7] * i1), tg);
          }
#pragma unroll
          for (int c = 0; c < 4; c++) {
            stg_u4(xptr(4 + hb, c), aq[c][0], aq[c][1], aq[c][2], aq[c][3]);
            sts_u4(stash + (4 + hb) * 8192 + c * 2048, aq[c][0], aq[c][1], aq[c][2], aq[c][3]);
          }
        }
      });
      PROF(w, 1 + 2 * t);
    }
    PROF(w, 10);

    const int n_own = odd ? 3 : 6;
    auto load_a = [&](int kb) INL {
      if (kb < n_own) {
#pragma unroll
        for (int jj = 0; jj < 4; jj++) {
          const int i = (kb * 4 + jj) * 4;
          lds_u4(stash + kb * 8192 + jj * 2048, A[i], A[i + 1], A[i + 2], A[i + 3]);
        }
      } else {
        const int xs = odd ? kb - 3 : kb;
#pragma unroll
        for (int jj = 0; jj < 4; jj++) {
          const int i = (kb * 4 + jj) * 4;
          ldg_poll_u4(xptr(xs, jj), A[i], A[i + 1], A[i + 2], A[i + 3]);
        }
      }
    };
    auto fix_a = [&](int kb) INL {
      if (kb >= n_own) {
        const int xs = odd ? kb - 3 : kb;
        recv_group<4>(xptr(xs, 0), &A[kb * 16], xoff & 1u);
      }
    };
#pragma unroll
    for (int kb = 0; kb < 7; kb++) load_a(kb);
    PROF(w, 11);

    const uint32_t ooff = (uint32_t)(m * 128 + w * 64 + wq * 16 + (lane >> 3)) * kD + odd * 256 + p * 64 + (lane & 7) * 8;
    float acc2[2][32];
    uint32_t poff = (uint32_t)((m * 2 + odd) * 24 + w) * 8192u + (uint32_t)t128 * 16u;
    asm volatile("" : "+r"(poff));
    auto pptr = [&](int dest, int sl) INL { return (uint4*)((char*)g_pbuf + (poff + (uint32_t)(dest * 3 + sl) * 16384u)); };
    uint32_t P[3][16];
    uint4 xr[4];
    auto send = [&](float (&acc)[32], int bi) INL {
      uint4* dst = pptr((p + 1 + bi) & 3, bi);
#pragma unroll
      for (int q = 0; q < 4; q++)
        stg_u4(dst + q * 128, tagged(pack_bf16(acc[q * 8], acc[q * 8 + 1]), xoff & 1u), tagged(pack_bf16(acc[q * 8 + 2], acc[q * 8 + 3]), xoff & 1u),
               tagged(pack_bf16(acc[q * 8 + 4], acc[q * 8 + 5]), xoff & 1u), tagged(pack_bf16(acc[q * 8 + 6], acc[q * 8 + 7]), xoff & 1u));
      PROF(w, 12 + 2 * bi);
    };
    auto fetch = [&](int sl) INL {
#pragma unroll
      for (int q = 0; q < 4; q++) ldg_poll_u4(pptr(p, sl) + q * 128, P[sl][q * 4], P[sl][q * 4 + 1], P[sl][q * 4 + 2], P[sl][q * 4 + 3]);
    };
    static_for<36>([&](auto ic) INL {
      constexpr int i = decltype(ic)::value, bi = p2_bi(i), kb = p2_kb(i), j = i >> 1, st = j & 7;
      if (i == 9) { load_a(7); load_a(8); }
      if (i == 14) PROF(w, 2);
      if (bi == 0 && kb >= 3) fix_a(kb);
      if (i == 15) PROF(w, 4);
      if (i == 7) PROF(w, 6);
      if (i == 0 || i == 7 || i == 14 || i == 18 || i == 27) pp_wait();
      if ((i & 1) == 0) mbar_wait(BAR(B_FULL + st), (5 + (j >> 3)) & 1);
      wgmma_fence();
      static_for<4>([&](auto kkc) INL {
        constexpr int kk = decltype(kkc)::value, a = (kb * 4 + kk) * 4;
        wgmma_n64_rs<(kb | kk) != 0, desc_lo(stage_off(st) + (i & 1) * 8192 + kk * 2048, 0), kHi128>(acc2[bi & 1], A[a], A[a + 1], A[a + 2], A[a + 3]);
      });
      wgmma_commit();
      if (i == 4 || i == 11 || i == 15 || i == 24 || (i == 33 && w == 0)) pp_pass();
      if (i > 0) {
        wgmma_wait<1>();
        if ((i & 1) == 0 && j - 1 <= 9) release((j - 1) & 7);
      }
      if constexpr (i == 17) { send(acc2[0], 0); wgmma_wait<0>(); send(acc2[1], 1); }
      if constexpr (i == 26) {
        fetch(0);
        fetch(1);
        wgmma_wait<0>();
        send(acc2[0], 2);
        PROF(w, 13);
        recv_group<4>(pptr(p, 0), &P[0][0], xoff & 1u);
        recv_group<4>(pptr(p, 1), &P[1][0], xoff & 1u);
#pragma unroll
        for (int q = 0; q < 16; q++) {
          acc2[0][2 * q] = __uint_as_float(P[0][q] << 16) + __uint_as_float(P[1][q] << 16);
          acc2[0][2 * q + 1] = __uint_as_float(P[0][q] & 0xffff0000u) + __uint_as_float(P[1][q] & 0xffff0000u);
        }
        PROF(w, 15);
      }
      if constexpr (i == 28) {
#pragma unroll
        for (int q = 0; q < 4; q++) xr[q] = __ldg((const uint4*)(x + ooff + q * 4 * kD));
      }
      if constexpr (i == 31) fetch(2);
    });
    PROF(w, 17);
    recv_group<4>(pptr(p, 2), &P[2][0], xoff & 1u);
    wgmma_wait<0>();
    PROF(w, 18);
    {
      const uint32_t tile = area + wq * 4352;
#pragma unroll
      for (int q = 0; q < 8; q++) {
        float rr[4];
#pragma unroll
        for (int e = 0; e < 4; e++) rr[e] = acc2[1][q * 4 + e] + acc2[0][q * 4 + e];
        rr[0] += __uint_as_float(P[2][2 * q] << 16);
        rr[1] += __uint_as_float(P[2][2 * q] & 0xffff0000u);
        rr[2] += __uint_as_float(P[2][2 * q + 1] << 16);
        rr[3] += __uint_as_float(P[2][2 * q + 1] & 0xffff0000u);
        const uint32_t ad = tile + g * 272 + q * 32 + tq * 8;
        asm volatile("st.shared.v2.f32 [%0], {%1,%2};" ::"r"(ad), "f"(rr[0]), "f"(rr[1]) : "memory");
        asm volatile("st.shared.v2.f32 [%0], {%1,%2};" ::"r"(ad + 8 * 272), "f"(rr[2]), "f"(rr[3]) : "memory");
      }
      __syncwarp();
#pragma unroll
      for (int q = 0; q < 4; q++) {
        const uint32_t ad = tile + ((lane >> 3) + 4 * q) * 272 + (lane & 7) * 32;
        uint32_t v[8];
        lds_u4(ad, v[0], v[1], v[2], v[3]);
        lds_u4(ad + 16, v[4], v[5], v[6], v[7]);
        const uint32_t xv[4] = {xr[q].x, xr[q].y, xr[q].z, xr[q].w};
        uint32_t o[4];
#pragma unroll
        for (int e = 0; e < 4; e++)
          o[e] = pack_bf16(__uint_as_float(v[2 * e]) + __uint_as_float(xv[e] << 16), __uint_as_float(v[2 * e + 1]) + __uint_as_float(xv[e] & 0xffff0000u));
        stg_u4(out + ooff + q * 4 * kD, o[0], o[1], o[2], o[3]);
      }
    }
    PROF(w, 19);
    if (tid == 0) {
      const uint32_t old = atomicAdd(&g_done, 1u);
      if ((old & 127u) == 127u) st_relaxed(&g_epoch, ld_relaxed(&g_epoch) + 1u);
    }
  }
#undef BAR
}

typedef CUresult (*EncodeFn)(CUtensorMap*, CUtensorMapDataType, cuuint32_t, void*, const cuuint64_t*, const cuuint64_t*,
                             const cuuint32_t*, const cuuint32_t*, CUtensorMapInterleave, CUtensorMapSwizzle,
                             CUtensorMapL2promotion, CUtensorMapFloatOOBfill);

void make_map(EncodeFn enc, CUtensorMap* tm, const void* ptr, int rows, int cols, bool narrow) {
  cuuint64_t gd[2] = {(cuuint64_t)cols, (cuuint64_t)rows};
  cuuint64_t gs[1] = {(cuuint64_t)cols * 2};
  cuuint32_t bd[2] = {narrow ? 32u : 64u, narrow ? 128u : 64u};
  cuuint32_t es[2] = {1, 1};
  enc(tm, CU_TENSOR_MAP_DATA_TYPE_BFLOAT16, 2, const_cast<void*>(ptr), gd, gs, bd, es, CU_TENSOR_MAP_INTERLEAVE_NONE,
      narrow ? CU_TENSOR_MAP_SWIZZLE_64B : CU_TENSOR_MAP_SWIZZLE_128B, CU_TENSOR_MAP_L2_PROMOTION_L2_256B, CU_TENSOR_MAP_FLOAT_OOB_FILL_NONE);
}

}

extern "C" void kernel_launch(void* const* d_in, const int* in_sizes, int n_in, void* d_out, int out_size) {
  static EncodeFn enc = nullptr;
  if (!enc) {
    void* fn = nullptr;
    cudaDriverEntryPointQueryResult qr;
    cudaGetDriverEntryPoint("cuTensorMapEncodeTiled", &fn, cudaEnableDefault, &qr);
    enc = (EncodeFn)fn;
    cudaFuncSetAttribute(fused_kernel, cudaFuncAttributeMaxDynamicSharedMemorySize, kSmemBytes);
  }
  CUtensorMap tm_x, tm_wqkv, tm_w1, tm_w3, tm_w2, tm_wo;
  make_map(enc, &tm_x, d_in[0], kS, kD, false);
  make_map(enc, &tm_wqkv, d_in[1], kD, 3 * kD, true);
  make_map(enc, &tm_wo, d_in[2], kD, kD, false);
  make_map(enc, &tm_w1, d_in[4], kD, kF, true);
  make_map(enc, &tm_w3, d_in[5], kD, kF, true);
  make_map(enc, &tm_w2, d_in[6], kF, kD, false);
  fused_kernel<<<128, 384, kSmemBytes>>>(tm_x, tm_wqkv, tm_w1, tm_w3, tm_w2, tm_wo, (const __nv_bfloat16*)d_in[0],
                                         (__nv_bfloat16*)d_out);
}
```

```cpp
#include <cuda_runtime.h>
#include <cuda_bf16.h>
#include <cuda.h>
#include <stdint.h>

extern __shared__ __align__(1024) uint8_t smem_raw[];

namespace {

constexpr int kS = 2048, kD = 512, kF = 1792;
#define XPOS 1
#define XUP 16
constexpr uint32_t kSpinLimit = 1u << 22;

__device__ uint4    g_xbuf[16][4][9][2][4][128];
__device__ uint4    g_pbuf[16][2][4][3][2][4][128];
__device__ float    g_kv[2][32][16][16];
__device__ float    g_z[2][32][16];
__device__ uint32_t g_kvcnt[4][32];
__device__ uint32_t g_epoch;
__device__ uint32_t g_done;
#define PROF(wg, i) do {} while (0)
#define TWAIT(acc, stmt) do { stmt; } while (0)

__device__ __forceinline__ uint32_t smem_u32(const void* p) { return (uint32_t)__cvta_generic_to_shared(p); }
__device__ __forceinline__ void mbar_init(uint32_t bar, uint32_t cnt) {
  asm volatile("mbarrier.init.shared::cta.b64 [%0], %1;" ::"r"(bar), "r"(cnt) : "memory");
}
__device__ __forceinline__ void mbar_expect_tx(uint32_t bar, uint32_t bytes) {
  asm volatile("mbarrier.arrive.expect_tx.shared::cta.b64 _, [%0], %1;" ::"r"(bar), "r"(bytes) : "memory");
}
__device__ __forceinline__ void mbar_arrive(uint32_t bar) {
  asm volatile("mbarrier.arrive.shared::cta.b64 _, [%0];" ::"r"(bar) : "memory");
}
__device__ __forceinline__ void mbar_wait(uint32_t bar, uint32_t parity) {
  asm volatile(
      "{\n.reg .pred p;\n"
      "LAB_WAIT:\n"
      "mbarrier.try_wait.parity.shared::cta.b64 p, [%0], %1;\n"
      "@p bra DONE;\n"
      "bra LAB_WAIT;\n"
      "DONE:\n}" ::"r"(bar), "r"(parity) : "memory");
}
__device__ __forceinline__ void tma_load_2d(uint32_t dst, const CUtensorMap* tm, uint32_t bar, int c0, int c1) {
  asm volatile(
      "cp.async.bulk.tensor.2d.shared::cluster.global.mbarrier::complete_tx::bytes [%0], [%1, {%3, %4}], [%2];" ::"r"(dst),
      "l"(tm), "r"(bar), "r"(c0), "r"(c1)
      : "memory");
}
__device__ __forceinline__ void tma_load_2d_mc(uint32_t dst, const CUtensorMap* tm, uint32_t bar, int c0, int c1) {
  asm volatile(
      "cp.async.bulk.tensor.2d.shared::cluster.global.mbarrier::complete_tx::bytes.multicast::cluster [%0], [%1, {%3, %4}], [%2], %5;" ::"r"(dst),
      "l"(tm), "r"(bar), "r"(c0), "r"(c1), "h"((uint16_t)3)
      : "memory");
}
__device__ __forceinline__ void mbar_arrive_cluster(uint32_t bar, uint32_t cta) {
  asm volatile("{\n.reg .b32 ra;\nmapa.shared::cluster.u32 ra, %0, %1;\nmbarrier.arrive.shared::cluster.b64 _, [ra];\n}" ::"r"(bar), "r"(cta) : "memory");
}
__device__ __forceinline__ void prefetch_tmap(const CUtensorMap* tm) {
  asm volatile("prefetch.tensormap [%0];" ::"l"(tm) : "memory");
}
__device__ __forceinline__ void wgmma_fence() { asm volatile("wgmma.fence.sync.aligned;" ::: "memory"); }
__device__ __forceinline__ void wgmma_commit() { asm volatile("wgmma.commit_group.sync.aligned;" ::: "memory"); }
template <int N>
__device__ __forceinline__ void wgmma_wait() { asm volatile("wgmma.wait_group.sync.aligned %0;" ::"n"(N) : "memory"); }
__device__ __forceinline__ void bar_sync(int id, int n) { asm volatile("bar.sync %0, %1;" ::"r"(id), "r"(n) : "memory"); }
__device__ __forceinline__ void bar_arrive(int id, int n) { asm volatile("bar.arrive %0, %1;" ::"r"(id), "r"(n) : "memory"); }
__device__ __forceinline__ void fence_proxy_async() { asm volatile("fence.proxy.async.shared::cta;" ::: "memory"); }

__device__ __forceinline__ uint32_t ld_acquire(const uint32_t* p) {
  uint32_t v;
  asm volatile("ld.acquire.gpu.global.u32 %0, [%1];" : "=r"(v) : "l"(p) : "memory");
  return v;
}
__device__ __forceinline__ uint32_t ld_relaxed(const uint32_t* p) {
  uint32_t v;
  asm volatile("ld.relaxed.gpu.global.u32 %0, [%1];" : "=r"(v) : "l"(p));
  return v;
}
__device__ __forceinline__ void cluster_wait() { asm volatile("barrier.cluster.wait.aligned;" ::: "memory"); }
__device__ __forceinline__ void st_relaxed(uint32_t* p, uint32_t v) {
  asm volatile("st.relaxed.gpu.global.u32 [%0], %1;" ::"l"(p), "r"(v) : "memory");
}
__device__ __forceinline__ void wait_flag_eq(const uint32_t* p, uint32_t val) {
  uint32_t it = 0;
  while (ld_acquire(p) != val) {
    if (++it > kSpinLimit) break;
  }
}
__device__ __forceinline__ void wait_count_ge(const uint32_t* p, uint32_t val) {
  uint32_t it = 0;
  while ((int32_t)(ld_acquire(p) - val) < 0) {
    __nanosleep(64);
    if (++it > kSpinLimit) break;
  }
}
__device__ __forceinline__ void ldg_poll_u4(const void* p, uint32_t& a, uint32_t& b, uint32_t& c, uint32_t& d) {
  asm volatile("ld.relaxed.gpu.global.v4.u32 {%0,%1,%2,%3}, [%4];" : "=r"(a), "=r"(b), "=r"(c), "=r"(d) : "l"(p) : "memory");
}
template <int N>
__device__ __forceinline__ void recv_group(const uint4* p, uint32_t* r, uint32_t tag) {
  uint32_t it = 0;
  while (true) {
    uint32_t bad = 0u;
#pragma unroll
    for (int i = 0; i < 4 * N; i++) bad |= r[i] ^ tag;
    if (!__any_sync(0xffffffffu, (bad & 1u) != 0u) || ++it > kSpinLimit) break;
#pragma unroll
    for (int q = 0; q < N; q++) ldg_poll_u4(p + q * 128, r[q * 4], r[q * 4 + 1], r[q * 4 + 2], r[q * 4 + 3]);
  }
}
__device__ __forceinline__ uint32_t tagged(uint32_t v, uint32_t tag) { return (v & ~1u) | tag; }
__device__ __forceinline__ float4 ldg_cg_f4(const void* p) {
  float4 v;
  asm volatile("ld.global.cg.v4.f32 {%0,%1,%2,%3}, [%4];" : "=f"(v.x), "=f"(v.y), "=f"(v.z), "=f"(v.w) : "l"(p) : "memory");
  return v;
}
__device__ __forceinline__ void stg_u4(void* p, uint32_t a, uint32_t b, uint32_t c, uint32_t d) {
  asm volatile("st.global.v4.u32 [%0], {%1,%2,%3,%4};" ::"l"(p), "r"(a), "r"(b), "r"(c), "r"(d) : "memory");
}
__device__ __forceinline__ void stg_f4(void* p, float a, float b, float c, float d) {
  asm volatile("st.global.v4.f32 [%0], {%1,%2,%3,%4};" ::"l"(p), "f"(a), "f"(b), "f"(c), "f"(d) : "memory");
}
__device__ __forceinline__ void sts_u4(uint32_t addr, uint32_t a, uint32_t b, uint32_t c, uint32_t d) {
  asm volatile("st.shared.v4.u32 [%0], {%1,%2,%3,%4};" ::"r"(addr), "r"(a), "r"(b), "r"(c), "r"(d) : "memory");
}
__device__ __forceinline__ void lds_u4(uint32_t addr, uint32_t& a, uint32_t& b, uint32_t& c, uint32_t& d) {
  asm volatile("ld.shared.v4.u32 {%0,%1,%2,%3}, [%4];" : "=r"(a), "=r"(b), "=r"(c), "=r"(d) : "r"(addr) : "memory");
}
__device__ __forceinline__ uint32_t lds_u32(uint32_t addr) {
  uint32_t v;
  asm volatile("ld.shared.u32 %0, [%1];" : "=r"(v) : "r"(addr) : "memory");
  return v;
}
__device__ __forceinline__ void ldmatrix_x4(uint32_t addr, uint32_t& a, uint32_t& b, uint32_t& c, uint32_t& d) {
  asm volatile("ldmatrix.sync.aligned.m8n8.x4.shared.b16 {%0,%1,%2,%3}, [%4];" : "=r"(a), "=r"(b), "=r"(c), "=r"(d) : "r"(addr) : "memory");
}
__device__ __forceinline__ void ldmatrix_x4_trans(uint32_t addr, uint32_t& a, uint32_t& b, uint32_t& c, uint32_t& d) {
  asm volatile("ldmatrix.sync.aligned.m8n8.x4.trans.shared.b16 {%0,%1,%2,%3}, [%4];" : "=r"(a), "=r"(b), "=r"(c), "=r"(d) : "r"(addr) : "memory");
}
__device__ __forceinline__ void stmatrix_x4(uint32_t addr, uint32_t a, uint32_t b, uint32_t c, uint32_t d) {
  asm volatile("stmatrix.sync.aligned.m8n8.x4.shared.b16 [%0], {%1,%2,%3,%4};" ::"r"(addr), "r"(a), "r"(b), "r"(c), "r"(d) : "memory");
}
__device__ __forceinline__ void mma_16816(float (&c)[4], uint32_t a0, uint32_t a1, uint32_t a2, uint32_t a3, uint32_t b0, uint32_t b1) {
  asm(
      "mma.sync.aligned.m16n8k16.row.col.f32.bf16.bf16.f32 {%0,%1,%2,%3}, {%4,%5,%6,%7}, {%8,%9}, {%0,%1,%2,%3};"
      : "+f"(c[0]), "+f"(c[1]), "+f"(c[2]), "+f"(c[3])
      : "r"(a0), "r"(a1), "r"(a2), "r"(a3), "r"(b0), "r"(b1));
}
__device__ __forceinline__ uint32_t pack_bf16(float lo, float hi) {
  uint32_t r;
  asm("cvt.rn.bf16x2.f32 %0, %1, %2;" : "=r"(r) : "f"(hi), "f"(lo));
  return r;
}
__device__ __forceinline__ uint32_t hsub2_bf16(uint32_t a, uint32_t b) {
  uint32_t r;
  asm("sub.rn.bf16x2 %0, %1, %2;" : "=r"(r) : "r"(a), "r"(b));
  return r;
}
__device__ __forceinline__ float ex2f(float x) {
  float r;
  asm("ex2.approx.ftz.f32 %0, %1;" : "=f"(r) : "f"(x));
  return r;
}
__device__ __forceinline__ float rcpf(float x) {
  float r;
  asm("rcp.approx.ftz.f32 %0, %1;" : "=f"(r) : "f"(x));
  return r;
}
__device__ __forceinline__ void red_add_v2(float* p, float a, float b) {
  asm volatile("red.relaxed.gpu.global.add.v2.f32 [%0], {%1,%2};" ::"l"(p), "f"(a), "f"(b) : "memory");
}
__device__ __forceinline__ void red_add(float* p, float a) {
  asm volatile("red.relaxed.gpu.global.add.f32 [%0], %1;" ::"l"(p), "f"(a) : "memory");
}
__device__ __forceinline__ float phi_f(float t) {
  float e = ex2f(t * 1.4426950408889634f);
  return (t > 0.f ? t + 1.f : e) + 1e-6f;
}

#define R8(a, o) "+f"(a[o + 0]), "+f"(a[o + 1]), "+f"(a[o + 2]), "+f"(a[o + 3]), "+f"(a[o + 4]), "+f"(a[o + 5]), "+f"(a[o + 6]), "+f"(a[o + 7])

#define W8(a, o) "=f"(a[o + 0]), "=f"(a[o + 1]), "=f"(a[o + 2]), "=f"(a[o + 3]), "=f"(a[o + 4]), "=f"(a[o + 5]), "=f"(a[o + 6]), "=f"(a[o + 7])
#define D32 "{%0,%1,%2,%3,%4,%5,%6,%7,%8,%9,%10,%11,%12,%13,%14,%15,%16,%17,%18,%19,%20,%21,%22,%23,%24,%25,%26,%27,%28,%29,%30,%31}"
#define D36 "{%0,%1,%2,%3,%4,%5,%6,%7,%8,%9,%10,%11,%12,%13,%14,%15,%16,%17,%18,%19,%20,%21,%22,%23,%24,%25,%26,%27,%28,%29,%30,%31,%32,%33,%34,%35}"

constexpr uint32_t kHi128 = (1024u >> 4) | (1u << 30);
constexpr uint32_t kHi64 = (512u >> 4) | (2u << 30);
__host__ __device__ constexpr uint32_t desc_lo(uint32_t off, uint32_t lbo) { return (off >> 4) | ((lbo >> 4) << 16); }

template <bool ACC, uint32_t LO, uint32_t HI>
__device__ __forceinline__ void wgmma_n64_rs(float (&d)[32], uint32_t a0, uint32_t a1, uint32_t a2, uint32_t a3) {
  if (ACC) {
    asm volatile(
        "{\n.reg .pred p;\n.reg .b32 lo;\n.reg .b64 dd;\nsetp.eq.b32 p, 0, 0;\nmov.u32 lo, 64;\nadd.u32 lo, lo, %36;\nmov.b64 dd, {lo, %37};\n"
        "wgmma.mma_async.sync.aligned.m64n64k16.f32.bf16.bf16 " D32 ", {%32,%33,%34,%35}, dd, p, 1, 1, 1;\n}"
        : R8(d, 0), R8(d, 8), R8(d, 16), R8(d, 24)
        : "r"(a0), "r"(a1), "r"(a2), "r"(a3), "n"(LO), "n"(HI));
  } else {
    asm volatile(
        "{\n.reg .pred p;\n.reg .b32 lo;\n.reg .b64 dd;\nsetp.ne.b32 p, 0, 0;\nmov.u32 lo, 64;\nadd.u32 lo, lo, %36;\nmov.b64 dd, {lo, %37};\n"
        "wgmma.mma_async.sync.aligned.m64n64k16.f32.bf16.bf16 " D32 ", {%32,%33,%34,%35}, dd, p, 1, 1, 1;\n}"
        : W8(d, 0), W8(d, 8), W8(d, 16), W8(d, 24)
        : "r"(a0), "r"(a1), "r"(a2), "r"(a3), "n"(LO), "n"(HI));
  }
}
template <bool ACC, uint32_t LOA, uint32_t LOB>
__device__ __forceinline__ void wgmma_n72_ss_tt(float (&d)[36], uint32_t base) {
  if (ACC) {
    asm volatile(
        "{\n.reg .pred p;\n.reg .b32 lo;\n.reg .b64 da, db;\nsetp.eq.b32 p, 0, 0;\n"
        "add.u32 lo, %36, %37;\nmov.b64 da, {lo, %39};\nadd.u32 lo, %36, %38;\nmov.b64 db, {lo, %39};\n"
        "wgmma.mma_async.sync.aligned.m64n72k16.f32.bf16.bf16 " D36 ", da, db, p, 1, 1, 1, 1;\n}"
        : R8(d, 0), R8(d, 8), R8(d, 16), R8(d, 24), "+f"(d[32]), "+f"(d[33]), "+f"(d[34]), "+f"(d[35])
        : "r"(base), "n"(LOA), "n"(LOB), "n"(kHi128));
  } else {
    asm volatile(
        "{\n.reg .pred p;\n.reg .b32 lo;\n.reg .b64 da, db;\nsetp.ne.b32 p, 0, 0;\n"
        "add.u32 lo, %36, %37;\nmov.b64 da, {lo, %39};\nadd.u32 lo, %36, %38;\nmov.b64 db, {lo, %39};\n"
        "wgmma.mma_async.sync.aligned.m64n72k16.f32.bf16.bf16 " D36 ", da, db, p, 1, 1, 1, 1;\n}"
        : W8(d, 0), W8(d, 8), W8(d, 16), W8(d, 24), "=f"(d[32]), "=f"(d[33]), "=f"(d[34]), "=f"(d[35])
        : "r"(base), "n"(LOA), "n"(LOB), "n"(kHi128));
  }
}

#define INL __attribute__((always_inline))
template <uint32_t LO>
__device__ __forceinline__ void wgmma_n24_rs(float (&d)[12], uint32_t a0, uint32_t a1, uint32_t a2, uint32_t a3, uint32_t base) {
  asm volatile(
      "{\n.reg .pred p;\n.reg .b32 lo;\n.reg .b64 dd;\nsetp.ne.b32 p, 0, 0;\nadd.u32 lo, %16, %17;\nmov.b64 dd, {lo, %18};\n"
      "wgmma.mma_async.sync.aligned.m64n24k16.f32.bf16.bf16 {%0,%1,%2,%3,%4,%5,%6,%7,%8,%9,%10,%11}, {%12,%13,%14,%15}, dd, p, 1, 1, 1;\n}"
      : W8(d, 0), "=f"(d[8]), "=f"(d[9]), "=f"(d[10]), "=f"(d[11])
      : "r"(a0), "r"(a1), "r"(a2), "r"(a3), "r"(base), "n"(LO), "n"(256u >> 4));
}

template <int V> struct IC { static constexpr int value = V; };
template <int N, int I = 0, typename F>
__device__ __forceinline__ void static_for(F&& f) {
  if constexpr (I < N) { f(IC<I>{}); static_for<N, I + 1>(f); }
}

__host__ __device__ constexpr uint32_t stage_off(int st) {
  return st < 6 ? 131072u + (uint32_t)st * 16384u : (uint32_t)(st - 6) * 65536u + 49152u;
}

constexpr int B_FULL = 0, B_EMPTY = 8, B_XFULL = 16, B_XDONE = 32, B_KVREADY = 33, B_EV = 34, B_COUNT = 38;
constexpr uint32_t kBarOff = 229376;
constexpr int kSmemBytes = 229376 + 1024;

__host__ __device__ constexpr int p2_bi(int i) { return i < 7 ? 0 : i < 14 ? 1 : i < 16 ? 0 : i < 18 ? 1 : i / 9; }
__host__ __device__ constexpr int p2_kb(int i) { return i < 7 ? i : i < 14 ? i - 7 : i < 16 ? i - 7 : i < 18 ? i - 9 : i % 9; }

enum { K_NONE = 0, K_GU = 1, K_KV = 2, K_Q = 3 };

__global__ void __cluster_dims__(2, 1, 1) __launch_bounds__(384, 1)
fused_kernel(const __grid_constant__ CUtensorMap tm_x, const __grid_constant__ CUtensorMap tm_wqkv,
             const __grid_constant__ CUtensorMap tm_w1, const __grid_constant__ CUtensorMap tm_w3,
             const __grid_constant__ CUtensorMap tm_w2, const __grid_constant__ CUtensorMap tm_wo,
             const __nv_bfloat16* __restrict__ x, __nv_bfloat16* __restrict__ out) {
  const uint32_t sbase = smem_u32(smem_raw);
  const uint32_t bars = sbase + kBarOff;
  const int tid = threadIdx.x, lane = tid & 31;
  const int warp = __shfl_sync(0xffffffffu, tid >> 5, 0);
  const int cr = blockIdx.x & 1;
  const int r = (blockIdx.x >> 1) & 7, m = ((blockIdx.x >> 4) << 1) | cr, p = r >> 1, odd = r & 1;
#define BAR(i) (bars + 8u * (uint32_t)(i))
  if (tid == 256) {
    if ((sbase & 0x3FFFFu) != 1024u) __trap();
#pragma unroll
    for (int i = 0; i < 16; i++) mbar_init(BAR(B_XFULL + i), 1);
    fence_proxy_async();
#pragma unroll
    for (int b = 0; b < XUP; b++) {
      mbar_expect_tx(BAR(B_XFULL + b), 8192);
      tma_load_2d(sbase + (b >> 3) * 65536 + (b & 7) * 8192, &tm_x, BAR(B_XFULL + b), (b & 7) * 64, m * 128 + (b >> 3) * 64);
    }
#pragma unroll
    for (int i = 0; i < 8; i++) { mbar_init(BAR(B_FULL + i), 1); mbar_init(BAR(B_EMPTY + i), 4); }
#pragma unroll
    for (int i = 0; i < 4; i++) mbar_init(BAR(B_EV + i), 4);
    mbar_init(BAR(B_XDONE), 2);
    mbar_init(BAR(B_KVREADY), 3);
    asm volatile("fence.mbarrier_init.release.cluster;" ::: "memory");
    fence_proxy_async();
  } else if (tid == 288) {
    prefetch_tmap(odd ? &tm_wqkv : (cr ? &tm_w3 : &tm_w1));
  }
  __syncwarp();
  asm volatile("barrier.cluster.arrive.relaxed.aligned;" ::: "memory");
  PROF((tid >> 7), 21);
  __syncthreads();

  if (warp >= 8) {
    asm volatile("setmaxnreg.dec.sync.aligned.u32 24;");
    PROF(2, 3);
    cluster_wait();
    PROF(2, 2);
    const uint32_t epoch = warp == 8 ? 0u : ld_relaxed(&g_epoch);
    const uint32_t tag = epoch + 1u;
    const int par = epoch & 1;
    if (warp == 8) {
      if (lane == 0) {
        int twp = 0;
        for (int j = 0; j < 10; j++) {
          const CUtensorMap* tm;
          int col;
          if (!odd) {
            if (j < 8) { tm = cr ? &tm_w3 : &tm_w1; col = 7 * p * 64 + j * 32; }
            else { tm = &tm_wqkv; col = 128 * p + (j - 8) * 64 + cr * 32; }
          } else {
            if (j < 4) { tm = &tm_wqkv; col = 512 + cr * 512 + 128 * p + j * 32; }
            else { tm = cr ? &tm_w3 : &tm_w1; col = (7 * p + 4) * 64 + (j - 4) * 32; }
          }
          const int t = j >> 1;
          for (int kq = 0; kq < 4; kq++) {
            if (j == 0 && kq == XPOS) {
              for (int b = XUP; b < 16; b++) {
                mbar_expect_tx(BAR(B_XFULL + b), 8192);
                tma_load_2d(sbase + 65536 + (b & 7) * 8192, &tm_x, BAR(B_XFULL + b), (b & 7) * 64, m * 128 + 64);
              }
            }
            const int k = (j & 1) * 4 + kq;
            TWAIT(twp, mbar_wait(BAR(B_EMPTY + k), k < 6 ? ((t & 1) ^ 1) : (t & 1)));
            mbar_expect_tx(BAR(B_FULL + k), 16384);
            tma_load_2d_mc(sbase + stage_off(k) + cr * 8192, tm, BAR(B_FULL + k), col, kq * 128);
          }
        }
        for (int j = 0; j < 18; j++) {
          const int st = j & 7, n = 5 + (j >> 3);
          const int i = 2 * j + cr;
          const int bi = p2_bi(i), kb = p2_kb(i);
          const int col = odd * 256 + ((p + 1 + bi) & 3) * 64;
          const CUtensorMap* tmk;
          int row;
          if (!odd) {
            if (kb < 4) { tmk = &tm_w2; row = (7 * p + kb) * 64; }
            else if (kb < 6) { tmk = &tm_wo; row = (2 * p + kb - 4) * 64; }
            else { tmk = &tm_w2; row = (7 * p + 4 + kb - 6) * 64; }
          } else {
            if (kb < 3) { tmk = &tm_w2; row = (7 * p + 4 + kb) * 64; }
            else if (kb < 7) { tmk = &tm_w2; row = (7 * p + kb - 3) * 64; }
            else { tmk = &tm_wo; row = (2 * p + kb - 7) * 64; }
          }
          mbar_wait(BAR(B_EMPTY + st), st < 6 ? ((n & 1) ^ 1) : (n & 1));
          mbar_expect_tx(BAR(B_FULL + st), 16384);
          tma_load_2d_mc(sbase + stage_off(st) + cr * 8192, tmk, BAR(B_FULL + st), col, row);
        }
      }
    } else if (odd) {
      if (lane == 0 && warp <= 10) {
        const int w = warp - 9;
        for (int e = 0; e < 2; e++) {
          mbar_wait(BAR(B_EV + w * 2 + e), 0);
          __threadfence();
          atomicAdd(&g_kvcnt[p][0], 1u);
        }
      }
    } else {
      const int hl = tid - 288;
      {
        const int ce = m * 4 + p;
        if (hl < 32) *(float4*)(&g_kv[par ^ 1][0][0][0] + ce * 128 + hl * 4) = make_float4(0.f, 0.f, 0.f, 0.f);
        else if (hl < 40) (&g_z[par ^ 1][0][0])[ce * 8 + hl - 32] = 0.f;
      }
      mbar_wait(BAR(B_XDONE), 0);
      wait_count_ge(&g_kvcnt[p][0], 64u * tag);
      const float* kvp = &g_kv[par][8 * p][0][0];
      const float* zp = &g_z[par][8 * p][0];
      const uint32_t dst0 = sbase + 5 * 8192, dst1 = dst0 + 65536;
#pragma unroll
      for (int h2 = 0; h2 < 2; h2++) {
        float4 v[3];
#pragma unroll
        for (int i = 0; i < 3; i++) {
          const int c = (h2 * 3 + i) * 96 + hl;
          v[i] = c < 512 ? ldg_cg_f4(kvp + c * 4) : (c < 544 ? ldg_cg_f4(zp + (c - 512) * 4) : make_float4(0.f, 0.f, 0.f, 0.f));
        }
#pragma unroll
        for (int i = 0; i < 3; i++) {
          const int c = (h2 * 3 + i) * 96 + hl;
          if (c < 512) {
            const int h = c >> 6, d = (c >> 2) & 15, e = (c & 3) * 4;
            const uint32_t off = h * 768 + ((e >> 3) * 2 + (d >> 3)) * 128 + (d & 7) * 16 + (e & 7) * 2;
            const uint32_t lo = pack_bf16(v[i].x, v[i].y), hi = pack_bf16(v[i].z, v[i].w);
            asm volatile("st.shared.v2.u32 [%0], {%1,%2};" ::"r"(dst0 + off), "r"(lo), "r"(hi) : "memory");
            asm volatile("st.shared.v2.u32 [%0], {%1,%2};" ::"r"(dst1 + off), "r"(lo), "r"(hi) : "memory");
          } else if (c < 544) {
            const int h = (c - 512) >> 2, d = ((c - 512) & 3) * 4;
            const uint32_t off = h * 768 + (4 + (d >> 3)) * 128 + (d & 7) * 16;
            const float zz[4] = {v[i].x, v[i].y, v[i].z, v[i].w};
#pragma unroll
            for (int q = 0; q < 4; q++) {
              const uint32_t zq = pack_bf16(zz[q], zz[q]);
              sts_u4(dst0 + off + q * 16, zq, zq, zq, zq);
              sts_u4(dst1 + off + q * 16, zq, zq, zq, zq);
            }
          }
        }
      }
      fence_proxy_async();
      __syncwarp();
      if (lane == 0) mbar_arrive(BAR(B_KVREADY));
    }
  } else {
    asm volatile("setmaxnreg.inc.sync.aligned.u32 240;");
    const int w = warp >> 2, wq = warp & 3, t128 = tid & 127;
    const int g = lane >> 2, tq = lane & 3;
    const uint32_t area = sbase + (uint32_t)w * 65536u;
    const bool elect = (t128 == 0);
    PROF(w, 22);
    const uint32_t dbase = (sbase & 0x3FFFFu) >> 4;
    uint32_t xoff = (uint32_t)((m * 4 + p) * 18 + w) * 8192u + (uint32_t)t128 * 16u;
    uint32_t stash = area + (uint32_t)t128 * 16u;
    const uint32_t epoch_c = ld_relaxed(&g_epoch);
    auto xptr = [&](int slot, int jj) INL { return (uint4*)((char*)g_xbuf + ((xoff & ~1u) + (uint32_t)slot * 16384u + (uint32_t)jj * 2048u)); };
    uint32_t A[144];
    float rs0, rs1;
    auto release = [&](int st) INL {
      if (elect) { mbar_arrive_cluster(BAR(B_EMPTY + st), 0); mbar_arrive_cluster(BAR(B_EMPTY + st), 1); }
    };

    {
      const int row = wq * 16 + (lane & 7) + ((lane >> 3) & 1) * 8;
      const uint32_t rbase = area + row * 128;
      float s0[2][4] = {}, q0[2][4] = {}, q1[2][4] = {};
      const uint32_t ones = 0x3F803F80u;
#pragma unroll
      for (int b = 0; b < 8; b++) {
        mbar_wait(BAR(B_XFULL + w * 8 + b), 0);
        if (b == 0) PROF(w, 23);
        if (b == 7) PROF(w, 24);
#pragma unroll
        for (int kk = 0; kk < 4; kk++) {
          const int i = (b * 4 + kk) * 4;
          ldmatrix_x4(rbase + b * 8192 + (((kk * 2 + (lane >> 4)) ^ (row & 7)) << 4), A[i], A[i + 1], A[i + 2], A[i + 3]);
        }
#pragma unroll
        for (int kk = 0; kk < 4; kk++) {
          const int i = (b * 4 + kk) * 4;
          mma_16816(s0[kk & 1], A[i], A[i + 1], A[i + 2], A[i + 3], ones, ones);
          mma_16816(q0[kk & 1], A[i], A[i + 1], A[i + 2], A[i + 3], A[i], A[i + 2]);
          mma_16816(q1[kk & 1], A[i], A[i + 1], A[i + 2], A[i + 3], A[i + 1], A[i + 3]);
        }
      }
      const float mean0 = (s0[0][0] + s0[1][0]) * (1.f / 512.f), mean1 = (s0[0][2] + s0[1][2]) * (1.f / 512.f);
      const uint32_t m0 = pack_bf16(mean0, mean0), m1 = pack_bf16(mean1, mean1);
#pragma unroll
      for (int i = 0; i < 128; i += 2) {
        A[i] = hsub2_bf16(A[i], m0);
        A[i + 1] = hsub2_bf16(A[i + 1], m1);
      }
      float v0 = (g & 1) ? q0[0][1] + q0[1][1] : q0[0][0] + q0[1][0];
      float v1 = (g & 1) ? q1[0][3] + q1[1][3] : q1[0][2] + q1[1][2];
      const int src = 4 * g + (g >> 1);
      v0 = __shfl_sync(0xffffffffu, v0, src);
      v1 = __shfl_sync(0xffffffffu, v1, src);
      v0 = fmaxf(v0 * (1.f / 512.f) - mean0 * mean0, 0.f);
      v1 = fmaxf(v1 * (1.f / 512.f) - mean1 * mean1, 0.f);
      rs0 = rsqrtf(v0 + 1e-5f);
      rs1 = rsqrtf(v1 + 1e-5f);
      bar_sync(1 + w, 128);
      cluster_wait();
      asm volatile("" : "+r"(xoff), "+r"(stash));
      PROF(w, 0);
      release(6); release(7);
      if (elect) mbar_arrive(BAR(B_XDONE));
    }

    auto gu_chunk = [&](float (&acc)[32], int f, int slot, int xslot, int hb) INL {
      const float c0 = rs0 * -1.4426950408889634f, c1 = rs1 * -1.4426950408889634f;
      const float q0 = rs0 * rs0, q1 = rs1 * rs1;
      uint32_t h[4];
#pragma unroll
      for (int i = 0; i < 4; i++) {
        const float ga = acc[f * 8 + 2 * i], gb = acc[f * 8 + 2 * i + 1];
        const float ua = acc[16 + f * 8 + 2 * i], ub = acc[16 + f * 8 + 2 * i + 1];
        const float c = (i & 1) ? c1 : c0, q = (i & 1) ? q1 : q0;
        const float da = 1.f + ex2f(fminf(ga * c, 60.f)), db = 1.f + ex2f(fminf(gb * c, 60.f));
        const float rq = rcpf(da * db) * q;
        h[i] = tagged(pack_bf16(ga * ua * (db * rq), gb * ub * (da * rq)), xoff & 1u);
      }
      const int jj = hb * 2 + f;
      sts_u4(stash + slot * 8192 + jj * 2048, h[0], h[1], h[2], h[3]);
      stg_u4(xptr(xslot, jj), h[0], h[1], h[2], h[3]);
    };
    auto kv_stage = [&](float (&acc)[32], int c, int hb) INL {
      const int srow = wq * 16 + (lane & 7) + ((lane >> 3) & 1) * 8;
      const uint32_t base = area + (3 + c) * 8192 + srow * 128;
#pragma unroll
      for (int jj = 0; jj < 2; jj++) {
        const int a = c * 16 + jj * 8;
        uint32_t r0, r1, r2, r3;
        if (c == 0) {
          r0 = pack_bf16(phi_f(acc[a] * rs0), phi_f(acc[a + 1] * rs0));
          r1 = pack_bf16(phi_f(acc[a + 2] * rs1), phi_f(acc[a + 3] * rs1));
          r2 = pack_bf16(phi_f(acc[a + 4] * rs0), phi_f(acc[a + 5] * rs0));
          r3 = pack_bf16(phi_f(acc[a + 6] * rs1), phi_f(acc[a + 7] * rs1));
        } else {
          r0 = pack_bf16(acc[a] * rs0, acc[a + 1] * rs0);
          r1 = pack_bf16(acc[a + 2] * rs1, acc[a + 3] * rs1);
          r2 = pack_bf16(acc[a + 4] * rs0, acc[a + 5] * rs0);
          r3 = pack_bf16(acc[a + 6] * rs1, acc[a + 7] * rs1);
        }
        stmatrix_x4(base + (((hb * 4 + jj * 2 + (lane >> 4)) ^ (srow & 7)) << 4), r0, r1, r2, r3);
      }
    };
    auto signal = [&](int e) INL {
      __syncwarp();
      if (lane == 0) mbar_arrive(BAR(B_EV + w * 2 + e));
    };

    auto pp_wait = [&]() INL { bar_sync(3 + w, 256); };
    auto pp_pass = [&]() INL { bar_arrive(3 + (w ^ 1), 256); };
    if (w == 1) pp_pass();
    int tw1 = 0, tw2 = 0, tw3 = 0;
#pragma unroll 1
    for (int t = 0; t < 5; t++) {
      const uint32_t ph = t & 1;
      const int kind = odd ? (t < 2 ? K_KV : K_GU) : (t < 4 ? K_GU : K_Q);
      const int slot = odd ? t - 2 : t, xslot = odd ? t + 4 : t;
      static_for<2>([&](auto hc) INL {
        constexpr int hb = decltype(hc)::value;
        float acc[32];
        TWAIT(tw2, pp_wait());
        static_for<4>([&](auto kc) INL {
          constexpr int kq = decltype(kc)::value, k = hb * 4 + kq;
          TWAIT(tw1, mbar_wait(BAR(B_FULL + k), ph));
          wgmma_fence();
          static_for<8>([&](auto kkc) INL {
            constexpr int kk = decltype(kkc)::value, i = (kq * 8 + kk) * 4;
            wgmma_n64_rs<(kq | kk) != 0, desc_lo(stage_off(k) + kk * 1024, 8192), kHi64>(acc, A[i], A[i + 1], A[i + 2], A[i + 3]);
          });
          wgmma_commit();
          if (kq == 2) pp_pass();
          if (kq > 0) {
            wgmma_wait<1>();
            release(k - 1);
          }
        });
        TWAIT(tw3, wgmma_wait<0>());
        release(hb * 4 + 3);
        if (hb == 0 && t == 0) xoff |= (epoch_c & 1u) ^ 1u;
        if (kind == K_GU) {
          gu_chunk(acc, 0, slot, xslot, hb);
          gu_chunk(acc, 1, slot, xslot, hb);
        } else if (kind == K_KV) {
          if (hb == 0 && t == 0) sts_u4(stash + 5 * 8192, 0x3F803F80u, 0x3F803F80u, 0x3F803F80u, 0x3F803F80u);
          kv_stage(acc, 0, hb);
          kv_stage(acc, 1, hb);
          if (hb == 1) {
            float kvacc[36];
            const int par = (xoff & 1u) ^ 1u;
            fence_proxy_async();
            bar_sync(1 + w, 128);
            wgmma_fence();
            static_for<4>([&](auto kkc) INL {
              constexpr int kk = decltype(kkc)::value;
              wgmma_n72_ss_tt<kk != 0, desc_lo(3 * 8192 + kk * 2048, 0), desc_lo(4 * 8192 + kk * 2048, 8192 - kk * 2048)>(kvacc, dbase + w * 4096);
            });
            wgmma_commit();
            wgmma_wait<0>();
            float c[8];
#pragma unroll
            for (int i = 0; i < 8; i++)
              c[i] = wq == 0 ? kvacc[i] : (wq == 1 ? kvacc[8 + i] : (wq == 2 ? kvacc[16 + i] : kvacc[24 + i]));
            const int head = (2 * p + t) * 4 + wq;
            float* kvp = &g_kv[par][head][0][0];
            red_add_v2(kvp + g * 16 + 2 * tq, c[0], c[1]);
            red_add_v2(kvp + (g + 8) * 16 + 2 * tq, c[2], c[3]);
            red_add_v2(kvp + g * 16 + 8 + 2 * tq, c[4], c[5]);
            red_add_v2(kvp + (g + 8) * 16 + 8 + 2 * tq, c[6], c[7]);
            if (tq == 0) {
              red_add(&g_z[par][head][g], kvacc[32]);
              red_add(&g_z[par][head][g + 8], kvacc[34]);
            }
            signal(t);
          }
        } else {
          uint32_t aq[4][4];
#pragma unroll
          for (int c = 0; c < 4; c++) {
            const int a = c * 8;
            aq[c][0] = pack_bf16(phi_f(acc[a] * rs0), phi_f(acc[a + 1] * rs0));
            aq[c][1] = pack_bf16(phi_f(acc[a + 2] * rs1), phi_f(acc[a + 3] * rs1));
            aq[c][2] = pack_bf16(phi_f(acc[a + 4] * rs0), phi_f(acc[a + 5] * rs0));
            aq[c][3] = pack_bf16(phi_f(acc[a + 6] * rs1), phi_f(acc[a + 7] * rs1));
          }
          if (hb == 0) mbar_wait(BAR(B_KVREADY), 0);
          float nd[4][12];
          wgmma_fence();
          static_for<4>([&](auto cc) INL {
            constexpr int c = decltype(cc)::value;
            wgmma_n24_rs<desc_lo(5 * 8192 + (hb * 4 + c) * 768, 128)>(nd[c], aq[c][0], aq[c][1], aq[c][2], aq[c][3], dbase + w * 4096);
          });
          wgmma_commit();
          wgmma_wait<0>();
          if (hb == 1) bar_sync(1 + w, 128);
          const uint32_t tg = xoff & 1u;
#pragma unroll
          for (int c = 0; c < 4; c++) {
            const float i0 = __fdividef(1.f, nd[c][8] + 1e-6f), i1 = __fdividef(1.f, nd[c][10] + 1e-6f);
            aq[c][0] = tagged(pack_bf16(nd[c][0] * i0, nd[c][1] * i0), tg);
            aq[c][1] = tagged(pack_bf16(nd[c][2] * i1, nd[c][3] * i1), tg);
            aq[c][2] = tagged(pack_bf16(nd[c][4] * i0, nd[c][5] * i0), tg);
            aq[c][3] = tagged(pack_bf16(nd[c][6] * i1, nd[c][7] * i1), tg);
          }
#pragma unroll
          for (int c = 0; c < 4; c++) {
            stg_u4(xptr(4 + hb, c), aq[c][0], aq[c][1], aq[c][2], aq[c][3]);
            sts_u4(stash + (4 + hb) * 8192 + c * 2048, aq[c][0], aq[c][1], aq[c][2], aq[c][3]);
          }
        }
      });
      PROF(w, 1 + 2 * t);
    }
    PROF(w, 10);

    const int n_own = odd ? 3 : 6;
    auto load_a = [&](int kb) INL {
      if (kb < n_own) {
#pragma unroll
        for (int jj = 0; jj < 4; jj++) {
          const int i = (kb * 4 + jj) * 4;
          lds_u4(stash + kb * 8192 + jj * 2048, A[i], A[i + 1], A[i + 2], A[i + 3]);
        }
      } else {
        const int xs = odd ? kb - 3 : kb;
#pragma unroll
        for (int jj = 0; jj < 4; jj++) {
          const int i = (kb * 4 + jj) * 4;
          ldg_poll_u4(xptr(xs, jj), A[i], A[i + 1], A[i + 2], A[i + 3]);
        }
      }
    };
    auto fix_a = [&](int kb) INL {
      if (kb >= n_own) {
        const int xs = odd ? kb - 3 : kb;
        recv_group<4>(xptr(xs, 0), &A[kb * 16], xoff & 1u);
      }
    };
#pragma unroll
    for (int kb = 0; kb < 7; kb++) load_a(kb);
    PROF(w, 11);

    const uint32_t ooff = (uint32_t)(m * 128 + w * 64 + wq * 16 + (lane >> 3)) * kD + odd * 256 + p * 64 + (lane & 7) * 8;
    float acc2[2][32];
    uint32_t poff = (uint32_t)((m * 2 + odd) * 24 + w) * 8192u + (uint32_t)t128 * 16u;
    asm volatile("" : "+r"(poff));
    auto pptr = [&](int dest, int sl) INL { return (uint4*)((char*)g_pbuf + (poff + (uint32_t)(dest * 3 + sl) * 16384u)); };
    uint32_t P[3][16];
    uint4 xr[4];
    auto send = [&](float (&acc)[32], int bi) INL {
      uint4* dst = pptr((p + 1 + bi) & 3, bi);
#pragma unroll
      for (int q = 0; q < 4; q++)
        stg_u4(dst + q * 128, tagged(pack_bf16(acc[q * 8], acc[q * 8 + 1]), xoff & 1u), tagged(pack_bf16(acc[q * 8 + 2], acc[q * 8 + 3]), xoff & 1u),
               tagged(pack_bf16(acc[q * 8 + 4], acc[q * 8 + 5]), xoff & 1u), tagged(pack_bf16(acc[q * 8 + 6], acc[q * 8 + 7]), xoff & 1u));
      PROF(w, 12 + 2 * bi);
    };
    auto fetch = [&](int sl) INL {
#pragma unroll
      for (int q = 0; q < 4; q++)
        asm volatile("cp.async.cg.shared.global [%0], [%1], 16;" ::"r"(stash + (3 + sl) * 8192 + q * 2048), "l"(pptr(p, sl) + q * 128) : "memory");
    };
    auto collect = [&](int sl) INL {
      asm volatile("cp.async.wait_all;" ::: "memory");
#pragma unroll
      for (int q = 0; q < 4; q++) lds_u4(stash + (3 + sl) * 8192 + q * 2048, P[sl][q * 4], P[sl][q * 4 + 1], P[sl][q * 4 + 2], P[sl][q * 4 + 3]);
      recv_group<4>(pptr(p, sl), &P[sl][0], xoff & 1u);
    };
    static_for<36>([&](auto ic) INL {
      constexpr int i = decltype(ic)::value, bi = p2_bi(i), kb = p2_kb(i), j = i >> 1, st = j & 7;
      if (i == 9) { load_a(7); load_a(8); }
      if (i == 14) PROF(w, 2);
      if (bi == 0 && kb >= 3) fix_a(kb);
      if (i == 15) PROF(w, 4);
      if (i == 7) PROF(w, 6);
      if (i == 0 || i == 7 || i == 14 || i == 18 || i == 27) pp_wait();
      if ((i & 1) == 0) mbar_wait(BAR(B_FULL + st), (5 + (j >> 3)) & 1);
      wgmma_fence();
      static_for<4>([&](auto kkc) INL {
        constexpr int kk = decltype(kkc)::value, a = (kb * 4 + kk) * 4;
        wgmma_n64_rs<(kb | kk) != 0, desc_lo(stage_off(st) + (i & 1) * 8192 + kk * 2048, 0), kHi128>(acc2[bi & 1], A[a], A[a + 1], A[a + 2], A[a + 3]);
      });
      wgmma_commit();
      if (i == 4 || i == 11 || i == 15 || i == 24 || (i == 33 && w == 0)) pp_pass();
      if (i > 0) {
        wgmma_wait<1>();
        if ((i & 1) == 0 && j - 1 <= 9) release((j - 1) & 7);
      }
      if constexpr (i == 17) { send(acc2[0], 0); wgmma_wait<0>(); send(acc2[1], 1); }
      if constexpr (i == 26) {
        wgmma_wait<0>();
        send(acc2[0], 2);
        PROF(w, 13);
        collect(0);
        collect(1);
#pragma unroll
        for (int q = 0; q < 16; q++) {
          acc2[0][2 * q] = __uint_as_float(P[0][q] << 16) + __uint_as_float(P[1][q] << 16);
          acc2[0][2 * q + 1] = __uint_as_float(P[0][q] & 0xffff0000u) + __uint_as_float(P[1][q] & 0xffff0000u);
        }
        PROF(w, 15);
      }
      if constexpr (i == 28) {
#pragma unroll
        for (int q = 0; q < 4; q++) xr[q] = __ldg((const uint4*)(x + ooff + q * 4 * kD));
      }
      if constexpr (i == 21) { fetch(0); fetch(1); }
      if constexpr (i == 31) fetch(2);
    });
    PROF(w, 17);
    collect(2);
    wgmma_wait<0>();
    PROF(w, 18);
    {
      const uint32_t tile = area + wq * 4352;
#pragma unroll
      for (int q = 0; q < 8; q++) {
        float rr[4];
#pragma unroll
        for (int e = 0; e < 4; e++) rr[e] = acc2[1][q * 4 + e] + acc2[0][q * 4 + e];
        rr[0] += __uint_as_float(P[2][2 * q] << 16);
        rr[1] += __uint_as_float(P[2][2 * q] & 0xffff0000u);
        rr[2] += __uint_as_float(P[2][2 * q + 1] << 16);
        rr[3] += __uint_as_float(P[2][2 * q + 1] & 0xffff0000u);
        const uint32_t ad = tile + g * 272 + q * 32 + tq * 8;
        asm volatile("st.shared.v2.f32 [%0], {%1,%2};" ::"r"(ad), "f"(rr[0]), "f"(rr[1]) : "memory");
        asm volatile("st.shared.v2.f32 [%0], {%1,%2};" ::"r"(ad + 8 * 272), "f"(rr[2]), "f"(rr[3]) : "memory");
      }
      __syncwarp();
#pragma unroll
      for (int q = 0; q < 4; q++) {
        const uint32_t ad = tile + ((lane >> 3) + 4 * q) * 272 + (lane & 7) * 32;
        uint32_t v[8];
        lds_u4(ad, v[0], v[1], v[2], v[3]);
        lds_u4(ad + 16, v[4], v[5], v[6], v[7]);
        const uint32_t xv[4] = {xr[q].x, xr[q].y, xr[q].z, xr[q].w};
        uint32_t o[4];
#pragma unroll
        for (int e = 0; e < 4; e++)
          o[e] = pack_bf16(__uint_as_float(v[2 * e]) + __uint_as_float(xv[e] << 16), __uint_as_float(v[2 * e + 1]) + __uint_as_float(xv[e] & 0xffff0000u));
        stg_u4(out + ooff + q * 4 * kD, o[0], o[1], o[2], o[3]);
      }
    }
    PROF(w, 19);
    if (tid == 0) {
      const uint32_t old = atomicAdd(&g_done, 1u);
      if ((old & 127u) == 127u) st_relaxed(&g_epoch, ld_relaxed(&g_epoch) + 1u);
    }
  }
#undef BAR
}

typedef CUresult (*EncodeFn)(CUtensorMap*, CUtensorMapDataType, cuuint32_t, void*, const cuuint64_t*, const cuuint64_t*,
                             const cuuint32_t*, const cuuint32_t*, CUtensorMapInterleave, CUtensorMapSwizzle,
                             CUtensorMapL2promotion, CUtensorMapFloatOOBfill);

void make_map(EncodeFn enc, CUtensorMap* tm, const void* ptr, int rows, int cols, bool narrow) {
  cuuint64_t gd[2] = {(cuuint64_t)cols, (cuuint64_t)rows};
  cuuint64_t gs[1] = {(cuuint64_t)cols * 2};
  cuuint32_t bd[2] = {narrow ? 32u : 64u, narrow ? 128u : 64u};
  cuuint32_t es[2] = {1, 1};
  enc(tm, CU_TENSOR_MAP_DATA_TYPE_BFLOAT16, 2, const_cast<void*>(ptr), gd, gs, bd, es, CU_TENSOR_MAP_INTERLEAVE_NONE,
      narrow ? CU_TENSOR_MAP_SWIZZLE_64B : CU_TENSOR_MAP_SWIZZLE_128B, CU_TENSOR_MAP_L2_PROMOTION_L2_256B, CU_TENSOR_MAP_FLOAT_OOB_FILL_NONE);
}

}

extern "C" void kernel_launch(void* const* d_in, const int* in_sizes, int n_in, void* d_out, int out_size) {
  static EncodeFn enc = nullptr;
  if (!enc) {
    void* fn = nullptr;
    cudaDriverEntryPointQueryResult qr;
    cudaGetDriverEntryPoint("cuTensorMapEncodeTiled", &fn, cudaEnableDefault, &qr);
    enc = (EncodeFn)fn;
    cudaFuncSetAttribute(fused_kernel, cudaFuncAttributeMaxDynamicSharedMemorySize, kSmemBytes);
  }
  CUtensorMap tm_x, tm_wqkv, tm_w1, tm_w3, tm_w2, tm_wo;
  make_map(enc, &tm_x, d_in[0], kS, kD, false);
  make_map(enc, &tm_wqkv, d_in[1], kD, 3 * kD, true);
  make_map(enc, &tm_wo, d_in[2], kD, kD, false);
  make_map(enc, &tm_w1, d_in[4], kD, kF, true);
  make_map(enc, &tm_w3, d_in[5], kD, kF, true);
  make_map(enc, &tm_w2, d_in[6], kF, kD, false);
  fused_kernel<<<128, 384, kSmemBytes>>>(tm_x, tm_wqkv, tm_w1, tm_w3, tm_w2, tm_wo, (const __nv_bfloat16*)d_in[0],
                                         (__nv_bfloat16*)d_out);
}
```

```cpp
#include <cuda_runtime.h>
#include <cuda_bf16.h>
#include <cuda.h>
#include <stdint.h>

extern __shared__ __align__(1024) uint8_t smem_raw[];

namespace {

constexpr int kS = 2048, kD = 512, kF = 1792;
#define XPOS 1
#define FPOS 32
#define XUP 16
constexpr uint32_t kSpinLimit = 1u << 22;

__device__ uint4    g_xbuf[16][4][9][2][4][128];
__device__ uint4    g_pbuf[16][2][4][3][2][4][128];
__device__ float    g_kv[2][32][16][16];
__device__ float    g_z[2][32][16];
__device__ uint32_t g_kvcnt[4][32];
__device__ uint32_t g_epoch;
__device__ uint32_t g_done;
#define PROF(wg, i) do {} while (0)
#define TWAIT(acc, stmt) do { stmt; } while (0)

__device__ __forceinline__ uint32_t smem_u32(const void* p) { return (uint32_t)__cvta_generic_to_shared(p); }
__device__ __forceinline__ void mbar_init(uint32_t bar, uint32_t cnt) {
  asm volatile("mbarrier.init.shared::cta.b64 [%0], %1;" ::"r"(bar), "r"(cnt) : "memory");
}
__device__ __forceinline__ void mbar_expect_tx(uint32_t bar, uint32_t bytes) {
  asm volatile("mbarrier.arrive.expect_tx.shared::cta.b64 _, [%0], %1;" ::"r"(bar), "r"(bytes) : "memory");
}
__device__ __forceinline__ void mbar_arrive(uint32_t bar) {
  asm volatile("mbarrier.arrive.shared::cta.b64 _, [%0];" ::"r"(bar) : "memory");
}
__device__ __forceinline__ void mbar_wait(uint32_t bar, uint32_t parity) {
  asm volatile(
      "{\n.reg .pred p;\n"
      "LAB_WAIT:\n"
      "mbarrier.try_wait.parity.shared::cta.b64 p, [%0], %1;\n"
      "@p bra DONE;\n"
      "bra LAB_WAIT;\n"
      "DONE:\n}" ::"r"(bar), "r"(parity) : "memory");
}
__device__ __forceinline__ void tma_load_2d(uint32_t dst, const CUtensorMap* tm, uint32_t bar, int c0, int c1) {
  asm volatile(
      "cp.async.bulk.tensor.2d.shared::cluster.global.mbarrier::complete_tx::bytes [%0], [%1, {%3, %4}], [%2];" ::"r"(dst),
      "l"(tm), "r"(bar), "r"(c0), "r"(c1)
      : "memory");
}
__device__ __forceinline__ void tma_load_2d_mc(uint32_t dst, const CUtensorMap* tm, uint32_t bar, int c0, int c1) {
  asm volatile(
      "cp.async.bulk.tensor.2d.shared::cluster.global.mbarrier::complete_tx::bytes.multicast::cluster [%0], [%1, {%3, %4}], [%2], %5;" ::"r"(dst),
      "l"(tm), "r"(bar), "r"(c0), "r"(c1), "h"((uint16_t)3)
      : "memory");
}
__device__ __forceinline__ void mbar_arrive_cluster(uint32_t bar, uint32_t cta) {
  asm volatile("{\n.reg .b32 ra;\nmapa.shared::cluster.u32 ra, %0, %1;\nmbarrier.arrive.shared::cluster.b64 _, [ra];\n}" ::"r"(bar), "r"(cta) : "memory");
}
__device__ __forceinline__ void prefetch_tmap(const CUtensorMap* tm) {
  asm volatile("prefetch.tensormap [%0];" ::"l"(tm) : "memory");
}
__device__ __forceinline__ void wgmma_fence() { asm volatile("wgmma.fence.sync.aligned;" ::: "memory"); }
__device__ __forceinline__ void wgmma_commit() { asm volatile("wgmma.commit_group.sync.aligned;" ::: "memory"); }
template <int N>
__device__ __forceinline__ void wgmma_wait() { asm volatile("wgmma.wait_group.sync.aligned %0;" ::"n"(N) : "memory"); }
__device__ __forceinline__ void bar_sync(int id, int n) { asm volatile("bar.sync %0, %1;" ::"r"(id), "r"(n) : "memory"); }
__device__ __forceinline__ void bar_arrive(int id, int n) { asm volatile("bar.arrive %0, %1;" ::"r"(id), "r"(n) : "memory"); }
__device__ __forceinline__ void fence_proxy_async() { asm volatile("fence.proxy.async.shared::cta;" ::: "memory"); }

__device__ __forceinline__ uint32_t ld_acquire(const uint32_t* p) {
  uint32_t v;
  asm volatile("ld.acquire.gpu.global.u32 %0, [%1];" : "=r"(v) : "l"(p) : "memory");
  return v;
}
__device__ __forceinline__ uint32_t ld_relaxed(const uint32_t* p) {
  uint32_t v;
  asm volatile("ld.relaxed.gpu.global.u32 %0, [%1];" : "=r"(v) : "l"(p));
  return v;
}
__device__ __forceinline__ void cluster_wait() { asm volatile("barrier.cluster.wait.aligned;" ::: "memory"); }
__device__ __forceinline__ void st_relaxed(uint32_t* p, uint32_t v) {
  asm volatile("st.relaxed.gpu.global.u32 [%0], %1;" ::"l"(p), "r"(v) : "memory");
}
__device__ __forceinline__ void wait_flag_eq(const uint32_t* p, uint32_t val) {
  uint32_t it = 0;
  while (ld_acquire(p) != val) {
    if (++it > kSpinLimit) break;
  }
}
__device__ __forceinline__ void wait_count_ge(const uint32_t* p, uint32_t val) {
  uint32_t it = 0;
  while ((int32_t)(ld_acquire(p) - val) < 0) {
    __nanosleep(64);
    if (++it > kSpinLimit) break;
  }
}
__device__ __forceinline__ void ldg_poll_u4(const void* p, uint32_t& a, uint32_t& b, uint32_t& c, uint32_t& d) {
  asm volatile("ld.relaxed.gpu.global.v4.u32 {%0,%1,%2,%3}, [%4];" : "=r"(a), "=r"(b), "=r"(c), "=r"(d) : "l"(p) : "memory");
}
template <int N>
__device__ __forceinline__ void recv_group(const uint4* p, uint32_t* r, uint32_t tag) {
  uint32_t it = 0;
  while (true) {
    uint32_t bad = 0u;
#pragma unroll
    for (int i = 0; i < 4 * N; i++) bad |= r[i] ^ tag;
    if (!__any_sync(0xffffffffu, (bad & 1u) != 0u) || ++it > kSpinLimit) break;
#pragma unroll
    for (int q = 0; q < N; q++) ldg_poll_u4(p + q * 128, r[q * 4], r[q * 4 + 1], r[q * 4 + 2], r[q * 4 + 3]);
  }
}
__device__ __forceinline__ uint32_t tagged(uint32_t v, uint32_t tag) { return (v & ~1u) | tag; }
__device__ __forceinline__ float4 ldg_cg_f4(const void* p) {
  float4 v;
  asm volatile("ld.global.cg.v4.f32 {%0,%1,%2,%3}, [%4];" : "=f"(v.x), "=f"(v.y), "=f"(v.z), "=f"(v.w) : "l"(p) : "memory");
  return v;
}
__device__ __forceinline__ void stg_u4(void* p, uint32_t a, uint32_t b, uint32_t c, uint32_t d) {
  asm volatile("st.global.v4.u32 [%0], {%1,%2,%3,%4};" ::"l"(p), "r"(a), "r"(b), "r"(c), "r"(d) : "memory");
}
__device__ __forceinline__ void stg_f4(void* p, float a, float b, float c, float d) {
  asm volatile("st.global.v4.f32 [%0], {%1,%2,%3,%4};" ::"l"(p), "f"(a), "f"(b), "f"(c), "f"(d) : "memory");
}
__device__ __forceinline__ void sts_u4(uint32_t addr, uint32_t a, uint32_t b, uint32_t c, uint32_t d) {
  asm volatile("st.shared.v4.u32 [%0], {%1,%2,%3,%4};" ::"r"(addr), "r"(a), "r"(b), "r"(c), "r"(d) : "memory");
}
__device__ __forceinline__ void lds_u4(uint32_t addr, uint32_t& a, uint32_t& b, uint32_t& c, uint32_t& d) {
  asm volatile("ld.shared.v4.u32 {%0,%1,%2,%3}, [%4];" : "=r"(a), "=r"(b), "=r"(c), "=r"(d) : "r"(addr) : "memory");
}
__device__ __forceinline__ uint32_t lds_u32(uint32_t addr) {
  uint32_t v;
  asm volatile("ld.shared.u32 %0, [%1];" : "=r"(v) : "r"(addr) : "memory");
  return v;
}
__device__ __forceinline__ void ldmatrix_x4(uint32_t addr, uint32_t& a, uint32_t& b, uint32_t& c, uint32_t& d) {
  asm volatile("ldmatrix.sync.aligned.m8n8.x4.shared.b16 {%0,%1,%2,%3}, [%4];" : "=r"(a), "=r"(b), "=r"(c), "=r"(d) : "r"(addr) : "memory");
}
__device__ __forceinline__ void ldmatrix_x4_trans(uint32_t addr, uint32_t& a, uint32_t& b, uint32_t& c, uint32_t& d) {
  asm volatile("ldmatrix.sync.aligned.m8n8.x4.trans.shared.b16 {%0,%1,%2,%3}, [%4];" : "=r"(a), "=r"(b), "=r"(c), "=r"(d) : "r"(addr) : "memory");
}
__device__ __forceinline__ void stmatrix_x4(uint32_t addr, uint32_t a, uint32_t b, uint32_t c, uint32_t d) {
  asm volatile("stmatrix.sync.aligned.m8n8.x4.shared.b16 [%0], {%1,%2,%3,%4};" ::"r"(addr), "r"(a), "r"(b), "r"(c), "r"(d) : "memory");
}
__device__ __forceinline__ void mma_16816(float (&c)[4], uint32_t a0, uint32_t a1, uint32_t a2, uint32_t a3, uint32_t b0, uint32_t b1) {
  asm(
      "mma.sync.aligned.m16n8k16.row.col.f32.bf16.bf16.f32 {%0,%1,%2,%3}, {%4,%5,%6,%7}, {%8,%9}, {%0,%1,%2,%3};"
      : "+f"(c[0]), "+f"(c[1]), "+f"(c[2]), "+f"(c[3])
      : "r"(a0), "r"(a1), "r"(a2), "r"(a3), "r"(b0), "r"(b1));
}
__device__ __forceinline__ uint32_t pack_bf16(float lo, float hi) {
  uint32_t r;
  asm("cvt.rn.bf16x2.f32 %0, %1, %2;" : "=r"(r) : "f"(hi), "f"(lo));
  return r;
}
__device__ __forceinline__ uint32_t hsub2_bf16(uint32_t a, uint32_t b) {
  uint32_t r;
  asm("sub.rn.bf16x2 %0, %1, %2;" : "=r"(r) : "r"(a), "r"(b));
  return r;
}
__device__ __forceinline__ float ex2f(float x) {
  float r;
  asm("ex2.approx.ftz.f32 %0, %1;" : "=f"(r) : "f"(x));
  return r;
}
__device__ __forceinline__ float rcpf(float x) {
  float r;
  asm("rcp.approx.ftz.f32 %0, %1;" : "=f"(r) : "f"(x));
  return r;
}
__device__ __forceinline__ void red_add_v2(float* p, float a, float b) {
  asm volatile("red.relaxed.gpu.global.add.v2.f32 [%0], {%1,%2};" ::"l"(p), "f"(a), "f"(b) : "memory");
}
__device__ __forceinline__ void red_add(float* p, float a) {
  asm volatile("red.relaxed.gpu.global.add.f32 [%0], %1;" ::"l"(p), "f"(a) : "memory");
}
__device__ __forceinline__ float phi_f(float t) {
  float e = ex2f(t * 1.4426950408889634f);
  return (t > 0.f ? t + 1.f : e) + 1e-6f;
}

#define R8(a, o) "+f"(a[o + 0]), "+f"(a[o + 1]), "+f"(a[o + 2]), "+f"(a[o + 3]), "+f"(a[o + 4]), "+f"(a[o + 5]), "+f"(a[o + 6]), "+f"(a[o + 7])

#define W8(a, o) "=f"(a[o + 0]), "=f"(a[o + 1]), "=f"(a[o + 2]), "=f"(a[o + 3]), "=f"(a[o + 4]), "=f"(a[o + 5]), "=f"(a[o + 6]), "=f"(a[o + 7])
#define D32 "{%0,%1,%2,%3,%4,%5,%6,%7,%8,%9,%10,%11,%12,%13,%14,%15,%16,%17,%18,%19,%20,%21,%22,%23,%24,%25,%26,%27,%28,%29,%30,%31}"
#define D36 "{%0,%1,%2,%3,%4,%5,%6,%7,%8,%9,%10,%11,%12,%13,%14,%15,%16,%17,%18,%19,%20,%21,%22,%23,%24,%25,%26,%27,%28,%29,%30,%31,%32,%33,%34,%35}"

constexpr uint32_t kHi128 = (1024u >> 4) | (1u << 30);
constexpr uint32_t kHi64 = (512u >> 4) | (2u << 30);
__host__ __device__ constexpr uint32_t desc_lo(uint32_t off, uint32_t lbo) { return (off >> 4) | ((lbo >> 4) << 16); }

template <bool ACC, uint32_t LO, uint32_t HI>
__device__ __forceinline__ void wgmma_n64_rs(float (&d)[32], uint32_t a0, uint32_t a1, uint32_t a2, uint32_t a3) {
  if (ACC) {
    asm volatile(
        "{\n.reg .pred p;\n.reg .b32 lo;\n.reg .b64 dd;\nsetp.eq.b32 p, 0, 0;\nmov.u32 lo, 64;\nadd.u32 lo, lo, %36;\nmov.b64 dd, {lo, %37};\n"
        "wgmma.mma_async.sync.aligned.m64n64k16.f32.bf16.bf16 " D32 ", {%32,%33,%34,%35}, dd, p, 1, 1, 1;\n}"
        : R8(d, 0), R8(d, 8), R8(d, 16), R8(d, 24)
        : "r"(a0), "r"(a1), "r"(a2), "r"(a3), "n"(LO), "n"(HI));
  } else {
    asm volatile(
        "{\n.reg .pred p;\n.reg .b32 lo;\n.reg .b64 dd;\nsetp.ne.b32 p, 0, 0;\nmov.u32 lo, 64;\nadd.u32 lo, lo, %36;\nmov.b64 dd, {lo, %37};\n"
        "wgmma.mma_async.sync.aligned.m64n64k16.f32.bf16.bf16 " D32 ", {%32,%33,%34,%35}, dd, p, 1, 1, 1;\n}"
        : W8(d, 0), W8(d, 8), W8(d, 16), W8(d, 24)
        : "r"(a0), "r"(a1), "r"(a2), "r"(a3), "n"(LO), "n"(HI));
  }
}
template <bool ACC, uint32_t LOA, uint32_t LOB>
__device__ __forceinline__ void wgmma_n72_ss_tt(float (&d)[36], uint32_t base) {
  if (ACC) {
    asm volatile(
        "{\n.reg .pred p;\n.reg .b32 lo;\n.reg .b64 da, db;\nsetp.eq.b32 p, 0, 0;\n"
        "add.u32 lo, %36, %37;\nmov.b64 da, {lo, %39};\nadd.u32 lo, %36, %38;\nmov.b64 db, {lo, %39};\n"
        "wgmma.mma_async.sync.aligned.m64n72k16.f32.bf16.bf16 " D36 ", da, db, p, 1, 1, 1, 1;\n}"
        : R8(d, 0), R8(d, 8), R8(d, 16), R8(d, 24), "+f"(d[32]), "+f"(d[33]), "+f"(d[34]), "+f"(d[35])
        : "r"(base), "n"(LOA), "n"(LOB), "n"(kHi128));
  } else {
    asm volatile(
        "{\n.reg .pred p;\n.reg .b32 lo;\n.reg .b64 da, db;\nsetp.ne.b32 p, 0, 0;\n"
        "add.u32 lo, %36, %37;\nmov.b64 da, {lo, %39};\nadd.u32 lo, %36, %38;\nmov.b64 db, {lo, %39};\n"
        "wgmma.mma_async.sync.aligned.m64n72k16.f32.bf16.bf16 " D36 ", da, db, p, 1, 1, 1, 1;\n}"
        : W8(d, 0), W8(d, 8), W8(d, 16), W8(d, 24), "=f"(d[32]), "=f"(d[33]), "=f"(d[34]), "=f"(d[35])
        : "r"(base), "n"(LOA), "n"(LOB), "n"(kHi128));
  }
}

#define INL __attribute__((always_inline))
template <uint32_t LO>
__device__ __forceinline__ void wgmma_n24_rs(float (&d)[12], uint32_t a0, uint32_t a1, uint32_t a2, uint32_t a3, uint32_t base) {
  asm volatile(
      "{\n.reg .pred p;\n.reg .b32 lo;\n.reg .b64 dd;\nsetp.ne.b32 p, 0, 0;\nadd.u32 lo, %16, %17;\nmov.b64 dd, {lo, %18};\n"
      "wgmma.mma_async.sync.aligned.m64n24k16.f32.bf16.bf16 {%0,%1,%2,%3,%4,%5,%6,%7,%8,%9,%10,%11}, {%12,%13,%14,%15}, dd, p, 1, 1, 1;\n}"
      : W8(d, 0), "=f"(d[8]), "=f"(d[9]), "=f"(d[10]), "=f"(d[11])
      : "r"(a0), "r"(a1), "r"(a2), "r"(a3), "r"(base), "n"(LO), "n"(256u >> 4));
}

template <int V> struct IC { static constexpr int value = V; };
template <int N, int I = 0, typename F>
__device__ __forceinline__ void static_for(F&& f) {
  if constexpr (I < N) { f(IC<I>{}); static_for<N, I + 1>(f); }
}

__host__ __device__ constexpr uint32_t stage_off(int st) {
  return st < 6 ? 131072u + (uint32_t)st * 16384u : (uint32_t)(st - 6) * 65536u + 49152u;
}

constexpr int B_FULL = 0, B_EMPTY = 8, B_XFULL = 16, B_XDONE = 32, B_KVREADY = 33, B_EV = 34, B_COUNT = 38;
constexpr uint32_t kBarOff = 229376;
constexpr int kSmemBytes = 229376 + 1024;

__host__ __device__ constexpr int p2_bi(int i) { return i < 7 ? 0 : i < 14 ? 1 : i < 16 ? 0 : i < 18 ? 1 : i / 9; }
__host__ __device__ constexpr int p2_kb(int i) { return i < 7 ? i : i < 14 ? i - 7 : i < 16 ? i - 7 : i < 18 ? i - 9 : i % 9; }

enum { K_NONE = 0, K_GU = 1, K_KV = 2, K_Q = 3 };

__global__ void __cluster_dims__(2, 1, 1) __launch_bounds__(384, 1)
fused_kernel(const __grid_constant__ CUtensorMap tm_x, const __grid_constant__ CUtensorMap tm_wqkv,
             const __grid_constant__ CUtensorMap tm_w1, const __grid_constant__ CUtensorMap tm_w3,
             const __grid_constant__ CUtensorMap tm_w2, const __grid_constant__ CUtensorMap tm_wo,
             const __nv_bfloat16* __restrict__ x, __nv_bfloat16* __restrict__ out) {
  const uint32_t sbase = smem_u32(smem_raw);
  const uint32_t bars = sbase + kBarOff;
  const int tid = threadIdx.x, lane = tid & 31;
  const int warp = __shfl_sync(0xffffffffu, tid >> 5, 0);
  const int cr = blockIdx.x & 1;
  const int r = (blockIdx.x >> 1) & 7, m = ((blockIdx.x >> 4) << 1) | cr, p = r >> 1, odd = r & 1;
#define BAR(i) (bars + 8u * (uint32_t)(i))
  if (tid == 256) {
    if ((sbase & 0x3FFFFu) != 1024u) __trap();
#pragma unroll
    for (int i = 0; i < 16; i++) mbar_init(BAR(B_XFULL + i), 1);
    fence_proxy_async();
#pragma unroll
    for (int b = 0; b < XUP; b++) {
      mbar_expect_tx(BAR(B_XFULL + b), 8192);
      tma_load_2d(sbase + (b >> 3) * 65536 + (b & 7) * 8192, &tm_x, BAR(B_XFULL + b), (b & 7) * 64, m * 128 + (b >> 3) * 64);
    }
#pragma unroll
    for (int i = 0; i < 8; i++) { mbar_init(BAR(B_FULL + i), 1); mbar_init(BAR(B_EMPTY + i), 4); }
#pragma unroll
    for (int i = 0; i < 4; i++) mbar_init(BAR(B_EV + i), 4);
    mbar_init(BAR(B_XDONE), 2);
    mbar_init(BAR(B_KVREADY), 3);
    asm volatile("fence.mbarrier_init.release.cluster;" ::: "memory");
    fence_proxy_async();
  } else if (tid == 288) {
    prefetch_tmap(odd ? &tm_wqkv : (cr ? &tm_w3 : &tm_w1));
  }
  __syncwarp();
  asm volatile("barrier.cluster.arrive.relaxed.aligned;" ::: "memory");
  PROF((tid >> 7), 21);
  __syncthreads();

  if (warp >= 8) {
    asm volatile("setmaxnreg.dec.sync.aligned.u32 24;");
    PROF(2, 3);
    cluster_wait();
    PROF(2, 2);
    const uint32_t epoch = warp == 8 ? 0u : ld_relaxed(&g_epoch);
    const uint32_t tag = epoch + 1u;
    const int par = epoch & 1;
    if (warp == 8) {
      if (lane == 0) {
        int twp = 0;
        for (int j = 0; j < 10; j++) {
          const CUtensorMap* tm;
          int col;
          if (!odd) {
            if (j < 8) { tm = cr ? &tm_w3 : &tm_w1; col = 7 * p * 64 + j * 32; }
            else { tm = &tm_wqkv; col = 128 * p + (j - 8) * 64 + cr * 32; }
          } else {
            if (j < 4) { tm = &tm_wqkv; col = 512 + cr * 512 + 128 * p + j * 32; }
            else { tm = cr ? &tm_w3 : &tm_w1; col = (7 * p + 4) * 64 + (j - 4) * 32; }
          }
          const int t = j >> 1;
          for (int kq = 0; kq < 4; kq++) {
            if (j == 0 && kq == XPOS) {
              for (int b = XUP; b < 16; b++) {
                mbar_expect_tx(BAR(B_XFULL + b), 8192);
                tma_load_2d(sbase + 65536 + (b & 7) * 8192, &tm_x, BAR(B_XFULL + b), (b & 7) * 64, m * 128 + 64);
              }
            }
            const int k = (j & 1) * 4 + kq;
            TWAIT(twp, mbar_wait(BAR(B_EMPTY + k), k < 6 ? ((t & 1) ^ 1) : (t & 1)));
            mbar_expect_tx(BAR(B_FULL + k), 16384);
            tma_load_2d_mc(sbase + stage_off(k) + cr * 8192, tm, BAR(B_FULL + k), col, kq * 128);
          }
        }
        for (int j = 0; j < 18; j++) {
          const int st = j & 7, n = 5 + (j >> 3);
          const int i = 2 * j + cr;
          const int bi = p2_bi(i), kb = p2_kb(i);
          const int col = odd * 256 + ((p + 1 + bi) & 3) * 64;
          const CUtensorMap* tmk;
          int row;
          if (!odd) {
            if (kb < 4) { tmk = &tm_w2; row = (7 * p + kb) * 64; }
            else if (kb < 6) { tmk = &tm_wo; row = (2 * p + kb - 4) * 64; }
            else { tmk = &tm_w2; row = (7 * p + 4 + kb - 6) * 64; }
          } else {
            if (kb < 3) { tmk = &tm_w2; row = (7 * p + 4 + kb) * 64; }
            else if (kb < 7) { tmk = &tm_w2; row = (7 * p + kb - 3) * 64; }
            else { tmk = &tm_wo; row = (2 * p + kb - 7) * 64; }
          }
          mbar_wait(BAR(B_EMPTY + st), st < 6 ? ((n & 1) ^ 1) : (n & 1));
          mbar_expect_tx(BAR(B_FULL + st), 16384);
          tma_load_2d_mc(sbase + stage_off(st) + cr * 8192, tmk, BAR(B_FULL + st), col, row);
        }
      }
    } else if (odd) {
      if (lane == 0 && warp <= 10) {
        const int w = warp - 9;
        for (int e = 0; e < 2; e++) {
          mbar_wait(BAR(B_EV + w * 2 + e), 0);
          __threadfence();
          atomicAdd(&g_kvcnt[p][0], 1u);
        }
      }
    } else {
      const int hl = tid - 288;
      {
        const int ce = m * 4 + p;
        if (hl < 32) *(float4*)(&g_kv[par ^ 1][0][0][0] + ce * 128 + hl * 4) = make_float4(0.f, 0.f, 0.f, 0.f);
        else if (hl < 40) (&g_z[par ^ 1][0][0])[ce * 8 + hl - 32] = 0.f;
      }
      mbar_wait(BAR(B_XDONE), 0);
      wait_count_ge(&g_kvcnt[p][0], 64u * tag);
      const float* kvp = &g_kv[par][8 * p][0][0];
      const float* zp = &g_z[par][8 * p][0];
      const uint32_t dst0 = sbase + 5 * 8192, dst1 = dst0 + 65536;
#pragma unroll
      for (int h2 = 0; h2 < 2; h2++) {
        float4 v[3];
#pragma unroll
        for (int i = 0; i < 3; i++) {
          const int c = (h2 * 3 + i) * 96 + hl;
          v[i] = c < 512 ? ldg_cg_f4(kvp + c * 4) : (c < 544 ? ldg_cg_f4(zp + (c - 512) * 4) : make_float4(0.f, 0.f, 0.f, 0.f));
        }
#pragma unroll
        for (int i = 0; i < 3; i++) {
          const int c = (h2 * 3 + i) * 96 + hl;
          if (c < 512) {
            const int h = c >> 6, d = (c >> 2) & 15, e = (c & 3) * 4;
            const uint32_t off = h * 768 + ((e >> 3) * 2 + (d >> 3)) * 128 + (d & 7) * 16 + (e & 7) * 2;
            const uint32_t lo = pack_bf16(v[i].x, v[i].y), hi = pack_bf16(v[i].z, v[i].w);
            asm volatile("st.shared.v2.u32 [%0], {%1,%2};" ::"r"(dst0 + off), "r"(lo), "r"(hi) : "memory");
            asm volatile("st.shared.v2.u32 [%0], {%1,%2};" ::"r"(dst1 + off), "r"(lo), "r"(hi) : "memory");
          } else if (c < 544) {
            const int h = (c - 512) >> 2, d = ((c - 512) & 3) * 4;
            const uint32_t off = h * 768 + (4 + (d >> 3)) * 128 + (d & 7) * 16;
            const float zz[4] = {v[i].x, v[i].y, v[i].z, v[i].w};
#pragma unroll
            for (int q = 0; q < 4; q++) {
              const uint32_t zq = pack_bf16(zz[q], zz[q]);
              sts_u4(dst0 + off + q * 16, zq, zq, zq, zq);
              sts_u4(dst1 + off + q * 16, zq, zq, zq, zq);
            }
          }
        }
      }
      fence_proxy_async();
      __syncwarp();
      if (lane == 0) mbar_arrive(BAR(B_KVREADY));
    }
  } else {
    asm volatile("setmaxnreg.inc.sync.aligned.u32 240;");
    const int w = warp >> 2, wq = warp & 3, t128 = tid & 127;
    const int g = lane >> 2, tq = lane & 3;
    const uint32_t area = sbase + (uint32_t)w * 65536u;
    const bool elect = (t128 == 0);
    PROF(w, 22);
    const uint32_t dbase = (sbase & 0x3FFFFu) >> 4;
    uint32_t xoff = (uint32_t)((m * 4 + p) * 18 + w) * 8192u + (uint32_t)t128 * 16u;
    uint32_t stash = area + (uint32_t)t128 * 16u;
    const uint32_t epoch_c = ld_relaxed(&g_epoch);
    auto xptr = [&](int slot, int jj) INL { return (uint4*)((char*)g_xbuf + ((xoff & ~1u) + (uint32_t)slot * 16384u + (uint32_t)jj * 2048u)); };
    uint32_t A[144];
    float rs0, rs1;
    auto release = [&](int st) INL {
      if (elect) { mbar_arrive_cluster(BAR(B_EMPTY + st), 0); mbar_arrive_cluster(BAR(B_EMPTY + st), 1); }
    };

    {
      const int row = wq * 16 + (lane & 7) + ((lane >> 3) & 1) * 8;
      const uint32_t rbase = area + row * 128;
      float s0[2][4] = {}, q0[2][4] = {}, q1[2][4] = {};
      const uint32_t ones = 0x3F803F80u;
#pragma unroll
      for (int b = 0; b < 8; b++) {
        mbar_wait(BAR(B_XFULL + w * 8 + b), 0);
        if (b == 0) PROF(w, 23);
        if (b == 7) PROF(w, 24);
#pragma unroll
        for (int kk = 0; kk < 4; kk++) {
          const int i = (b * 4 + kk) * 4;
          ldmatrix_x4(rbase + b * 8192 + (((kk * 2 + (lane >> 4)) ^ (row & 7)) << 4), A[i], A[i + 1], A[i + 2], A[i + 3]);
        }
#pragma unroll
        for (int kk = 0; kk < 4; kk++) {
          const int i = (b * 4 + kk) * 4;
          mma_16816(s0[kk & 1], A[i], A[i + 1], A[i + 2], A[i + 3], ones, ones);
          mma_16816(q0[kk & 1], A[i], A[i + 1], A[i + 2], A[i + 3], A[i], A[i + 2]);
          mma_16816(q1[kk & 1], A[i], A[i + 1], A[i + 2], A[i + 3], A[i + 1], A[i + 3]);
        }
      }
      const float mean0 = (s0[0][0] + s0[1][0]) * (1.f / 512.f), mean1 = (s0[0][2] + s0[1][2]) * (1.f / 512.f);
      const uint32_t m0 = pack_bf16(mean0, mean0), m1 = pack_bf16(mean1, mean1);
#pragma unroll
      for (int i = 0; i < 128; i += 2) {
        A[i] = hsub2_bf16(A[i], m0);
        A[i + 1] = hsub2_bf16(A[i + 1], m1);
      }
      float v0 = (g & 1) ? q0[0][1] + q0[1][1] : q0[0][0] + q0[1][0];
      float v1 = (g & 1) ? q1[0][3] + q1[1][3] : q1[0][2] + q1[1][2];
      const int src = 4 * g + (g >> 1);
      v0 = __shfl_sync(0xffffffffu, v0, src);
      v1 = __shfl_sync(0xffffffffu, v1, src);
      v0 = fmaxf(v0 * (1.f / 512.f) - mean0 * mean0, 0.f);
      v1 = fmaxf(v1 * (1.f / 512.f) - mean1 * mean1, 0.f);
      rs0 = rsqrtf(v0 + 1e-5f);
      rs1 = rsqrtf(v1 + 1e-5f);
      bar_sync(1 + w, 128);
      cluster_wait();
      asm volatile("" : "+r"(xoff), "+r"(stash));
      PROF(w, 0);
      release(6); release(7);
      if (elect) mbar_arrive(BAR(B_XDONE));
    }

    auto gu_chunk = [&](float (&acc)[32], int f, int slot, int xslot, int hb) INL {
      const float c0 = rs0 * -1.4426950408889634f, c1 = rs1 * -1.4426950408889634f;
      const float q0 = rs0 * rs0, q1 = rs1 * rs1;
      uint32_t h[4];
#pragma unroll
      for (int i = 0; i < 4; i++) {
        const float ga = acc[f * 8 + 2 * i], gb = acc[f * 8 + 2 * i + 1];
        const float ua = acc[16 + f * 8 + 2 * i], ub = acc[16 + f * 8 + 2 * i + 1];
        const float c = (i & 1) ? c1 : c0, q = (i & 1) ? q1 : q0;
        const float da = 1.f + ex2f(fminf(ga * c, 60.f)), db = 1.f + ex2f(fminf(gb * c, 60.f));
        const float rq = rcpf(da * db) * q;
        h[i] = tagged(pack_bf16(ga * ua * (db * rq), gb * ub * (da * rq)), xoff & 1u);
      }
      const int jj = hb * 2 + f;
      sts_u4(stash + slot * 8192 + jj * 2048, h[0], h[1], h[2], h[3]);
      stg_u4(xptr(xslot, jj), h[0], h[1], h[2], h[3]);
    };
    auto kv_stage = [&](float (&acc)[32], int c, int hb) INL {
      const int srow = wq * 16 + (lane & 7) + ((lane >> 3) & 1) * 8;
      const uint32_t base = area + (3 + c) * 8192 + srow * 128;
#pragma unroll
      for (int jj = 0; jj < 2; jj++) {
        const int a = c * 16 + jj * 8;
        uint32_t r0, r1, r2, r3;
        if (c == 0) {
          r0 = pack_bf16(phi_f(acc[a] * rs0), phi_f(acc[a + 1] * rs0));
          r1 = pack_bf16(phi_f(acc[a + 2] * rs1), phi_f(acc[a + 3] * rs1));
          r2 = pack_bf16(phi_f(acc[a + 4] * rs0), phi_f(acc[a + 5] * rs0));
          r3 = pack_bf16(phi_f(acc[a + 6] * rs1), phi_f(acc[a + 7] * rs1));
        } else {
          r0 = pack_bf16(acc[a] * rs0, acc[a + 1] * rs0);
          r1 = pack_bf16(acc[a + 2] * rs1, acc[a + 3] * rs1);
          r2 = pack_bf16(acc[a + 4] * rs0, acc[a + 5] * rs0);
          r3 = pack_bf16(acc[a + 6] * rs1, acc[a + 7] * rs1);
        }
        stmatrix_x4(base + (((hb * 4 + jj * 2 + (lane >> 4)) ^ (srow & 7)) << 4), r0, r1, r2, r3);
      }
    };
    auto signal = [&](int e) INL {
      __syncwarp();
      if (lane == 0) mbar_arrive(BAR(B_EV + w * 2 + e));
    };

    auto pp_wait = [&]() INL { bar_sync(3 + w, 256); };
    auto pp_pass = [&]() INL { bar_arrive(3 + (w ^ 1), 256); };
    if (w == 1) pp_pass();
    int tw1 = 0, tw2 = 0, tw3 = 0;
#pragma unroll 1
    for (int t = 0; t < 5; t++) {
      const uint32_t ph = t & 1;
      const int kind = odd ? (t < 2 ? K_KV : K_GU) : (t < 4 ? K_GU : K_Q);
      const int slot = odd ? t - 2 : t, xslot = odd ? t + 4 : t;
      static_for<2>([&](auto hc) INL {
        constexpr int hb = decltype(hc)::value;
        float acc[32];
        TWAIT(tw2, pp_wait());
        static_for<4>([&](auto kc) INL {
          constexpr int kq = decltype(kc)::value, k = hb * 4 + kq;
          TWAIT(tw1, mbar_wait(BAR(B_FULL + k), ph));
          wgmma_fence();
          static_for<8>([&](auto kkc) INL {
            constexpr int kk = decltype(kkc)::value, i = (kq * 8 + kk) * 4;
            wgmma_n64_rs<(kq | kk) != 0, desc_lo(stage_off(k) + kk * 1024, 8192), kHi64>(acc, A[i], A[i + 1], A[i + 2], A[i + 3]);
          });
          wgmma_commit();
          if (kq == 2) pp_pass();
          if (kq > 0) {
            wgmma_wait<1>();
            release(k - 1);
          }
        });
        TWAIT(tw3, wgmma_wait<0>());
        release(hb * 4 + 3);
        if (hb == 0 && t == 0) xoff |= (epoch_c & 1u) ^ 1u;
        if (kind == K_GU) {
          gu_chunk(acc, 0, slot, xslot, hb);
          gu_chunk(acc, 1, slot, xslot, hb);
        } else if (kind == K_KV) {
          if (hb == 0 && t == 0) sts_u4(stash + 5 * 8192, 0x3F803F80u, 0x3F803F80u, 0x3F803F80u, 0x3F803F80u);
          kv_stage(acc, 0, hb);
          kv_stage(acc, 1, hb);
          if (hb == 1) {
            float kvacc[36];
            const int par = (xoff & 1u) ^ 1u;
            fence_proxy_async();
            bar_sync(1 + w, 128);
            wgmma_fence();
            static_for<4>([&](auto kkc) INL {
              constexpr int kk = decltype(kkc)::value;
              wgmma_n72_ss_tt<kk != 0, desc_lo(3 * 8192 + kk * 2048, 0), desc_lo(4 * 8192 + kk * 2048, 8192 - kk * 2048)>(kvacc, dbase + w * 4096);
            });
            wgmma_commit();
            wgmma_wait<0>();
            float c[8];
#pragma unroll
            for (int i = 0; i < 8; i++)
              c[i] = wq == 0 ? kvacc[i] : (wq == 1 ? kvacc[8 + i] : (wq == 2 ? kvacc[16 + i] : kvacc[24 + i]));
            const int head = (2 * p + t) * 4 + wq;
            float* kvp = &g_kv[par][head][0][0];
            red_add_v2(kvp + g * 16 + 2 * tq, c[0], c[1]);
            red_add_v2(kvp + (g + 8) * 16 + 2 * tq, c[2], c[3]);
            red_add_v2(kvp + g * 16 + 8 + 2 * tq, c[4], c[5]);
            red_add_v2(kvp + (g + 8) * 16 + 8 + 2 * tq, c[6], c[7]);
            if (tq == 0) {
              red_add(&g_z[par][head][g], kvacc[32]);
              red_add(&g_z[par][head][g + 8], kvacc[34]);
            }
            signal(t);
          }
        } else {
          uint32_t aq[4][4];
#pragma unroll
          for (int c = 0; c < 4; c++) {
            const int a = c * 8;
            aq[c][0] = pack_bf16(phi_f(acc[a] * rs0), phi_f(acc[a + 1] * rs0));
            aq[c][1] = pack_bf16(phi_f(acc[a + 2] * rs1), phi_f(acc[a + 3] * rs1));
            aq[c][2] = pack_bf16(phi_f(acc[a + 4] * rs0), phi_f(acc[a + 5] * rs0));
            aq[c][3] = pack_bf16(phi_f(acc[a + 6] * rs1), phi_f(acc[a + 7] * rs1));
          }
          if (hb == 0) mbar_wait(BAR(B_KVREADY), 0);
          float nd[4][12];
          wgmma_fence();
          static_for<4>([&](auto cc) INL {
            constexpr int c = decltype(cc)::value;
            wgmma_n24_rs<desc_lo(5 * 8192 + (hb * 4 + c) * 768, 128)>(nd[c], aq[c][0], aq[c][1], aq[c][2], aq[c][3], dbase + w * 4096);
          });
          wgmma_commit();
          wgmma_wait<0>();
          if (hb == 1) bar_sync(1 + w, 128);
          const uint32_t tg = xoff & 1u;
#pragma unroll
          for (int c = 0; c < 4; c++) {
            const float i0 = __fdividef(1.f, nd[c][8] + 1e-6f), i1 = __fdividef(1.f, nd[c][10] + 1e-6f);
            aq[c][0] = tagged(pack_bf16(nd[c][0] * i0, nd[c][1] * i0), tg);
            aq[c][1] = tagged(pack_bf16(nd[c][2] * i1, nd[c][3] * i1), tg);
            aq[c][2] = tagged(pack_bf16(nd[c][4] * i0, nd[c][5] * i0), tg);
            aq[c][3] = tagged(pack_bf16(nd[c][6] * i1, nd[c][7] * i1), tg);
          }
#pragma unroll
          for (int c = 0; c < 4; c++) {
            stg_u4(xptr(4 + hb, c), aq[c][0], aq[c][1], aq[c][2], aq[c][3]);
            sts_u4(stash + (4 + hb) * 8192 + c * 2048, aq[c][0], aq[c][1], aq[c][2], aq[c][3]);
          }
        }
      });
      PROF(w, 1 + 2 * t);
    }
    PROF(w, 10);

    const int n_own = odd ? 3 : 6;
    auto load_a = [&](int kb) INL {
      if (kb < n_own) {
#pragma unroll
        for (int jj = 0; jj < 4; jj++) {
          const int i = (kb * 4 + jj) * 4;
          lds_u4(stash + kb * 8192 + jj * 2048, A[i], A[i + 1], A[i + 2], A[i + 3]);
        }
      } else {
        const int xs = odd ? kb - 3 : kb;
#pragma unroll
        for (int jj = 0; jj < 4; jj++) {
          const int i = (kb * 4 + jj) * 4;
          ldg_poll_u4(xptr(xs, jj), A[i], A[i + 1], A[i + 2], A[i + 3]);
        }
      }
    };
    auto fix_a = [&](int kb) INL {
      if (kb >= n_own) {
        const int xs = odd ? kb - 3 : kb;
        recv_group<4>(xptr(xs, 0), &A[kb * 16], xoff & 1u);
      }
    };
#pragma unroll
    for (int kb = 0; kb < 7; kb++) load_a(kb);
    PROF(w, 11);

    const uint32_t ooff = (uint32_t)(m * 128 + w * 64 + wq * 16 + (lane >> 3)) * kD + odd * 256 + p * 64 + (lane & 7) * 8;
    float acc2[2][32];
    uint32_t poff = (uint32_t)((m * 2 + odd) * 24 + w) * 8192u + (uint32_t)t128 * 16u;
    asm volatile("" : "+r"(poff));
    auto pptr = [&](int dest, int sl) INL { return (uint4*)((char*)g_pbuf + (poff + (uint32_t)(dest * 3 + sl) * 16384u)); };
    uint32_t P[3][16];
    uint4 xr[4];
    auto send = [&](float (&acc)[32], int bi) INL {
      uint4* dst = pptr((p + 1 + bi) & 3, bi);
#pragma unroll
      for (int q = 0; q < 4; q++)
        stg_u4(dst + q * 128, tagged(pack_bf16(acc[q * 8], acc[q * 8 + 1]), xoff & 1u), tagged(pack_bf16(acc[q * 8 + 2], acc[q * 8 + 3]), xoff & 1u),
               tagged(pack_bf16(acc[q * 8 + 4], acc[q * 8 + 5]), xoff & 1u), tagged(pack_bf16(acc[q * 8 + 6], acc[q * 8 + 7]), xoff & 1u));
      PROF(w, 12 + 2 * bi);
    };
    auto fetch = [&](int sl) INL {
#pragma unroll
      for (int q = 0; q < 4; q++)
        asm volatile("cp.async.cg.shared.global [%0], [%1], 16;" ::"r"(stash + (3 + sl) * 8192 + q * 2048), "l"(pptr(p, sl) + q * 128) : "memory");
    };
    auto collect = [&](int sl) INL {
      asm volatile("cp.async.wait_all;" ::: "memory");
#pragma unroll
      for (int q = 0; q < 4; q++) lds_u4(stash + (3 + sl) * 8192 + q * 2048, P[sl][q * 4], P[sl][q * 4 + 1], P[sl][q * 4 + 2], P[sl][q * 4 + 3]);
      recv_group<4>(pptr(p, sl), &P[sl][0], xoff & 1u);
    };
    static_for<36>([&](auto ic) INL {
      constexpr int i = decltype(ic)::value, bi = p2_bi(i), kb = p2_kb(i), j = i >> 1, st = j & 7;
      if (i == 9) { load_a(7); load_a(8); }
      if (i == 14) PROF(w, 2);
      if (bi == 0 && kb >= 3) fix_a(kb);
      if (i == 15) PROF(w, 4);
      if (i == 7) PROF(w, 6);
      if (i == 0 || i == 7 || i == 14 || i == 18 || i == 27) pp_wait();
      if ((i & 1) == 0) mbar_wait(BAR(B_FULL + st), (5 + (j >> 3)) & 1);
      wgmma_fence();
      static_for<4>([&](auto kkc) INL {
        constexpr int kk = decltype(kkc)::value, a = (kb * 4 + kk) * 4;
        wgmma_n64_rs<(kb | kk) != 0, desc_lo(stage_off(st) + (i & 1) * 8192 + kk * 2048, 0), kHi128>(acc2[bi & 1], A[a], A[a + 1], A[a + 2], A[a + 3]);
      });
      wgmma_commit();
      if (i == 4 || i == 11 || i == 15 || i == 24 || (i == 33 && w == 0)) pp_pass();
      if (i > 0) {
        wgmma_wait<1>();
        if ((i & 1) == 0 && j - 1 <= 9) release((j - 1) & 7);
      }
      if constexpr (i == 17) { send(acc2[0], 0); wgmma_wait<0>(); send(acc2[1], 1); }
      if constexpr (i == 26) { wgmma_wait<0>(); send(acc2[0], 2); }
      if constexpr (i == 28) {
#pragma unroll
        for (int q = 0; q < 4; q++) xr[q] = __ldg((const uint4*)(x + ooff + q * 4 * kD));
      }
      if constexpr (i == 27) { fetch(0); fetch(1); }
      if constexpr (i == FPOS) fetch(2);
    });
    PROF(w, 17);
    collect(0);
    collect(1);
#pragma unroll
    for (int q = 0; q < 16; q++) {
      acc2[0][2 * q] = __uint_as_float(P[0][q] << 16) + __uint_as_float(P[1][q] << 16);
      acc2[0][2 * q + 1] = __uint_as_float(P[0][q] & 0xffff0000u) + __uint_as_float(P[1][q] & 0xffff0000u);
    }
    PROF(w, 13);
    collect(2);
    PROF(w, 15);
    wgmma_wait<0>();
    PROF(w, 18);
    {
      const uint32_t tile = area + wq * 4352;
#pragma unroll
      for (int q = 0; q < 8; q++) {
        float rr[4];
#pragma unroll
        for (int e = 0; e < 4; e++) rr[e] = acc2[1][q * 4 + e] + acc2[0][q * 4 + e];
        rr[0] += __uint_as_float(P[2][2 * q] << 16);
        rr[1] += __uint_as_float(P[2][2 * q] & 0xffff0000u);
        rr[2] += __uint_as_float(P[2][2 * q + 1] << 16);
        rr[3] += __uint_as_float(P[2][2 * q + 1] & 0xffff0000u);
        const uint32_t ad = tile + g * 272 + q * 32 + tq * 8;
        asm volatile("st.shared.v2.f32 [%0], {%1,%2};" ::"r"(ad), "f"(rr[0]), "f"(rr[1]) : "memory");
        asm volatile("st.shared.v2.f32 [%0], {%1,%2};" ::"r"(ad + 8 * 272), "f"(rr[2]), "f"(rr[3]) : "memory");
      }
      __syncwarp();
#pragma unroll
      for (int q = 0; q < 4; q++) {
        const uint32_t ad = tile + ((lane >> 3) + 4 * q) * 272 + (lane & 7) * 32;
        uint32_t v[8];
        lds_u4(ad, v[0], v[1], v[2], v[3]);
        lds_u4(ad + 16, v[4], v[5], v[6], v[7]);
        const uint32_t xv[4] = {xr[q].x, xr[q].y, xr[q].z, xr[q].w};
        uint32_t o[4];
#pragma unroll
        for (int e = 0; e < 4; e++)
          o[e] = pack_bf16(__uint_as_float(v[2 * e]) + __uint_as_float(xv[e] << 16), __uint_as_float(v[2 * e + 1]) + __uint_as_float(xv[e] & 0xffff0000u));
        stg_u4(out + ooff + q * 4 * kD, o[0], o[1], o[2], o[3]);
      }
    }
    PROF(w, 19);
    if (tid == 0) {
      const uint32_t old = atomicAdd(&g_done, 1u);
      if ((old & 127u) == 127u) st_relaxed(&g_epoch, ld_relaxed(&g_epoch) + 1u);
    }
  }
#undef BAR
}

typedef CUresult (*EncodeFn)(CUtensorMap*, CUtensorMapDataType, cuuint32_t, void*, const cuuint64_t*, const cuuint64_t*,
                             const cuuint32_t*, const cuuint32_t*, CUtensorMapInterleave, CUtensorMapSwizzle,
                             CUtensorMapL2promotion, CUtensorMapFloatOOBfill);

void make_map(EncodeFn enc, CUtensorMap* tm, const void* ptr, int rows, int cols, bool narrow) {
  cuuint64_t gd[2] = {(cuuint64_t)cols, (cuuint64_t)rows};
  cuuint64_t gs[1] = {(cuuint64_t)cols * 2};
  cuuint32_t bd[2] = {narrow ? 32u : 64u, narrow ? 128u : 64u};
  cuuint32_t es[2] = {1, 1};
  enc(tm, CU_TENSOR_MAP_DATA_TYPE_BFLOAT16, 2, const_cast<void*>(ptr), gd, gs, bd, es, CU_TENSOR_MAP_INTERLEAVE_NONE,
      narrow ? CU_TENSOR_MAP_SWIZZLE_64B : CU_TENSOR_MAP_SWIZZLE_128B, CU_TENSOR_MAP_L2_PROMOTION_L2_256B, CU_TENSOR_MAP_FLOAT_OOB_FILL_NONE);
}

}

extern "C" void kernel_launch(void* const* d_in, const int* in_sizes, int n_in, void* d_out, int out_size) {
  static EncodeFn enc = nullptr;
  if (!enc) {
    void* fn = nullptr;
    cudaDriverEntryPointQueryResult qr;
    cudaGetDriverEntryPoint("cuTensorMapEncodeTiled", &fn, cudaEnableDefault, &qr);
    enc = (EncodeFn)fn;
    cudaFuncSetAttribute(fused_kernel, cudaFuncAttributeMaxDynamicSharedMemorySize, kSmemBytes);
  }
  CUtensorMap tm_x, tm_wqkv, tm_w1, tm_w3, tm_w2, tm_wo;
  make_map(enc, &tm_x, d_in[0], kS, kD, false);
  make_map(enc, &tm_wqkv, d_in[1], kD, 3 * kD, true);
  make_map(enc, &tm_wo, d_in[2], kD, kD, false);
  make_map(enc, &tm_w1, d_in[4], kD, kF, true);
  make_map(enc, &tm_w3, d_in[5], kD, kF, true);
  make_map(enc, &tm_w2, d_in[6], kF, kD, false);
  fused_kernel<<<128, 384, kSmemBytes>>>(tm_x, tm_wqkv, tm_w1, tm_w3, tm_w2, tm_wo, (const __nv_bfloat16*)d_in[0],
                                         (__nv_bfloat16*)d_out);
}
```

```cpp
#include <cuda_runtime.h>
#include <cuda_bf16.h>
#include <cuda.h>
#include <stdint.h>

extern __shared__ __align__(1024) uint8_t smem_raw[];

namespace {

constexpr int kS = 2048, kD = 512, kF = 1792;
#define XPER 2
#define FPOS 32
#define PPOS 3
#define XUP 4
constexpr uint32_t kSpinLimit = 1u << 22;

__device__ uint4    g_xbuf[16][4][9][2][4][128];
__device__ uint4    g_pbuf[16][2][4][3][2][4][128];
__device__ float    g_kv[2][32][16][16];
__device__ float    g_z[2][32][16];
__device__ uint32_t g_kvcnt[4][32];
__device__ uint32_t g_epoch;
__device__ uint32_t g_done;
#define PROF(wg, i) do {} while (0)
#define TWAIT(acc, stmt) do { stmt; } while (0)

__device__ __forceinline__ uint32_t smem_u32(const void* p) { return (uint32_t)__cvta_generic_to_shared(p); }
__device__ __forceinline__ void mbar_init(uint32_t bar, uint32_t cnt) {
  asm volatile("mbarrier.init.shared::cta.b64 [%0], %1;" ::"r"(bar), "r"(cnt) : "memory");
}
__device__ __forceinline__ void mbar_expect_tx(uint32_t bar, uint32_t bytes) {
  asm volatile("mbarrier.arrive.expect_tx.shared::cta.b64 _, [%0], %1;" ::"r"(bar), "r"(bytes) : "memory");
}
__device__ __forceinline__ void mbar_arrive(uint32_t bar) {
  asm volatile("mbarrier.arrive.shared::cta.b64 _, [%0];" ::"r"(bar) : "memory");
}
__device__ __forceinline__ void mbar_wait(uint32_t bar, uint32_t parity) {
  asm volatile(
      "{\n.reg .pred p;\n"
      "LAB_WAIT:\n"
      "mbarrier.try_wait.parity.shared::cta.b64 p, [%0], %1;\n"
      "@p bra DONE;\n"
      "bra LAB_WAIT;\n"
      "DONE:\n}" ::"r"(bar), "r"(parity) : "memory");
}
__device__ __forceinline__ void tma_load_2d(uint32_t dst, const CUtensorMap* tm, uint32_t bar, int c0, int c1) {
  asm volatile(
      "cp.async.bulk.tensor.2d.shared::cluster.global.mbarrier::complete_tx::bytes [%0], [%1, {%3, %4}], [%2];" ::"r"(dst),
      "l"(tm), "r"(bar), "r"(c0), "r"(c1)
      : "memory");
}
__device__ __forceinline__ void tma_load_2d_mc(uint32_t dst, const CUtensorMap* tm, uint32_t bar, int c0, int c1) {
  asm volatile(
      "cp.async.bulk.tensor.2d.shared::cluster.global.mbarrier::complete_tx::bytes.multicast::cluster [%0], [%1, {%3, %4}], [%2], %5;" ::"r"(dst),
      "l"(tm), "r"(bar), "r"(c0), "r"(c1), "h"((uint16_t)3)
      : "memory");
}
__device__ __forceinline__ void mbar_arrive_cluster(uint32_t bar, uint32_t cta) {
  asm volatile("{\n.reg .b32 ra;\nmapa.shared::cluster.u32 ra, %0, %1;\nmbarrier.arrive.shared::cluster.b64 _, [ra];\n}" ::"r"(bar), "r"(cta) : "memory");
}
__device__ __forceinline__ void prefetch_tmap(const CUtensorMap* tm) {
  asm volatile("prefetch.tensormap [%0];" ::"l"(tm) : "memory");
}
__device__ __forceinline__ void wgmma_fence() { asm volatile("wgmma.fence.sync.aligned;" ::: "memory"); }
__device__ __forceinline__ void wgmma_commit() { asm volatile("wgmma.commit_group.sync.aligned;" ::: "memory"); }
template <int N>
__device__ __forceinline__ void wgmma_wait() { asm volatile("wgmma.wait_group.sync.aligned %0;" ::"n"(N) : "memory"); }
__device__ __forceinline__ void bar_sync(int id, int n) { asm volatile("bar.sync %0, %1;" ::"r"(id), "r"(n) : "memory"); }
__device__ __forceinline__ void bar_arrive(int id, int n) { asm volatile("bar.arrive %0, %1;" ::"r"(id), "r"(n) : "memory"); }
__device__ __forceinline__ void fence_proxy_async() { asm volatile("fence.proxy.async.shared::cta;" ::: "memory"); }

__device__ __forceinline__ uint32_t ld_acquire(const uint32_t* p) {
  uint32_t v;
  asm volatile("ld.acquire.gpu.global.u32 %0, [%1];" : "=r"(v) : "l"(p) : "memory");
  return v;
}
__device__ __forceinline__ uint32_t ld_relaxed(const uint32_t* p) {
  uint32_t v;
  asm volatile("ld.relaxed.gpu.global.u32 %0, [%1];" : "=r"(v) : "l"(p));
  return v;
}
__device__ __forceinline__ void cluster_wait() { asm volatile("barrier.cluster.wait.aligned;" ::: "memory"); }
__device__ __forceinline__ void st_relaxed(uint32_t* p, uint32_t v) {
  asm volatile("st.relaxed.gpu.global.u32 [%0], %1;" ::"l"(p), "r"(v) : "memory");
}
__device__ __forceinline__ void wait_flag_eq(const uint32_t* p, uint32_t val) {
  uint32_t it = 0;
  while (ld_acquire(p) != val) {
    if (++it > kSpinLimit) break;
  }
}
__device__ __forceinline__ void wait_count_ge(const uint32_t* p, uint32_t val) {
  uint32_t it = 0;
  while ((int32_t)(ld_acquire(p) - val) < 0) {
    __nanosleep(64);
    if (++it > kSpinLimit) break;
  }
}
__device__ __forceinline__ void ldg_poll_u4(const void* p, uint32_t& a, uint32_t& b, uint32_t& c, uint32_t& d) {
  asm volatile("ld.relaxed.gpu.global.v4.u32 {%0,%1,%2,%3}, [%4];" : "=r"(a), "=r"(b), "=r"(c), "=r"(d) : "l"(p) : "memory");
}
template <int N>
__device__ __forceinline__ void recv_group(const uint4* p, uint32_t* r, uint32_t tag) {
  uint32_t it = 0;
  while (true) {
    uint32_t bad = 0u;
#pragma unroll
    for (int i = 0; i < 4 * N; i++) bad |= r[i] ^ tag;
    if (!__any_sync(0xffffffffu, (bad & 1u) != 0u) || ++it > kSpinLimit) break;
#pragma unroll
    for (int q = 0; q < N; q++) ldg_poll_u4(p + q * 128, r[q * 4], r[q * 4 + 1], r[q * 4 + 2], r[q * 4 + 3]);
  }
}
__device__ __forceinline__ uint32_t tagged(uint32_t v, uint32_t tag) { return (v & ~1u) | tag; }
__device__ __forceinline__ float4 ldg_cg_f4(const void* p) {
  float4 v;
  asm volatile("ld.global.cg.v4.f32 {%0,%1,%2,%3}, [%4];" : "=f"(v.x), "=f"(v.y), "=f"(v.z), "=f"(v.w) : "l"(p) : "memory");
  return v;
}
__device__ __forceinline__ void stg_u4(void* p, uint32_t a, uint32_t b, uint32_t c, uint32_t d) {
  asm volatile("st.global.v4.u32 [%0], {%1,%2,%3,%4};" ::"l"(p), "r"(a), "r"(b), "r"(c), "r"(d) : "memory");
}
__device__ __forceinline__ void stg_f4(void* p, float a, float b, float c, float d) {
  asm volatile("st.global.v4.f32 [%0], {%1,%2,%3,%4};" ::"l"(p), "f"(a), "f"(b), "f"(c), "f"(d) : "memory");
}
__device__ __forceinline__ void sts_u4(uint32_t addr, uint32_t a, uint32_t b, uint32_t c, uint32_t d) {
  asm volatile("st.shared.v4.u32 [%0], {%1,%2,%3,%4};" ::"r"(addr), "r"(a), "r"(b), "r"(c), "r"(d) : "memory");
}
__device__ __forceinline__ void lds_u4(uint32_t addr, uint32_t& a, uint32_t& b, uint32_t& c, uint32_t& d) {
  asm volatile("ld.shared.v4.u32 {%0,%1,%2,%3}, [%4];" : "=r"(a), "=r"(b), "=r"(c), "=r"(d) : "r"(addr) : "memory");
}
__device__ __forceinline__ uint32_t lds_u32(uint32_t addr) {
  uint32_t v;
  asm volatile("ld.shared.u32 %0, [%1];" : "=r"(v) : "r"(addr) : "memory");
  return v;
}
__device__ __forceinline__ void ldmatrix_x4(uint32_t addr, uint32_t& a, uint32_t& b, uint32_t& c, uint32_t& d) {
  asm volatile("ldmatrix.sync.aligned.m8n8.x4.shared.b16 {%0,%1,%2,%3}, [%4];" : "=r"(a), "=r"(b), "=r"(c), "=r"(d) : "r"(addr) : "memory");
}
__device__ __forceinline__ void ldmatrix_x4_trans(uint32_t addr, uint32_t& a, uint32_t& b, uint32_t& c, uint32_t& d) {
  asm volatile("ldmatrix.sync.aligned.m8n8.x4.trans.shared.b16 {%0,%1,%2,%3}, [%4];" : "=r"(a), "=r"(b), "=r"(c), "=r"(d) : "r"(addr) : "memory");
}
__device__ __forceinline__ void stmatrix_x4(uint32_t addr, uint32_t a, uint32_t b, uint32_t c, uint32_t d) {
  asm volatile("stmatrix.sync.aligned.m8n8.x4.shared.b16 [%0], {%1,%2,%3,%4};" ::"r"(addr), "r"(a), "r"(b), "r"(c), "r"(d) : "memory");
}
__device__ __forceinline__ void mma_16816(float (&c)[4], uint32_t a0, uint32_t a1, uint32_t a2, uint32_t a3, uint32_t b0, uint32_t b1) {
  asm(
      "mma.sync.aligned.m16n8k16.row.col.f32.bf16.bf16.f32 {%0,%1,%2,%3}, {%4,%5,%6,%7}, {%8,%9}, {%0,%1,%2,%3};"
      : "+f"(c[0]), "+f"(c[1]), "+f"(c[2]), "+f"(c[3])
      : "r"(a0), "r"(a1), "r"(a2), "r"(a3), "r"(b0), "r"(b1));
}
__device__ __forceinline__ uint32_t pack_bf16(float lo, float hi) {
  uint32_t r;
  asm("cvt.rn.bf16x2.f32 %0, %1, %2;" : "=r"(r) : "f"(hi), "f"(lo));
  return r;
}
__device__ __forceinline__ uint32_t hsub2_bf16(uint32_t a, uint32_t b) {
  uint32_t r;
  asm("sub.rn.bf16x2 %0, %1, %2;" : "=r"(r) : "r"(a), "r"(b));
  return r;
}
__device__ __forceinline__ float ex2f(float x) {
  float r;
  asm("ex2.approx.ftz.f32 %0, %1;" : "=f"(r) : "f"(x));
  return r;
}
__device__ __forceinline__ float rcpf(float x) {
  float r;
  asm("rcp.approx.ftz.f32 %0, %1;" : "=f"(r) : "f"(x));
  return r;
}
__device__ __forceinline__ void red_add_v2(float* p, float a, float b) {
  asm volatile("red.relaxed.gpu.global.add.v2.f32 [%0], {%1,%2};" ::"l"(p), "f"(a), "f"(b) : "memory");
}
__device__ __forceinline__ void red_add(float* p, float a) {
  asm volatile("red.relaxed.gpu.global.add.f32 [%0], %1;" ::"l"(p), "f"(a) : "memory");
}
__device__ __forceinline__ float phi_f(float t) {
  float e = ex2f(t * 1.4426950408889634f);
  return (t > 0.f ? t + 1.f : e) + 1e-6f;
}

#define R8(a, o) "+f"(a[o + 0]), "+f"(a[o + 1]), "+f"(a[o + 2]), "+f"(a[o + 3]), "+f"(a[o + 4]), "+f"(a[o + 5]), "+f"(a[o + 6]), "+f"(a[o + 7])

#define W8(a, o) "=f"(a[o + 0]), "=f"(a[o + 1]), "=f"(a[o + 2]), "=f"(a[o + 3]), "=f"(a[o + 4]), "=f"(a[o + 5]), "=f"(a[o + 6]), "=f"(a[o + 7])
#define D32 "{%0,%1,%2,%3,%4,%5,%6,%7,%8,%9,%10,%11,%12,%13,%14,%15,%16,%17,%18,%19,%20,%21,%22,%23,%24,%25,%26,%27,%28,%29,%30,%31}"
#define D36 "{%0,%1,%2,%3,%4,%5,%6,%7,%8,%9,%10,%11,%12,%13,%14,%15,%16,%17,%18,%19,%20,%21,%22,%23,%24,%25,%26,%27,%28,%29,%30,%31,%32,%33,%34,%35}"

constexpr uint32_t kHi128 = (1024u >> 4) | (1u << 30);
constexpr uint32_t kHi64 = (512u >> 4) | (2u << 30);
__host__ __device__ constexpr uint32_t desc_lo(uint32_t off, uint32_t lbo) { return (off >> 4) | ((lbo >> 4) << 16); }

constexpr uint32_t kSmemBase = 1024;
template <bool CB, bool ACC, uint32_t LO, uint32_t HI>
__device__ __forceinline__ void wgmma_n64_rs(float (&d)[32], uint32_t a0, uint32_t a1, uint32_t a2, uint32_t a3, uint32_t base) {
  if (CB) {
    if (ACC) {
      asm volatile(
          "{\n.reg .pred p;\n.reg .b64 dd;\nsetp.eq.b32 p, 0, 0;\nmov.b64 dd, {%36, %37};\n"
          "wgmma.mma_async.sync.aligned.m64n64k16.f32.bf16.bf16 " D32 ", {%32,%33,%34,%35}, dd, p, 1, 1, 1;\n}"
          : R8(d, 0), R8(d, 8), R8(d, 16), R8(d, 24)
          : "r"(a0), "r"(a1), "r"(a2), "r"(a3), "n"(LO + (kSmemBase >> 4)), "n"(HI));
    } else {
      asm volatile(
          "{\n.reg .pred p;\n.reg .b64 dd;\nsetp.ne.b32 p, 0, 0;\nmov.b64 dd, {%36, %37};\n"
          "wgmma.mma_async.sync.aligned.m64n64k16.f32.bf16.bf16 " D32 ", {%32,%33,%34,%35}, dd, p, 1, 1, 1;\n}"
          : W8(d, 0), W8(d, 8), W8(d, 16), W8(d, 24)
          : "r"(a0), "r"(a1), "r"(a2), "r"(a3), "n"(LO + (kSmemBase >> 4)), "n"(HI));
    }
  } else {
    if (ACC) {
      asm volatile(
          "{\n.reg .pred p;\n.reg .b32 lo;\n.reg .b64 dd;\nsetp.eq.b32 p, 0, 0;\nadd.u32 lo, %36, %37;\nmov.b64 dd, {lo, %38};\n"
          "wgmma.mma_async.sync.aligned.m64n64k16.f32.bf16.bf16 " D32 ", {%32,%33,%34,%35}, dd, p, 1, 1, 1;\n}"
          : R8(d, 0), R8(d, 8), R8(d, 16), R8(d, 24)
          : "r"(a0), "r"(a1), "r"(a2), "r"(a3), "r"(base), "n"(LO), "n"(HI));
    } else {
      asm volatile(
          "{\n.reg .pred p;\n.reg .b32 lo;\n.reg .b64 dd;\nsetp.ne.b32 p, 0, 0;\nadd.u32 lo, %36, %37;\nmov.b64 dd, {lo, %38};\n"
          "wgmma.mma_async.sync.aligned.m64n64k16.f32.bf16.bf16 " D32 ", {%32,%33,%34,%35}, dd, p, 1, 1, 1;\n}"
          : W8(d, 0), W8(d, 8), W8(d, 16), W8(d, 24)
          : "r"(a0), "r"(a1), "r"(a2), "r"(a3), "r"(base), "n"(LO), "n"(HI));
    }
  }
}
template <bool ACC, uint32_t LOA, uint32_t LOB>
__device__ __forceinline__ void wgmma_n72_ss_tt(float (&d)[36], uint32_t base) {
  if (ACC) {
    asm volatile(
        "{\n.reg .pred p;\n.reg .b32 lo;\n.reg .b64 da, db;\nsetp.eq.b32 p, 0, 0;\n"
        "add.u32 lo, %36, %37;\nmov.b64 da, {lo, %39};\nadd.u32 lo, %36, %38;\nmov.b64 db, {lo, %39};\n"
        "wgmma.mma_async.sync.aligned.m64n72k16.f32.bf16.bf16 " D36 ", da, db, p, 1, 1, 1, 1;\n}"
        : R8(d, 0), R8(d, 8), R8(d, 16), R8(d, 24), "+f"(d[32]), "+f"(d[33]), "+f"(d[34]), "+f"(d[35])
        : "r"(base), "n"(LOA), "n"(LOB), "n"(kHi128));
  } else {
    asm volatile(
        "{\n.reg .pred p;\n.reg .b32 lo;\n.reg .b64 da, db;\nsetp.ne.b32 p, 0, 0;\n"
        "add.u32 lo, %36, %37;\nmov.b64 da, {lo, %39};\nadd.u32 lo, %36, %38;\nmov.b64 db, {lo, %39};\n"
        "wgmma.mma_async.sync.aligned.m64n72k16.f32.bf16.bf16 " D36 ", da, db, p, 1, 1, 1, 1;\n}"
        : W8(d, 0), W8(d, 8), W8(d, 16), W8(d, 24), "=f"(d[32]), "=f"(d[33]), "=f"(d[34]), "=f"(d[35])
        : "r"(base), "n"(LOA), "n"(LOB), "n"(kHi128));
  }
}

#define INL __attribute__((always_inline))
template <uint32_t LO>
__device__ __forceinline__ void wgmma_n24_rs(float (&d)[12], uint32_t a0, uint32_t a1, uint32_t a2, uint32_t a3, uint32_t base) {
  asm volatile(
      "{\n.reg .pred p;\n.reg .b32 lo;\n.reg .b64 dd;\nsetp.ne.b32 p, 0, 0;\nadd.u32 lo, %16, %17;\nmov.b64 dd, {lo, %18};\n"
      "wgmma.mma_async.sync.aligned.m64n24k16.f32.bf16.bf16 {%0,%1,%2,%3,%4,%5,%6,%7,%8,%9,%10,%11}, {%12,%13,%14,%15}, dd, p, 1, 1, 1;\n}"
      : W8(d, 0), "=f"(d[8]), "=f"(d[9]), "=f"(d[10]), "=f"(d[11])
      : "r"(a0), "r"(a1), "r"(a2), "r"(a3), "r"(base), "n"(LO), "n"(256u >> 4));
}

template <int V> struct IC { static constexpr int value = V; };
template <int N, int I = 0, typename F>
__device__ __forceinline__ void static_for(F&& f) {
  if constexpr (I < N) { f(IC<I>{}); static_for<N, I + 1>(f); }
}

__host__ __device__ constexpr uint32_t stage_off(int st) {
  return st < 6 ? 131072u + (uint32_t)st * 16384u : (uint32_t)(st - 6) * 65536u + 49152u;
}

constexpr int B_FULL = 0, B_EMPTY = 8, B_XFULL = 16, B_XDONE = 32, B_KVREADY = 33, B_EV = 34, B_CS = 38, B_COUNT = 39;
constexpr uint32_t kBarOff = 229376;
constexpr int kSmemBytes = 229376 + 1024;

__host__ __device__ constexpr int p2_bi(int i) { return i < 7 ? 0 : i < 14 ? 1 : i < 16 ? 0 : i < 18 ? 1 : i / 9; }
__host__ __device__ constexpr int p2_kb(int i) { return i < 7 ? i : i < 14 ? i - 7 : i < 16 ? i - 7 : i < 18 ? i - 9 : i % 9; }

enum { K_NONE = 0, K_GU = 1, K_KV = 2, K_Q = 3 };

template <bool CB>
__global__ void __cluster_dims__(2, 1, 1) __launch_bounds__(384, 1)
fused_kernel(const __grid_constant__ CUtensorMap tm_x, const __grid_constant__ CUtensorMap tm_wqkv,
             const __grid_constant__ CUtensorMap tm_w1, const __grid_constant__ CUtensorMap tm_w3,
             const __grid_constant__ CUtensorMap tm_w2, const __grid_constant__ CUtensorMap tm_wo,
             const __nv_bfloat16* __restrict__ x, __nv_bfloat16* __restrict__ out) {
  const uint32_t sbase = smem_u32(smem_raw);
  const uint32_t bars = sbase + kBarOff;
  const int tid = threadIdx.x, lane = tid & 31;
  const int warp = __shfl_sync(0xffffffffu, tid >> 5, 0);
  const int cr = blockIdx.x & 1;
  const int r = (blockIdx.x >> 1) & 7, m = ((blockIdx.x >> 4) << 1) | cr, p = r >> 1, odd = r & 1;
#define BAR(i) (bars + 8u * (uint32_t)(i))
  if (tid == 256) {
    if (CB ? (sbase & 0x3FFFFu) != kSmemBase : (sbase & 1023u) != 0u) __trap();
#pragma unroll
    for (int i = 0; i < 16; i++) mbar_init(BAR(B_XFULL + i), 1);
    fence_proxy_async();
#pragma unroll
    for (int b = 0; b < XUP; b++) {
      mbar_expect_tx(BAR(B_XFULL + b), 8192);
      tma_load_2d(sbase + (b >> 3) * 65536 + (b & 7) * 8192, &tm_x, BAR(B_XFULL + b), (b & 7) * 64, m * 128 + (b >> 3) * 64);
    }
#pragma unroll
    for (int i = 0; i < 8; i++) { mbar_init(BAR(B_FULL + i), 1); mbar_init(BAR(B_EMPTY + i), 4); }
#pragma unroll
    for (int i = 0; i < 4; i++) mbar_init(BAR(B_EV + i), 4);
    mbar_init(BAR(B_XDONE), 2);
    mbar_init(BAR(B_CS), 1);
    mbar_init(BAR(B_KVREADY), 3);
    asm volatile("fence.mbarrier_init.release.cluster;" ::: "memory");
    fence_proxy_async();
  } else if (tid == 288) {
    prefetch_tmap(odd ? &tm_wqkv : (cr ? &tm_w3 : &tm_w1));
  }
  __syncwarp();
  asm volatile("barrier.cluster.arrive.relaxed.aligned;" ::: "memory");
  PROF((tid >> 7), 21);
  __syncthreads();

  if (warp >= 8) {
    asm volatile("setmaxnreg.dec.sync.aligned.u32 24;");
    PROF(2, 3);
    cluster_wait();
    PROF(2, 2);
    const uint32_t epoch = warp == 8 ? 0u : ld_relaxed(&g_epoch);
    const uint32_t tag = epoch + 1u;
    const int par = epoch & 1;
    if (warp == 8) {
      if (lane == 0) {
        int twp = 0, xb = XUP;
        for (int j = 0; j < 10; j++) {
          const CUtensorMap* tm;
          int col;
          if (!odd) {
            if (j < 8) { tm = cr ? &tm_w3 : &tm_w1; col = 7 * p * 64 + j * 32; }
            else { tm = &tm_wqkv; col = 128 * p + (j - 8) * 64 + cr * 32; }
          } else {
            if (j < 4) { tm = &tm_wqkv; col = 512 + cr * 512 + 128 * p + j * 32; }
            else { tm = cr ? &tm_w3 : &tm_w1; col = (7 * p + 4) * 64 + (j - 4) * 32; }
          }
          const int t = j >> 1;
          for (int kq = 0; kq < 4; kq++) {
            const int k = (j & 1) * 4 + kq;
            TWAIT(twp, mbar_wait(BAR(B_EMPTY + k), k < 6 ? ((t & 1) ^ 1) : (t & 1)));
            mbar_expect_tx(BAR(B_FULL + k), 16384);
            tma_load_2d_mc(sbase + stage_off(k) + cr * 8192, tm, BAR(B_FULL + k), col, kq * 128);
            if (j == 0) {
              const int b1 = kq == 3 ? 16 : min(16, xb + XPER);
              for (; xb < b1; xb++) {
                mbar_expect_tx(BAR(B_XFULL + xb), 8192);
                tma_load_2d(sbase + (xb >> 3) * 65536 + (xb & 7) * 8192, &tm_x, BAR(B_XFULL + xb), (xb & 7) * 64, m * 128 + (xb >> 3) * 64);
              }
            }
          }
        }
        for (int j = 0; j < 18; j++) {
          const int st = j & 7, n = 5 + (j >> 3);
          const int i = 2 * j + cr;
          const int bi = p2_bi(i), kb = p2_kb(i);
          const int col = odd * 256 + ((p + 1 + bi) & 3) * 64;
          const CUtensorMap* tmk;
          int row;
          if (!odd) {
            if (kb < 4) { tmk = &tm_w2; row = (7 * p + kb) * 64; }
            else if (kb < 6) { tmk = &tm_wo; row = (2 * p + kb - 4) * 64; }
            else { tmk = &tm_w2; row = (7 * p + 4 + kb - 6) * 64; }
          } else {
            if (kb < 3) { tmk = &tm_w2; row = (7 * p + 4 + kb) * 64; }
            else if (kb < 7) { tmk = &tm_w2; row = (7 * p + kb - 3) * 64; }
            else { tmk = &tm_wo; row = (2 * p + kb - 7) * 64; }
          }
          mbar_wait(BAR(B_EMPTY + st), st < 6 ? ((n & 1) ^ 1) : (n & 1));
          mbar_expect_tx(BAR(B_FULL + st), 16384);
          tma_load_2d_mc(sbase + stage_off(st) + cr * 8192, tmk, BAR(B_FULL + st), col, row);
        }
      }
    } else if (odd) {
      if (lane == 0 && warp <= 10) {
        const int w = warp - 9;
        for (int e = 0; e < 2; e++) {
          mbar_wait(BAR(B_EV + w * 2 + e), 0);
          __threadfence();
          atomicAdd(&g_kvcnt[p][0], 1u);
        }
      }
    } else {
      const int hl = tid - 288;
      {
        const int ce = m * 4 + p;
        if (hl < 32) *(float4*)(&g_kv[par ^ 1][0][0][0] + ce * 128 + hl * 4) = make_float4(0.f, 0.f, 0.f, 0.f);
        else if (hl < 40) (&g_z[par ^ 1][0][0])[ce * 8 + hl - 32] = 0.f;
      }
      mbar_wait(BAR(B_XDONE), 0);
      wait_count_ge(&g_kvcnt[p][0], 64u * tag);
      const float* kvp = &g_kv[par][8 * p][0][0];
      const float* zp = &g_z[par][8 * p][0];
      const uint32_t dst0 = sbase + 5 * 8192, dst1 = dst0 + 65536;
#pragma unroll
      for (int h2 = 0; h2 < 2; h2++) {
        float4 v[3];
#pragma unroll
        for (int i = 0; i < 3; i++) {
          const int c = (h2 * 3 + i) * 96 + hl;
          v[i] = c < 512 ? ldg_cg_f4(kvp + c * 4) : (c < 544 ? ldg_cg_f4(zp + (c - 512) * 4) : make_float4(0.f, 0.f, 0.f, 0.f));
        }
#pragma unroll
        for (int i = 0; i < 3; i++) {
          const int c = (h2 * 3 + i) * 96 + hl;
          if (c < 512) {
            const int h = c >> 6, d = (c >> 2) & 15, e = (c & 3) * 4;
            const uint32_t off = h * 768 + ((e >> 3) * 2 + (d >> 3)) * 128 + (d & 7) * 16 + (e & 7) * 2;
            const uint32_t lo = pack_bf16(v[i].x, v[i].y), hi = pack_bf16(v[i].z, v[i].w);
            asm volatile("st.shared.v2.u32 [%0], {%1,%2};" ::"r"(dst0 + off), "r"(lo), "r"(hi) : "memory");
            asm volatile("st.shared.v2.u32 [%0], {%1,%2};" ::"r"(dst1 + off), "r"(lo), "r"(hi) : "memory");
          } else if (c < 544) {
            const int h = (c - 512) >> 2, d = ((c - 512) & 3) * 4;
            const uint32_t off = h * 768 + (4 + (d >> 3)) * 128 + (d & 7) * 16;
            const float zz[4] = {v[i].x, v[i].y, v[i].z, v[i].w};
#pragma unroll
            for (int q = 0; q < 4; q++) {
              const uint32_t zq = pack_bf16(zz[q], zz[q]);
              sts_u4(dst0 + off + q * 16, zq, zq, zq, zq);
              sts_u4(dst1 + off + q * 16, zq, zq, zq, zq);
            }
          }
        }
      }
      fence_proxy_async();
      __syncwarp();
      if (lane == 0) mbar_arrive(BAR(B_KVREADY));
    }
  } else {
    asm volatile("setmaxnreg.inc.sync.aligned.u32 240;");
    const int w = warp >> 2, wq = warp & 3, t128 = tid & 127;
    const int g = lane >> 2, tq = lane & 3;
    const uint32_t area = sbase + (uint32_t)w * 65536u;
    const bool elect = (t128 == 0);
    PROF(w, 22);
    const uint32_t dbase = (sbase & 0x3FFFFu) >> 4;
    uint32_t xoff = (uint32_t)((m * 4 + p) * 18 + w) * 8192u + (uint32_t)t128 * 16u;
    uint32_t stash = area + (uint32_t)t128 * 16u;
    const uint32_t epoch_c = ld_relaxed(&g_epoch);
    auto xptr = [&](int slot, int jj) INL { return (uint4*)((char*)g_xbuf + ((xoff & ~1u) + (uint32_t)slot * 16384u + (uint32_t)jj * 2048u)); };
    uint32_t A[144];
    float rs0 = 0.f, rs1 = 0.f;
    auto release = [&](int st) INL {
      if (elect) { mbar_arrive_cluster(BAR(B_EMPTY + st), 0); mbar_arrive_cluster(BAR(B_EMPTY + st), 1); }
    };

    asm volatile("" : "+r"(xoff), "+r"(stash));
    cluster_wait();

    auto gu_chunk = [&](float (&acc)[32], int f, int slot, int xslot, int hb) INL {
      const float c0 = rs0 * -1.4426950408889634f, c1 = rs1 * -1.4426950408889634f;
      const float q0 = rs0 * rs0, q1 = rs1 * rs1;
      uint32_t h[4];
#pragma unroll
      for (int i = 0; i < 4; i++) {
        const float ga = acc[f * 8 + 2 * i], gb = acc[f * 8 + 2 * i + 1];
        const float ua = acc[16 + f * 8 + 2 * i], ub = acc[16 + f * 8 + 2 * i + 1];
        const float c = (i & 1) ? c1 : c0, q = (i & 1) ? q1 : q0;
        const float da = 1.f + ex2f(fminf(ga * c, 60.f)), db = 1.f + ex2f(fminf(gb * c, 60.f));
        const float rq = rcpf(da * db) * q;
        h[i] = tagged(pack_bf16(ga * ua * (db * rq), gb * ub * (da * rq)), xoff & 1u);
      }
      const int jj = hb * 2 + f;
      sts_u4(stash + slot * 8192 + jj * 2048, h[0], h[1], h[2], h[3]);
      stg_u4(xptr(xslot, jj), h[0], h[1], h[2], h[3]);
    };
    auto kv_stage = [&](float (&acc)[32], int c, int hb) INL {
      const int srow = wq * 16 + (lane & 7) + ((lane >> 3) & 1) * 8;
      const uint32_t base = area + (3 + c) * 8192 + srow * 128;
#pragma unroll
      for (int jj = 0; jj < 2; jj++) {
        const int a = c * 16 + jj * 8;
        uint32_t r0, r1, r2, r3;
        if (c == 0) {
          r0 = pack_bf16(phi_f(acc[a] * rs0), phi_f(acc[a + 1] * rs0));
          r1 = pack_bf16(phi_f(acc[a + 2] * rs1), phi_f(acc[a + 3] * rs1));
          r2 = pack_bf16(phi_f(acc[a + 4] * rs0), phi_f(acc[a + 5] * rs0));
          r3 = pack_bf16(phi_f(acc[a + 6] * rs1), phi_f(acc[a + 7] * rs1));
        } else {
          r0 = pack_bf16(acc[a] * rs0, acc[a + 1] * rs0);
          r1 = pack_bf16(acc[a + 2] * rs1, acc[a + 3] * rs1);
          r2 = pack_bf16(acc[a + 4] * rs0, acc[a + 5] * rs0);
          r3 = pack_bf16(acc[a + 6] * rs1, acc[a + 7] * rs1);
        }
        stmatrix_x4(base + (((hb * 4 + jj * 2 + (lane >> 4)) ^ (srow & 7)) << 4), r0, r1, r2, r3);
      }
    };
    auto signal = [&](int e) INL {
      __syncwarp();
      if (lane == 0) mbar_arrive(BAR(B_EV + w * 2 + e));
    };

    auto pp_wait = [&]() INL { bar_sync(3 + w, 256); };
    auto pp_pass = [&]() INL { bar_arrive(3 + (w ^ 1), 256); };
    if (w == 1) pp_pass();
    {
      float acc[32];
          const int row = wq * 16 + (lane & 7) + ((lane >> 3) & 1) * 8;
          const uint32_t rbase = area + row * 128;
          float s0[4] = {}, q0[4] = {}, q1[4] = {};
          const uint32_t ones = 0x3F803F80u;
          const uint32_t csb = bars + 512 + tq * 8;
          if (w == 0) {
            static_for<4>([&](auto kc) INL {
              constexpr int kq = decltype(kc)::value;
              mbar_wait(BAR(B_FULL + kq), 0);
              wgmma_fence();
              static_for<8>([&](auto kkc) INL {
                constexpr int kk = decltype(kkc)::value;
                wgmma_n64_rs<CB, (kq | kk) != 0, desc_lo(stage_off(kq) + kk * 1024, 8192), kHi64>(acc, ones, ones, ones, ones, dbase);
              });
              wgmma_commit();
            });
            wgmma_wait<0>();
            if (t128 < 4) {
#pragma unroll
              for (int j = 0; j < 8; j++) asm volatile("st.shared.v2.f32 [%0], {%1,%2};" ::"r"(csb + j * 32), "f"(acc[4 * j]), "f"(acc[4 * j + 1]) : "memory");
            }
            __syncwarp();
            if (elect) mbar_arrive(BAR(B_CS));
          }
          static_for<4>([&](auto kc) INL {
            constexpr int kq = decltype(kc)::value;
#pragma unroll
            for (int b = 2 * kq; b < 2 * kq + 2; b++) {
              mbar_wait(BAR(B_XFULL + w * 8 + b), 0);
              if (b == 0) PROF(w, 23);
              if (b == 7) PROF(w, 24);
#pragma unroll
              for (int kk = 0; kk < 4; kk++) {
                const int i = (b * 4 + kk) * 4;
                ldmatrix_x4(rbase + b * 8192 + (((kk * 2 + (lane >> 4)) ^ (row & 7)) << 4), A[i], A[i + 1], A[i + 2], A[i + 3]);
              }
#pragma unroll
              for (int kk = 0; kk < 4; kk++) {
                const int i = (b * 4 + kk) * 4;
                mma_16816(s0, A[i], A[i + 1], A[i + 2], A[i + 3], ones, ones);
                mma_16816(q0, A[i], A[i + 1], A[i + 2], A[i + 3], A[i], A[i + 2]);
                mma_16816(q1, A[i], A[i + 1], A[i + 2], A[i + 3], A[i + 1], A[i + 3]);
              }
            }
            asm volatile("" : "+f"(s0[0]), "+f"(q0[0]), "+f"(q1[0]));
            mbar_wait(BAR(B_FULL + kq), 0);
            wgmma_fence();
            static_for<8>([&](auto kkc) INL {
              constexpr int kk = decltype(kkc)::value, i = (kq * 8 + kk) * 4;
              wgmma_n64_rs<CB, (kq | kk) != 0, desc_lo(stage_off(kq) + kk * 1024, 8192), kHi64>(acc, A[i], A[i + 1], A[i + 2], A[i + 3], dbase);
            });
            wgmma_commit();
            if (kq > 0) {
              wgmma_wait<1>();
              release(kq - 1);
            }
          });
          bar_sync(1 + w, 128);
          release(6); release(7);
          if (elect) mbar_arrive(BAR(B_XDONE));
          const float mean0 = s0[0] * (1.f / 512.f), mean1 = s0[2] * (1.f / 512.f);
          float v0 = (g & 1) ? q0[1] : q0[0];
          float v1 = (g & 1) ? q1[3] : q1[2];
          const int src = 4 * g + (g >> 1);
          v0 = __shfl_sync(0xffffffffu, v0, src);
          v1 = __shfl_sync(0xffffffffu, v1, src);
          v0 = fmaxf(v0 * (1.f / 512.f) - mean0 * mean0, 0.f);
          v1 = fmaxf(v1 * (1.f / 512.f) - mean1 * mean1, 0.f);
          rs0 = rsqrtf(v0 + 1e-5f);
          rs1 = rsqrtf(v1 + 1e-5f);
          wgmma_wait<0>();
          release(3);
          const uint32_t m0 = pack_bf16(mean0, mean0), m1 = pack_bf16(mean1, mean1);
#pragma unroll
          for (int i = 0; i < 128; i += 2) {
            A[i] = hsub2_bf16(A[i], m0);
            A[i + 1] = hsub2_bf16(A[i + 1], m1);
          }
          mbar_wait(BAR(B_CS), 0);
#pragma unroll
          for (int j = 0; j < 8; j++) {
            float c0, c1;
            asm volatile("ld.shared.v2.f32 {%0,%1}, [%2];" : "=f"(c0), "=f"(c1) : "r"(csb + j * 32) : "memory");
            acc[4 * j] = fmaf(-mean0, c0, acc[4 * j]);
            acc[4 * j + 1] = fmaf(-mean0, c1, acc[4 * j + 1]);
            acc[4 * j + 2] = fmaf(-mean1, c0, acc[4 * j + 2]);
            acc[4 * j + 3] = fmaf(-mean1, c1, acc[4 * j + 3]);
          }
          PROF(w, 0);
      xoff |= (epoch_c & 1u) ^ 1u;
      if (!odd) {
        gu_chunk(acc, 0, 0, 0, 0);
        gu_chunk(acc, 1, 0, 0, 0);
      } else {
        sts_u4(stash + 5 * 8192, 0x3F803F80u, 0x3F803F80u, 0x3F803F80u, 0x3F803F80u);
        kv_stage(acc, 0, 0);
        kv_stage(acc, 1, 0);
      }
    }
#pragma unroll 1
    for (int t = 0; t < 5; t++) {
      const uint32_t ph = t & 1;
      const int kind = odd ? (t < 2 ? K_KV : K_GU) : (t < 4 ? K_GU : K_Q);
      const int slot = odd ? t - 2 : t, xslot = odd ? t + 4 : t;
      static_for<2>([&](auto hc) INL {
        constexpr int hb = decltype(hc)::value;
        float acc[32];
        if (hb == 0 && t == 0) return;
        {
          pp_wait();
          static_for<4>([&](auto kc) INL {
            constexpr int kq = decltype(kc)::value, k = hb * 4 + kq;
            mbar_wait(BAR(B_FULL + k), ph);
            wgmma_fence();
            static_for<8>([&](auto kkc) INL {
              constexpr int kk = decltype(kkc)::value, i = (kq * 8 + kk) * 4;
              wgmma_n64_rs<CB, (kq | kk) != 0, desc_lo(stage_off(k) + kk * 1024, 8192), kHi64>(acc, A[i], A[i + 1], A[i + 2], A[i + 3], dbase);
            });
            wgmma_commit();
            if (kq == PPOS) pp_pass();
            if (kq > 0) {
              wgmma_wait<1>();
              release(k - 1);
            }
          });
          wgmma_wait<0>();
          release(hb * 4 + 3);
        }
        if (kind == K_GU) {
          gu_chunk(acc, 0, slot, xslot, hb);
          gu_chunk(acc, 1, slot, xslot, hb);
        } else if (kind == K_KV) {
          kv_stage(acc, 0, hb);
          kv_stage(acc, 1, hb);
          if (hb == 1) {
            float kvacc[36];
            const int par = (xoff & 1u) ^ 1u;
            fence_proxy_async();
            bar_sync(1 + w, 128);
            wgmma_fence();
            static_for<4>([&](auto kkc) INL {
              constexpr int kk = decltype(kkc)::value;
              wgmma_n72_ss_tt<kk != 0, desc_lo(3 * 8192 + kk * 2048, 0), desc_lo(4 * 8192 + kk * 2048, 8192 - kk * 2048)>(kvacc, dbase + w * 4096);
            });
            wgmma_commit();
            wgmma_wait<0>();
            float c[8];
#pragma unroll
            for (int i = 0; i < 8; i++)
              c[i] = wq == 0 ? kvacc[i] : (wq == 1 ? kvacc[8 + i] : (wq == 2 ? kvacc[16 + i] : kvacc[24 + i]));
            const int head = (2 * p + t) * 4 + wq;
            float* kvp = &g_kv[par][head][0][0];
            red_add_v2(kvp + g * 16 + 2 * tq, c[0], c[1]);
            red_add_v2(kvp + (g + 8) * 16 + 2 * tq, c[2], c[3]);
            red_add_v2(kvp + g * 16 + 8 + 2 * tq, c[4], c[5]);
            red_add_v2(kvp + (g + 8) * 16 + 8 + 2 * tq, c[6], c[7]);
            if (tq == 0) {
              red_add(&g_z[par][head][g], kvacc[32]);
              red_add(&g_z[par][head][g + 8], kvacc[34]);
            }
            signal(t);
          }
        } else {
          uint32_t aq[4][4];
#pragma unroll
          for (int c = 0; c < 4; c++) {
            const int a = c * 8;
            aq[c][0] = pack_bf16(phi_f(acc[a] * rs0), phi_f(acc[a + 1] * rs0));
            aq[c][1] = pack_bf16(phi_f(acc[a + 2] * rs1), phi_f(acc[a + 3] * rs1));
            aq[c][2] = pack_bf16(phi_f(acc[a + 4] * rs0), phi_f(acc[a + 5] * rs0));
            aq[c][3] = pack_bf16(phi_f(acc[a + 6] * rs1), phi_f(acc[a + 7] * rs1));
          }
          if (hb == 0) mbar_wait(BAR(B_KVREADY), 0);
          float nd[4][12];
          wgmma_fence();
          static_for<4>([&](auto cc) INL {
            constexpr int c = decltype(cc)::value;
            wgmma_n24_rs<desc_lo(5 * 8192 + (hb * 4 + c) * 768, 128)>(nd[c], aq[c][0], aq[c][1], aq[c][2], aq[c][3], dbase + w * 4096);
          });
          wgmma_commit();
          wgmma_wait<0>();
          if (hb == 1) bar_sync(1 + w, 128);
          const uint32_t tg = xoff & 1u;
#pragma unroll
          for (int c = 0; c < 4; c++) {
            const float i0 = __fdividef(1.f, nd[c][8] + 1e-6f), i1 = __fdividef(1.f, nd[c][10] + 1e-6f);
            aq[c][0] = tagged(pack_bf16(nd[c][0] * i0, nd[c][1] * i0), tg);
            aq[c][1] = tagged(pack_bf16(nd[c][2] * i1, nd[c][3] * i1), tg);
            aq[c][2] = tagged(pack_bf16(nd[c][4] * i0, nd[c][5] * i0), tg);
            aq[c][3] = tagged(pack_bf16(nd[c][6] * i1, nd[c][7] * i1), tg);
          }
#pragma unroll
          for (int c = 0; c < 4; c++) {
            stg_u4(xptr(4 + hb, c), aq[c][0], aq[c][1], aq[c][2], aq[c][3]);
            sts_u4(stash + (4 + hb) * 8192 + c * 2048, aq[c][0], aq[c][1], aq[c][2], aq[c][3]);
          }
        }
      });
      PROF(w, 1 + 2 * t);
    }
    PROF(w, 10);

    const int n_own = odd ? 3 : 6;
    auto load_a = [&](int kb) INL {
      if (kb < n_own) {
#pragma unroll
        for (int jj = 0; jj < 4; jj++) {
          const int i = (kb * 4 + jj) * 4;
          lds_u4(stash + kb * 8192 + jj * 2048, A[i], A[i + 1], A[i + 2], A[i + 3]);
        }
      } else {
        const int xs = odd ? kb - 3 : kb;
#pragma unroll
        for (int jj = 0; jj < 4; jj++) {
          const int i = (kb * 4 + jj) * 4;
          ldg_poll_u4(xptr(xs, jj), A[i], A[i + 1], A[i + 2], A[i + 3]);
        }
      }
    };
    auto fix_a = [&](int kb) INL {
      if (kb >= n_own) {
        const int xs = odd ? kb - 3 : kb;
        recv_group<4>(xptr(xs, 0), &A[kb * 16], xoff & 1u);
      }
    };
#pragma unroll
    for (int kb = 0; kb < 7; kb++) load_a(kb);
    PROF(w, 11);

    const uint32_t ooff = (uint32_t)(m * 128 + w * 64 + wq * 16 + (lane >> 3)) * kD + odd * 256 + p * 64 + (lane & 7) * 8;
    float acc2[2][32];
    uint32_t poff = (uint32_t)((m * 2 + odd) * 24 + w) * 8192u + (uint32_t)t128 * 16u;
    asm volatile("" : "+r"(poff));
    auto pptr = [&](int dest, int sl) INL { return (uint4*)((char*)g_pbuf + (poff + (uint32_t)(dest * 3 + sl) * 16384u)); };
    uint32_t P[3][16];
    uint4 xr[4];
    auto send = [&](float (&acc)[32], int bi) INL {
      uint4* dst = pptr((p + 1 + bi) & 3, bi);
#pragma unroll
      for (int q = 0; q < 4; q++)
        stg_u4(dst + q * 128, tagged(pack_bf16(acc[q * 8], acc[q * 8 + 1]), xoff & 1u), tagged(pack_bf16(acc[q * 8 + 2], acc[q * 8 + 3]), xoff & 1u),
               tagged(pack_bf16(acc[q * 8 + 4], acc[q * 8 + 5]), xoff & 1u), tagged(pack_bf16(acc[q * 8 + 6], acc[q * 8 + 7]), xoff & 1u));
      PROF(w, 12 + 2 * bi);
    };
    auto fetch = [&](int sl) INL {
#pragma unroll
      for (int q = 0; q < 4; q++)
        asm volatile("cp.async.cg.shared.global [%0], [%1], 16;" ::"r"(stash + (3 + sl) * 8192 + q * 2048), "l"(pptr(p, sl) + q * 128) : "memory");
    };
    auto collect = [&](int sl) INL {
      asm volatile("cp.async.wait_all;" ::: "memory");
#pragma unroll
      for (int q = 0; q < 4; q++) lds_u4(stash + (3 + sl) * 8192 + q * 2048, P[sl][q * 4], P[sl][q * 4 + 1], P[sl][q * 4 + 2], P[sl][q * 4 + 3]);
      recv_group<4>(pptr(p, sl), &P[sl][0], xoff & 1u);
    };
    static_for<36>([&](auto ic) INL {
      constexpr int i = decltype(ic)::value, bi = p2_bi(i), kb = p2_kb(i), j = i >> 1, st = j & 7;
      if (i == 9) { load_a(7); load_a(8); }
      if (i == 14) PROF(w, 2);
      if (bi == 0 && kb >= 3) fix_a(kb);
      if (i == 15) PROF(w, 4);
      if (i == 7) PROF(w, 6);
      if (i == 0 || i == 7 || i == 14 || i == 18 || i == 27) pp_wait();
      if ((i & 1) == 0) mbar_wait(BAR(B_FULL + st), (5 + (j >> 3)) & 1);
      wgmma_fence();
      static_for<4>([&](auto kkc) INL {
        constexpr int kk = decltype(kkc)::value, a = (kb * 4 + kk) * 4;
        wgmma_n64_rs<CB, (kb | kk) != 0, desc_lo(stage_off(st) + (i & 1) * 8192 + kk * 2048, 0), kHi128>(acc2[bi & 1], A[a], A[a + 1], A[a + 2], A[a + 3], dbase);
      });
      wgmma_commit();
      if (i == 4 || i == 11 || i == 15 || i == 24 || (i == 33 && w == 0)) pp_pass();
      if (i > 0) {
        wgmma_wait<1>();
        if ((i & 1) == 0 && j - 1 <= 9) release((j - 1) & 7);
      }
      if constexpr (i == 17) { send(acc2[0], 0); wgmma_wait<0>(); send(acc2[1], 1); }
      if constexpr (i == 26) { wgmma_wait<0>(); send(acc2[0], 2); }
      if constexpr (i == 28) {
#pragma unroll
        for (int q = 0; q < 4; q++) xr[q] = __ldg((const uint4*)(x + ooff + q * 4 * kD));
      }
      if constexpr (i == 27) { fetch(0); fetch(1); }
      if constexpr (i == FPOS) fetch(2);
    });
    PROF(w, 17);
    collect(0);
    collect(1);
#pragma unroll
    for (int q = 0; q < 16; q++) {
      acc2[0][2 * q] = __uint_as_float(P[0][q] << 16) + __uint_as_float(P[1][q] << 16);
      acc2[0][2 * q + 1] = __uint_as_float(P[0][q] & 0xffff0000u) + __uint_as_float(P[1][q] & 0xffff0000u);
    }
    PROF(w, 13);
    collect(2);
    PROF(w, 15);
    wgmma_wait<0>();
    PROF(w, 18);
    {
      const uint32_t tile = area + wq * 4352;
#pragma unroll
      for (int q = 0; q < 8; q++) {
        float rr[4];
#pragma unroll
        for (int e = 0; e < 4; e++) rr[e] = acc2[1][q * 4 + e] + acc2[0][q * 4 + e];
        rr[0] += __uint_as_float(P[2][2 * q] << 16);
        rr[1] += __uint_as_float(P[2][2 * q] & 0xffff0000u);
        rr[2] += __uint_as_float(P[2][2 * q + 1] << 16);
        rr[3] += __uint_as_float(P[2][2 * q + 1] & 0xffff0000u);
        const uint32_t ad = tile + g * 272 + q * 32 + tq * 8;
        asm volatile("st.shared.v2.f32 [%0], {%1,%2};" ::"r"(ad), "f"(rr[0]), "f"(rr[1]) : "memory");
        asm volatile("st.shared.v2.f32 [%0], {%1,%2};" ::"r"(ad + 8 * 272), "f"(rr[2]), "f"(rr[3]) : "memory");
      }
      __syncwarp();
#pragma unroll
      for (int q = 0; q < 4; q++) {
        const uint32_t ad = tile + ((lane >> 3) + 4 * q) * 272 + (lane & 7) * 32;
        uint32_t v[8];
        lds_u4(ad, v[0], v[1], v[2], v[3]);
        lds_u4(ad + 16, v[4], v[5], v[6], v[7]);
        const uint32_t xv[4] = {xr[q].x, xr[q].y, xr[q].z, xr[q].w};
        uint32_t o[4];
#pragma unroll
        for (int e = 0; e < 4; e++)
          o[e] = pack_bf16(__uint_as_float(v[2 * e]) + __uint_as_float(xv[e] << 16), __uint_as_float(v[2 * e + 1]) + __uint_as_float(xv[e] & 0xffff0000u));
        stg_u4(out + ooff + q * 4 * kD, o[0], o[1], o[2], o[3]);
      }
    }
    PROF(w, 19);
    if (tid == 0) {
      const uint32_t old = atomicAdd(&g_done, 1u);
      if ((old & 127u) == 127u) st_relaxed(&g_epoch, ld_relaxed(&g_epoch) + 1u);
    }
  }
#undef BAR
}

typedef CUresult (*EncodeFn)(CUtensorMap*, CUtensorMapDataType, cuuint32_t, void*, const cuuint64_t*, const cuuint64_t*,
                             const cuuint32_t*, const cuuint32_t*, CUtensorMapInterleave, CUtensorMapSwizzle,
                             CUtensorMapL2promotion, CUtensorMapFloatOOBfill);

void make_map(EncodeFn enc, CUtensorMap* tm, const void* ptr, int rows, int cols, bool narrow) {
  cuuint64_t gd[2] = {(cuuint64_t)cols, (cuuint64_t)rows};
  cuuint64_t gs[1] = {(cuuint64_t)cols * 2};
  cuuint32_t bd[2] = {narrow ? 32u : 64u, narrow ? 128u : 64u};
  cuuint32_t es[2] = {1, 1};
  enc(tm, CU_TENSOR_MAP_DATA_TYPE_BFLOAT16, 2, const_cast<void*>(ptr), gd, gs, bd, es, CU_TENSOR_MAP_INTERLEAVE_NONE,
      narrow ? CU_TENSOR_MAP_SWIZZLE_64B : CU_TENSOR_MAP_SWIZZLE_128B, CU_TENSOR_MAP_L2_PROMOTION_L2_256B, CU_TENSOR_MAP_FLOAT_OOB_FILL_NONE);
}

}

extern "C" void kernel_launch(void* const* d_in, const int* in_sizes, int n_in, void* d_out, int out_size) {
  static EncodeFn enc = nullptr;
  static bool const_base = false;
  if (!enc) {
    void* fn = nullptr;
    cudaDriverEntryPointQueryResult qr;
    cudaGetDriverEntryPoint("cuTensorMapEncodeTiled", &fn, cudaEnableDefault, &qr);
    enc = (EncodeFn)fn;
    cudaFuncSetAttribute(fused_kernel<true>, cudaFuncAttributeMaxDynamicSharedMemorySize, kSmemBytes);
    cudaFuncSetAttribute(fused_kernel<false>, cudaFuncAttributeMaxDynamicSharedMemorySize, kSmemBytes);
    int dev = 0, reserved = 0;
    cudaFuncAttributes fa;
    cudaGetDevice(&dev);
    cudaDeviceGetAttribute(&reserved, cudaDevAttrReservedSharedMemoryPerBlock, dev);
    const_base = cudaFuncGetAttributes(&fa, fused_kernel<true>) == cudaSuccess && fa.sharedSizeBytes == 0 && reserved == (int)kSmemBase;
  }
  CUtensorMap tm_x, tm_wqkv, tm_w1, tm_w3, tm_w2, tm_wo;
  make_map(enc, &tm_x, d_in[0], kS, kD, false);
  make_map(enc, &tm_wqkv, d_in[1], kD, 3 * kD, true);
  make_map(enc, &tm_wo, d_in[2], kD, kD, false);
  make_map(enc, &tm_w1, d_in[4], kD, kF, true);
  make_map(enc, &tm_w3, d_in[5], kD, kF, true);
  make_map(enc, &tm_w2, d_in[6], kF, kD, false);
  if (const_base)
    fused_kernel<true><<<128, 384, kSmemBytes>>>(tm_x, tm_wqkv, tm_w1, tm_w3, tm_w2, tm_wo, (const __nv_bfloat16*)d_in[0], (__nv_bfloat16*)d_out);
  else
    fused_kernel<false><<<128, 384, kSmemBytes>>>(tm_x, tm_wqkv, tm_w1, tm_w3, tm_w2, tm_wo, (const __nv_bfloat16*)d_in[0], (__nv_bfloat16*)d_out);
}
```

```cpp
#include <cuda_runtime.h>
#include <cuda_bf16.h>
#include <cuda.h>
#include <stdint.h>

extern __shared__ __align__(1024) uint8_t smem_raw[];

namespace {

constexpr int kS = 2048, kD = 512, kF = 1792;
constexpr uint32_t kSpinLimit = 1u << 22;
constexpr int PPOS = 28, QPOS = 2, FPOS = 33;

__device__ uint4    g_xbuf[16][4][9][2][4][128];
__device__ uint4    g_pbuf[16][2][4][3][2][4][128];
__device__ float    g_kv[2][32][16][16];
__device__ float    g_z[2][32][16];
__device__ uint32_t g_kvcnt[4][32];
__device__ uint32_t g_epoch;
__device__ uint32_t g_done;
#define PROF(wg, i) do {} while (0)

__device__ __forceinline__ uint32_t smem_u32(const void* p) { return (uint32_t)__cvta_generic_to_shared(p); }
__device__ __forceinline__ void mbar_init(uint32_t bar, uint32_t cnt) {
  asm volatile("mbarrier.init.shared::cta.b64 [%0], %1;" ::"r"(bar), "r"(cnt) : "memory");
}
__device__ __forceinline__ void mbar_expect_tx(uint32_t bar, uint32_t bytes) {
  asm volatile("mbarrier.arrive.expect_tx.shared::cta.b64 _, [%0], %1;" ::"r"(bar), "r"(bytes) : "memory");
}
__device__ __forceinline__ void mbar_arrive(uint32_t bar) {
  asm volatile("mbarrier.arrive.shared::cta.b64 _, [%0];" ::"r"(bar) : "memory");
}
__device__ __forceinline__ void mbar_wait(uint32_t bar, uint32_t parity) {
  asm volatile(
      "{\n.reg .pred p;\n"
      "LAB_WAIT:\n"
      "mbarrier.try_wait.parity.shared::cta.b64 p, [%0], %1;\n"
      "@p bra DONE;\n"
      "bra LAB_WAIT;\n"
      "DONE:\n}" ::"r"(bar), "r"(parity) : "memory");
}
__device__ __forceinline__ void tma_load_2d(uint32_t dst, const CUtensorMap* tm, uint32_t bar, int c0, int c1) {
  asm volatile(
      "cp.async.bulk.tensor.2d.shared::cluster.global.mbarrier::complete_tx::bytes [%0], [%1, {%3, %4}], [%2];" ::"r"(dst),
      "l"(tm), "r"(bar), "r"(c0), "r"(c1)
      : "memory");
}
__device__ __forceinline__ void tma_load_2d_mc(uint32_t dst, const CUtensorMap* tm, uint32_t bar, int c0, int c1) {
  asm volatile(
      "cp.async.bulk.tensor.2d.shared::cluster.global.mbarrier::complete_tx::bytes.multicast::cluster [%0], [%1, {%3, %4}], [%2], %5;" ::"r"(dst),
      "l"(tm), "r"(bar), "r"(c0), "r"(c1), "h"((uint16_t)3)
      : "memory");
}
__device__ __forceinline__ void mbar_arrive_cluster(uint32_t bar, uint32_t cta) {
  asm volatile("{\n.reg .b32 ra;\nmapa.shared::cluster.u32 ra, %0, %1;\nmbarrier.arrive.shared::cluster.b64 _, [ra];\n}" ::"r"(bar), "r"(cta) : "memory");
}
__device__ __forceinline__ void prefetch_tmap(const CUtensorMap* tm) {
  asm volatile("prefetch.tensormap [%0];" ::"l"(tm) : "memory");
}
__device__ __forceinline__ void wgmma_fence() { asm volatile("wgmma.fence.sync.aligned;" ::: "memory"); }
__device__ __forceinline__ void wgmma_commit() { asm volatile("wgmma.commit_group.sync.aligned;" ::: "memory"); }
template <int N>
__device__ __forceinline__ void wgmma_wait() { asm volatile("wgmma.wait_group.sync.aligned %0;" ::"n"(N) : "memory"); }
__device__ __forceinline__ void bar_sync(int id, int n) { asm volatile("bar.sync %0, %1;" ::"r"(id), "r"(n) : "memory"); }
__device__ __forceinline__ void bar_arrive(int id, int n) { asm volatile("bar.arrive %0, %1;" ::"r"(id), "r"(n) : "memory"); }
__device__ __forceinline__ void fence_proxy_async() { asm volatile("fence.proxy.async.shared::cta;" ::: "memory"); }

__device__ __forceinline__ uint32_t ld_acquire(const uint32_t* p) {
  uint32_t v;
  asm volatile("ld.acquire.gpu.global.u32 %0, [%1];" : "=r"(v) : "l"(p) : "memory");
  return v;
}
__device__ __forceinline__ uint32_t ld_relaxed(const uint32_t* p) {
  uint32_t v;
  asm volatile("ld.relaxed.gpu.global.u32 %0, [%1];" : "=r"(v) : "l"(p));
  return v;
}
__device__ __forceinline__ void cluster_wait() { asm volatile("barrier.cluster.wait.aligned;" ::: "memory"); }
__device__ __forceinline__ void st_relaxed(uint32_t* p, uint32_t v) {
  asm volatile("st.relaxed.gpu.global.u32 [%0], %1;" ::"l"(p), "r"(v) : "memory");
}
__device__ __forceinline__ void wait_count_ge(const uint32_t* p, uint32_t val) {
  uint32_t it = 0;
  while ((int32_t)(ld_acquire(p) - val) < 0) {
    __nanosleep(64);
    if (++it > kSpinLimit) break;
  }
}
__device__ __forceinline__ void ldg_poll_u4(const void* p, uint32_t& a, uint32_t& b, uint32_t& c, uint32_t& d) {
  asm volatile("ld.relaxed.gpu.global.v4.u32 {%0,%1,%2,%3}, [%4];" : "=r"(a), "=r"(b), "=r"(c), "=r"(d) : "l"(p) : "memory");
}
template <int N>
__device__ __forceinline__ void recv_group(const uint4* p, uint32_t* r, uint32_t tag) {
  uint32_t it = 0;
  while (true) {
    uint32_t bad = 0u;
#pragma unroll
    for (int i = 0; i < 4 * N; i++) bad |= r[i] ^ tag;
    if (!__any_sync(0xffffffffu, (bad & 1u) != 0u) || ++it > kSpinLimit) break;
#pragma unroll
    for (int q = 0; q < N; q++) ldg_poll_u4(p + q * 128, r[q * 4], r[q * 4 + 1], r[q * 4 + 2], r[q * 4 + 3]);
  }
}
__device__ __forceinline__ uint32_t tagged(uint32_t v, uint32_t tag) { return (v & ~1u) | tag; }
__device__ __forceinline__ float4 ldg_cg_f4(const void* p) {
  float4 v;
  asm volatile("ld.global.cg.v4.f32 {%0,%1,%2,%3}, [%4];" : "=f"(v.x), "=f"(v.y), "=f"(v.z), "=f"(v.w) : "l"(p) : "memory");
  return v;
}
__device__ __forceinline__ void stg_u4(void* p, uint32_t a, uint32_t b, uint32_t c, uint32_t d) {
  asm volatile("st.global.v4.u32 [%0], {%1,%2,%3,%4};" ::"l"(p), "r"(a), "r"(b), "r"(c), "r"(d) : "memory");
}
__device__ __forceinline__ void sts_u4(uint32_t addr, uint32_t a, uint32_t b, uint32_t c, uint32_t d) {
  asm volatile("st.shared.v4.u32 [%0], {%1,%2,%3,%4};" ::"r"(addr), "r"(a), "r"(b), "r"(c), "r"(d) : "memory");
}
__device__ __forceinline__ void lds_u4(uint32_t addr, uint32_t& a, uint32_t& b, uint32_t& c, uint32_t& d) {
  asm volatile("ld.shared.v4.u32 {%0,%1,%2,%3}, [%4];" : "=r"(a), "=r"(b), "=r"(c), "=r"(d) : "r"(addr) : "memory");
}
__device__ __forceinline__ void ldmatrix_x4(uint32_t addr, uint32_t& a, uint32_t& b, uint32_t& c, uint32_t& d) {
  asm volatile("ldmatrix.sync.aligned.m8n8.x4.shared.b16 {%0,%1,%2,%3}, [%4];" : "=r"(a), "=r"(b), "=r"(c), "=r"(d) : "r"(addr) : "memory");
}
__device__ __forceinline__ void stmatrix_x4(uint32_t addr, uint32_t a, uint32_t b, uint32_t c, uint32_t d) {
  asm volatile("stmatrix.sync.aligned.m8n8.x4.shared.b16 [%0], {%1,%2,%3,%4};" ::"r"(addr), "r"(a), "r"(b), "r"(c), "r"(d) : "memory");
}
__device__ __forceinline__ void mma_16816(float (&c)[4], uint32_t a0, uint32_t a1, uint32_t a2, uint32_t a3, uint32_t b0, uint32_t b1) {
  asm(
      "mma.sync.aligned.m16n8k16.row.col.f32.bf16.bf16.f32 {%0,%1,%2,%3}, {%4,%5,%6,%7}, {%8,%9}, {%0,%1,%2,%3};"
      : "+f"(c[0]), "+f"(c[1]), "+f"(c[2]), "+f"(c[3])
      : "r"(a0), "r"(a1), "r"(a2), "r"(a3), "r"(b0), "r"(b1));
}
__device__ __forceinline__ uint32_t pack_bf16(float lo, float hi) {
  uint32_t r;
  asm("cvt.rn.bf16x2.f32 %0, %1, %2;" : "=r"(r) : "f"(hi), "f"(lo));
  return r;
}
__device__ __forceinline__ uint32_t hsub2_bf16(uint32_t a, uint32_t b) {
  uint32_t r;
  asm("sub.rn.bf16x2 %0, %1, %2;" : "=r"(r) : "r"(a), "r"(b));
  return r;
}
__device__ __forceinline__ float ex2f(float x) {
  float r;
  asm("ex2.approx.ftz.f32 %0, %1;" : "=f"(r) : "f"(x));
  return r;
}
__device__ __forceinline__ float rcpf(float x) {
  float r;
  asm("rcp.approx.ftz.f32 %0, %1;" : "=f"(r) : "f"(x));
  return r;
}
__device__ __forceinline__ void red_add_v2(float* p, float a, float b) {
  asm volatile("red.relaxed.gpu.global.add.v2.f32 [%0], {%1,%2};" ::"l"(p), "f"(a), "f"(b) : "memory");
}
__device__ __forceinline__ void red_add(float* p, float a) {
  asm volatile("red.relaxed.gpu.global.add.f32 [%0], %1;" ::"l"(p), "f"(a) : "memory");
}
__device__ __forceinline__ float phi_f(float t) {
  float e = ex2f(t * 1.4426950408889634f);
  return (t > 0.f ? t + 1.f : e) + 1e-6f;
}

#define R8(a, o) "+f"(a[o + 0]), "+f"(a[o + 1]), "+f"(a[o + 2]), "+f"(a[o + 3]), "+f"(a[o + 4]), "+f"(a[o + 5]), "+f"(a[o + 6]), "+f"(a[o + 7])

#define W8(a, o) "=f"(a[o + 0]), "=f"(a[o + 1]), "=f"(a[o + 2]), "=f"(a[o + 3]), "=f"(a[o + 4]), "=f"(a[o + 5]), "=f"(a[o + 6]), "=f"(a[o + 7])
#define D32 "{%0,%1,%2,%3,%4,%5,%6,%7,%8,%9,%10,%11,%12,%13,%14,%15,%16,%17,%18,%19,%20,%21,%22,%23,%24,%25,%26,%27,%28,%29,%30,%31}"
#define D36 "{%0,%1,%2,%3,%4,%5,%6,%7,%8,%9,%10,%11,%12,%13,%14,%15,%16,%17,%18,%19,%20,%21,%22,%23,%24,%25,%26,%27,%28,%29,%30,%31,%32,%33,%34,%35}"

constexpr uint32_t kHi128 = (1024u >> 4) | (1u << 30);
constexpr uint32_t kHi64 = (512u >> 4) | (2u << 30);
__host__ __device__ constexpr uint32_t desc_lo(uint32_t off, uint32_t lbo) { return (off >> 4) | ((lbo >> 4) << 16); }

constexpr uint32_t kSmemBase = 1024;
template <bool CB, bool ACC, uint32_t LO, uint32_t HI>
__device__ __forceinline__ void wgmma_n64_rs(float (&d)[32], uint32_t a0, uint32_t a1, uint32_t a2, uint32_t a3, uint32_t base) {
  if (CB) {
    if (ACC) {
      asm volatile(
          "{\n.reg .pred p;\n.reg .b64 dd;\nsetp.eq.b32 p, 0, 0;\nmov.b64 dd, {%36, %37};\n"
          "wgmma.mma_async.sync.aligned.m64n64k16.f32.bf16.bf16 " D32 ", {%32,%33,%34,%35}, dd, p, 1, 1, 1;\n}"
          : R8(d, 0), R8(d, 8), R8(d, 16), R8(d, 24)
          : "r"(a0), "r"(a1), "r"(a2), "r"(a3), "n"(LO + (kSmemBase >> 4)), "n"(HI));
    } else {
      asm volatile(
          "{\n.reg .pred p;\n.reg .b64 dd;\nsetp.ne.b32 p, 0, 0;\nmov.b64 dd, {%36, %37};\n"
          "wgmma.mma_async.sync.aligned.m64n64k16.f32.bf16.bf16 " D32 ", {%32,%33,%34,%35}, dd, p, 1, 1, 1;\n}"
          : W8(d, 0), W8(d, 8), W8(d, 16), W8(d, 24)
          : "r"(a0), "r"(a1), "r"(a2), "r"(a3), "n"(LO + (kSmemBase >> 4)), "n"(HI));
    }
  } else {
    if (ACC) {
      asm volatile(
          "{\n.reg .pred p;\n.reg .b32 lo;\n.reg .b64 dd;\nsetp.eq.b32 p, 0, 0;\nadd.u32 lo, %36, %37;\nmov.b64 dd, {lo, %38};\n"
          "wgmma.mma_async.sync.aligned.m64n64k16.f32.bf16.bf16 " D32 ", {%32,%33,%34,%35}, dd, p, 1, 1, 1;\n}"
          : R8(d, 0), R8(d, 8), R8(d, 16), R8(d, 24)
          : "r"(a0), "r"(a1), "r"(a2), "r"(a3), "r"(base), "n"(LO), "n"(HI));
    } else {
      asm volatile(
          "{\n.reg .pred p;\n.reg .b32 lo;\n.reg .b64 dd;\nsetp.ne.b32 p, 0, 0;\nadd.u32 lo, %36, %37;\nmov.b64 dd, {lo, %38};\n"
          "wgmma.mma_async.sync.aligned.m64n64k16.f32.bf16.bf16 " D32 ", {%32,%33,%34,%35}, dd, p, 1, 1, 1;\n}"
          : W8(d, 0), W8(d, 8), W8(d, 16), W8(d, 24)
          : "r"(a0), "r"(a1), "r"(a2), "r"(a3), "r"(base), "n"(LO), "n"(HI));
    }
  }
}
template <bool ACC, uint32_t LOA, uint32_t LOB>
__device__ __forceinline__ void wgmma_n72_ss_tt(float (&d)[36], uint32_t base) {
  if (ACC) {
    asm volatile(
        "{\n.reg .pred p;\n.reg .b32 lo;\n.reg .b64 da, db;\nsetp.eq.b32 p, 0, 0;\n"
        "add.u32 lo, %36, %37;\nmov.b64 da, {lo, %39};\nadd.u32 lo, %36, %38;\nmov.b64 db, {lo, %39};\n"
        "wgmma.mma_async.sync.aligned.m64n72k16.f32.bf16.bf16 " D36 ", da, db, p, 1, 1, 1, 1;\n}"
        : R8(d, 0), R8(d, 8), R8(d, 16), R8(d, 24), "+f"(d[32]), "+f"(d[33]), "+f"(d[34]), "+f"(d[35])
        : "r"(base), "n"(LOA), "n"(LOB), "n"(kHi128));
  } else {
    asm volatile(
        "{\n.reg .pred p;\n.reg .b32 lo;\n.reg .b64 da, db;\nsetp.ne.b32 p, 0, 0;\n"
        "add.u32 lo, %36, %37;\nmov.b64 da, {lo, %39};\nadd.u32 lo, %36, %38;\nmov.b64 db, {lo, %39};\n"
        "wgmma.mma_async.sync.aligned.m64n72k16.f32.bf16.bf16 " D36 ", da, db, p, 1, 1, 1, 1;\n}"
        : W8(d, 0), W8(d, 8), W8(d, 16), W8(d, 24), "=f"(d[32]), "=f"(d[33]), "=f"(d[34]), "=f"(d[35])
        : "r"(base), "n"(LOA), "n"(LOB), "n"(kHi128));
  }
}

#define INL __attribute__((always_inline))
template <uint32_t LO>
__device__ __forceinline__ void wgmma_n24_rs(float (&d)[12], uint32_t a0, uint32_t a1, uint32_t a2, uint32_t a3, uint32_t base) {
  asm volatile(
      "{\n.reg .pred p;\n.reg .b32 lo;\n.reg .b64 dd;\nsetp.ne.b32 p, 0, 0;\nadd.u32 lo, %16, %17;\nmov.b64 dd, {lo, %18};\n"
      "wgmma.mma_async.sync.aligned.m64n24k16.f32.bf16.bf16 {%0,%1,%2,%3,%4,%5,%6,%7,%8,%9,%10,%11}, {%12,%13,%14,%15}, dd, p, 1, 1, 1;\n}"
      : W8(d, 0), "=f"(d[8]), "=f"(d[9]), "=f"(d[10]), "=f"(d[11])
      : "r"(a0), "r"(a1), "r"(a2), "r"(a3), "r"(base), "n"(LO), "n"(256u >> 4));
}

template <int V> struct IC { static constexpr int value = V; };
template <int N, int I = 0, typename F>
__device__ __forceinline__ void static_for(F&& f) {
  if constexpr (I < N) { f(IC<I>{}); static_for<N, I + 1>(f); }
}

__host__ __device__ constexpr uint32_t stage_off(int st) {
  return st < 6 ? 131072u + (uint32_t)st * 16384u : (uint32_t)(st - 6) * 65536u + 49152u;
}

constexpr int B_FULL = 0, B_EMPTY = 8, B_XFULL = 16, B_XDONE = 32, B_KVREADY = 33, B_EV = 34, B_COUNT = 38;
constexpr uint32_t kBarOff = 229376;
constexpr int kSmemBytes = 229376 + 1024;

__host__ __device__ constexpr int p2_bi(int i) { return i < 7 ? 0 : i < 14 ? 1 : i < 16 ? 0 : i < 18 ? 1 : i / 9; }
__host__ __device__ constexpr int p2_kb(int i) { return i < 7 ? i : i < 14 ? i - 7 : i < 16 ? i - 7 : i < 18 ? i - 9 : i % 9; }

enum { K_NONE = 0, K_GU = 1, K_KV = 2, K_Q = 3 };

template <bool CB>
__global__ void __cluster_dims__(2, 1, 1) __launch_bounds__(384, 1)
fused_kernel(const __grid_constant__ CUtensorMap tm_x, const __grid_constant__ CUtensorMap tm_wqkv,
             const __grid_constant__ CUtensorMap tm_w1, const __grid_constant__ CUtensorMap tm_w3,
             const __grid_constant__ CUtensorMap tm_w2, const __grid_constant__ CUtensorMap tm_wo,
             const __nv_bfloat16* __restrict__ x, __nv_bfloat16* __restrict__ out) {
  const uint32_t sbase = smem_u32(smem_raw);
  const uint32_t bars = sbase + kBarOff;
  const int tid = threadIdx.x, lane = tid & 31;
  const int warp = __shfl_sync(0xffffffffu, tid >> 5, 0);
  const int cr = blockIdx.x & 1;
  const int r = (blockIdx.x >> 1) & 7, m = ((blockIdx.x >> 4) << 1) | cr, p = r >> 1, odd = r & 1;
#define BAR(i) (bars + 8u * (uint32_t)(i))
  if (tid == 256) {
    if (CB ? (sbase & 0x3FFFFu) != kSmemBase : (sbase & 1023u) != 0u) __trap();
#pragma unroll
    for (int i = 0; i < 16; i++) mbar_init(BAR(B_XFULL + i), 1);
    fence_proxy_async();
#pragma unroll
    for (int b = 0; b < 16; b++) {
      mbar_expect_tx(BAR(B_XFULL + b), 8192);
      tma_load_2d(sbase + (b >> 3) * 65536 + (b & 7) * 8192, &tm_x, BAR(B_XFULL + b), (b & 7) * 64, m * 128 + (b >> 3) * 64);
    }
#pragma unroll
    for (int i = 0; i < 8; i++) { mbar_init(BAR(B_FULL + i), 1); mbar_init(BAR(B_EMPTY + i), 4); }
#pragma unroll
    for (int i = 0; i < 4; i++) mbar_init(BAR(B_EV + i), 4);
    mbar_init(BAR(B_XDONE), 2);
    mbar_init(BAR(B_KVREADY), 3);
    asm volatile("fence.mbarrier_init.release.cluster;" ::: "memory");
    fence_proxy_async();
  } else if (tid == 288) {
    prefetch_tmap(odd ? &tm_wqkv : (cr ? &tm_w3 : &tm_w1));
  }
  __syncwarp();
  asm volatile("barrier.cluster.arrive.relaxed.aligned;" ::: "memory");
  PROF((tid >> 7), 21);
  __syncthreads();

  if (warp >= 8) {
    asm volatile("setmaxnreg.dec.sync.aligned.u32 24;");
    PROF(2, 3);
    cluster_wait();
    PROF(2, 2);
    const uint32_t epoch = warp == 8 ? 0u : ld_relaxed(&g_epoch);
    const uint32_t tag = epoch + 1u;
    const int par = epoch & 1;
    if (warp == 8) {
      if (lane == 0) {
        for (int j = 0; j < 10; j++) {
          const CUtensorMap* tm;
          int col;
          if (!odd) {
            if (j < 8) { tm = cr ? &tm_w3 : &tm_w1; col = 7 * p * 64 + j * 32; }
            else { tm = &tm_wqkv; col = 128 * p + (j - 8) * 64 + cr * 32; }
          } else {
            if (j < 4) { tm = &tm_wqkv; col = 512 + cr * 512 + 128 * p + j * 32; }
            else { tm = cr ? &tm_w3 : &tm_w1; col = (7 * p + 4) * 64 + (j - 4) * 32; }
          }
          const int t = j >> 1;
          for (int kq = 0; kq < 4; kq++) {
            const int k = (j & 1) * 4 + kq;
            mbar_wait(BAR(B_EMPTY + k), k < 6 ? ((t & 1) ^ 1) : (t & 1));
            mbar_expect_tx(BAR(B_FULL + k), 16384);
            tma_load_2d_mc(sbase + stage_off(k) + cr * 8192, tm, BAR(B_FULL + k), col, kq * 128);
          }
        }
        for (int j = 0; j < 18; j++) {
          const int st = j & 7, n = 5 + (j >> 3);
          const int i = 2 * j + cr;
          const int bi = p2_bi(i), kb = p2_kb(i);
          const int col = odd * 256 + ((p + 1 + bi) & 3) * 64;
          const CUtensorMap* tmk;
          int row;
          if (!odd) {
            if (kb < 4) { tmk = &tm_w2; row = (7 * p + kb) * 64; }
            else if (kb < 6) { tmk = &tm_wo; row = (2 * p + kb - 4) * 64; }
            else { tmk = &tm_w2; row = (7 * p + 4 + kb - 6) * 64; }
          } else {
            if (kb < 3) { tmk = &tm_w2; row = (7 * p + 4 + kb) * 64; }
            else if (kb < 7) { tmk = &tm_w2; row = (7 * p + kb - 3) * 64; }
            else { tmk = &tm_wo; row = (2 * p + kb - 7) * 64; }
          }
          mbar_wait(BAR(B_EMPTY + st), st < 6 ? ((n & 1) ^ 1) : (n & 1));
          mbar_expect_tx(BAR(B_FULL + st), 16384);
          tma_load_2d_mc(sbase + stage_off(st) + cr * 8192, tmk, BAR(B_FULL + st), col, row);
        }
      }
    } else if (odd) {
      if (lane == 0 && warp <= 10) {
        const int w = warp - 9;
        for (int e = 0; e < 2; e++) {
          mbar_wait(BAR(B_EV + w * 2 + e), 0);
          __threadfence();
          atomicAdd(&g_kvcnt[p][0], 1u);
        }
      }
    } else {
      const int hl = tid - 288;
      {
        const int ce = m * 4 + p;
        if (hl < 32) *(float4*)(&g_kv[par ^ 1][0][0][0] + ce * 128 + hl * 4) = make_float4(0.f, 0.f, 0.f, 0.f);
        else if (hl < 40) (&g_z[par ^ 1][0][0])[ce * 8 + hl - 32] = 0.f;
      }
      mbar_wait(BAR(B_XDONE), 0);
      wait_count_ge(&g_kvcnt[p][0], 64u * tag);
      const float* kvp = &g_kv[par][8 * p][0][0];
      const float* zp = &g_z[par][8 * p][0];
      const uint32_t dst0 = sbase + 5 * 8192, dst1 = dst0 + 65536;
#pragma unroll
      for (int h2 = 0; h2 < 2; h2++) {
        float4 v[3];
#pragma unroll
        for (int i = 0; i < 3; i++) {
          const int c = (h2 * 3 + i) * 96 + hl;
          v[i] = c < 512 ? ldg_cg_f4(kvp + c * 4) : (c < 544 ? ldg_cg_f4(zp + (c - 512) * 4) : make_float4(0.f, 0.f, 0.f, 0.f));
        }
#pragma unroll
        for (int i = 0; i < 3; i++) {
          const int c = (h2 * 3 + i) * 96 + hl;
          if (c < 512) {
            const int h = c >> 6, d = (c >> 2) & 15, e = (c & 3) * 4;
            const uint32_t off = h * 768 + ((e >> 3) * 2 + (d >> 3)) * 128 + (d & 7) * 16 + (e & 7) * 2;
            const uint32_t lo = pack_bf16(v[i].x, v[i].y), hi = pack_bf16(v[i].z, v[i].w);
            asm volatile("st.shared.v2.u32 [%0], {%1,%2};" ::"r"(dst0 + off), "r"(lo), "r"(hi) : "memory");
            asm volatile("st.shared.v2.u32 [%0], {%1,%2};" ::"r"(dst1 + off), "r"(lo), "r"(hi) : "memory");
          } else if (c < 544) {
            const int h = (c - 512) >> 2, d = ((c - 512) & 3) * 4;
            const uint32_t off = h * 768 + (4 + (d >> 3)) * 128 + (d & 7) * 16;
            const float zz[4] = {v[i].x, v[i].y, v[i].z, v[i].w};
#pragma unroll
            for (int q = 0; q < 4; q++) {
              const uint32_t zq = pack_bf16(zz[q], zz[q]);
              sts_u4(dst0 + off + q * 16, zq, zq, zq, zq);
              sts_u4(dst1 + off + q * 16, zq, zq, zq, zq);
            }
          }
        }
      }
      fence_proxy_async();
      __syncwarp();
      if (lane == 0) mbar_arrive(BAR(B_KVREADY));
    }
  } else {
    asm volatile("setmaxnreg.inc.sync.aligned.u32 240;");
    const int w = warp >> 2, wq = warp & 3, t128 = tid & 127;
    const int g = lane >> 2, tq = lane & 3;
    const uint32_t area = sbase + (uint32_t)w * 65536u;
    const bool elect = (t128 == 0);
    PROF(w, 22);
    const uint32_t dbase = (sbase & 0x3FFFFu) >> 4;
    uint32_t xoff = (uint32_t)((m * 4 + p) * 18 + w) * 8192u + (uint32_t)t128 * 16u;
    uint32_t stash = area + (uint32_t)t128 * 16u;
    const uint32_t epoch_c = ld_relaxed(&g_epoch);
    auto xptr = [&](int slot, int jj) INL { return (uint4*)((char*)g_xbuf + ((xoff & ~1u) + (uint32_t)slot * 16384u + (uint32_t)jj * 2048u)); };
    uint32_t A[144];
    float rs0, rs1;
    auto release = [&](int st) INL {
      if (elect) { mbar_arrive_cluster(BAR(B_EMPTY + st), 0); mbar_arrive_cluster(BAR(B_EMPTY + st), 1); }
    };

    {
      const int row = wq * 16 + (lane & 7) + ((lane >> 3) & 1) * 8;
      const uint32_t rbase = area + row * 128;
      float s0[2][4] = {}, q0[2][4] = {}, q1[2][4] = {};
      const uint32_t ones = 0x3F803F80u;
#pragma unroll
      for (int b = 0; b < 8; b++) {
        mbar_wait(BAR(B_XFULL + w * 8 + b), 0);
        if (b == 0) PROF(w, 23);
        if (b == 7) PROF(w, 24);
#pragma unroll
        for (int kk = 0; kk < 4; kk++) {
          const int i = (b * 4 + kk) * 4;
          ldmatrix_x4(rbase + b * 8192 + (((kk * 2 + (lane >> 4)) ^ (row & 7)) << 4), A[i], A[i + 1], A[i + 2], A[i + 3]);
        }
#pragma unroll
        for (int kk = 0; kk < 4; kk++) {
          const int i = (b * 4 + kk) * 4;
          mma_16816(s0[kk & 1], A[i], A[i + 1], A[i + 2], A[i + 3], ones, ones);
          mma_16816(q0[kk & 1], A[i], A[i + 1], A[i + 2], A[i + 3], A[i], A[i + 2]);
          mma_16816(q1[kk & 1], A[i], A[i + 1], A[i + 2], A[i + 3], A[i + 1], A[i + 3]);
        }
      }
      const float mean0 = (s0[0][0] + s0[1][0]) * (1.f / 512.f), mean1 = (s0[0][2] + s0[1][2]) * (1.f / 512.f);
      const uint32_t m0 = pack_bf16(mean0, mean0), m1 = pack_bf16(mean1, mean1);
#pragma unroll
      for (int i = 0; i < 128; i += 2) {
        A[i] = hsub2_bf16(A[i], m0);
        A[i + 1] = hsub2_bf16(A[i + 1], m1);
      }
      float v0 = (g & 1) ? q0[0][1] + q0[1][1] : q0[0][0] + q0[1][0];
      float v1 = (g & 1) ? q1[0][3] + q1[1][3] : q1[0][2] + q1[1][2];
      const int src = 4 * g + (g >> 1);
      v0 = __shfl_sync(0xffffffffu, v0, src);
      v1 = __shfl_sync(0xffffffffu, v1, src);
      v0 = fmaxf(v0 * (1.f / 512.f) - mean0 * mean0, 0.f);
      v1 = fmaxf(v1 * (1.f / 512.f) - mean1 * mean1, 0.f);
      rs0 = rsqrtf(v0 + 1e-5f);
      rs1 = rsqrtf(v1 + 1e-5f);
      bar_sync(1 + w, 128);
      cluster_wait();
      asm volatile("" : "+r"(xoff), "+r"(stash));
      PROF(w, 0);
      release(6); release(7);
      if (elect) mbar_arrive(BAR(B_XDONE));
    }

    auto gu_chunk = [&](float (&acc)[32], int f, int slot, int xslot, int hb) INL {
      const float c0 = rs0 * -1.4426950408889634f, c1 = rs1 * -1.4426950408889634f;
      const float q0 = rs0 * rs0, q1 = rs1 * rs1;
      uint32_t h[4];
#pragma unroll
      for (int i = 0; i < 4; i++) {
        const float ga = acc[f * 8 + 2 * i], gb = acc[f * 8 + 2 * i + 1];
        const float ua = acc[16 + f * 8 + 2 * i], ub = acc[16 + f * 8 + 2 * i + 1];
        const float c = (i & 1) ? c1 : c0, q = (i & 1) ? q1 : q0;
        const float da = 1.f + ex2f(fminf(ga * c, 60.f)), db = 1.f + ex2f(fminf(gb * c, 60.f));
        const float rq = rcpf(da * db) * q;
        h[i] = tagged(pack_bf16(ga * ua * (db * rq), gb * ub * (da * rq)), xoff & 1u);
      }
      const int jj = hb * 2 + f;
      sts_u4(stash + slot * 8192 + jj * 2048, h[0], h[1], h[2], h[3]);
      stg_u4(xptr(xslot, jj), h[0], h[1], h[2], h[3]);
    };
    auto kv_stage = [&](float (&acc)[32], int c, int hb) INL {
      const int srow = wq * 16 + (lane & 7) + ((lane >> 3) & 1) * 8;
      const uint32_t base = area + (3 + c) * 8192 + srow * 128;
#pragma unroll
      for (int jj = 0; jj < 2; jj++) {
        const int a = c * 16 + jj * 8;
        uint32_t r0, r1, r2, r3;
        if (c == 0) {
          r0 = pack_bf16(phi_f(acc[a] * rs0), phi_f(acc[a + 1] * rs0));
          r1 = pack_bf16(phi_f(acc[a + 2] * rs1), phi_f(acc[a + 3] * rs1));
          r2 = pack_bf16(phi_f(acc[a + 4] * rs0), phi_f(acc[a + 5] * rs0));
          r3 = pack_bf16(phi_f(acc[a + 6] * rs1), phi_f(acc[a + 7] * rs1));
        } else {
          r0 = pack_bf16(acc[a] * rs0, acc[a + 1] * rs0);
          r1 = pack_bf16(acc[a + 2] * rs1, acc[a + 3] * rs1);
          r2 = pack_bf16(acc[a + 4] * rs0, acc[a + 5] * rs0);
          r3 = pack_bf16(acc[a + 6] * rs1, acc[a + 7] * rs1);
        }
        stmatrix_x4(base + (((hb * 4 + jj * 2 + (lane >> 4)) ^ (srow & 7)) << 4), r0, r1, r2, r3);
      }
    };
    auto signal = [&](int e) INL {
      __syncwarp();
      if (lane == 0) mbar_arrive(BAR(B_EV + w * 2 + e));
    };

    auto pp_wait = [&]() INL { bar_sync(3 + w, 256); };
    auto pp_pass = [&]() INL { bar_arrive(3 + (w ^ 1), 256); };
    if (w == 1) pp_pass();
#pragma unroll 1
    for (int t = 0; t < 5; t++) {
      const uint32_t ph = t & 1;
      const int kind = odd ? (t < 2 ? K_KV : K_GU) : (t < 4 ? K_GU : K_Q);
      const int slot = odd ? t - 2 : t, xslot = odd ? t + 4 : t;
      static_for<2>([&](auto hc) INL {
        constexpr int hb = decltype(hc)::value;
        float acc[32];
        pp_wait();
        static_for<4>([&](auto kc) INL {
          constexpr int kq = decltype(kc)::value, k = hb * 4 + kq;
          mbar_wait(BAR(B_FULL + k), ph);
          wgmma_fence();
          static_for<8>([&](auto kkc) INL {
            constexpr int kk = decltype(kkc)::value, i = (kq * 8 + kk) * 4;
            wgmma_n64_rs<CB, (kq | kk) != 0, desc_lo(stage_off(k) + kk * 1024, 8192), kHi64>(acc, A[i], A[i + 1], A[i + 2], A[i + 3], dbase);
            if (kq * 8 + kk == PPOS) pp_pass();
          });
          wgmma_commit();
          if (kq > 0) {
            wgmma_wait<1>();
            release(k - 1);
          }
        });
        wgmma_wait<0>();
        release(hb * 4 + 3);
        if (hb == 0 && t == 0) xoff |= (epoch_c & 1u) ^ 1u;
        if (kind == K_GU) {
          gu_chunk(acc, 0, slot, xslot, hb);
          gu_chunk(acc, 1, slot, xslot, hb);
        } else if (kind == K_KV) {
          if (hb == 0 && t == 0) sts_u4(stash + 5 * 8192, 0x3F803F80u, 0x3F803F80u, 0x3F803F80u, 0x3F803F80u);
          kv_stage(acc, 0, hb);
          kv_stage(acc, 1, hb);
          if (hb == 1) {
            float kvacc[36];
            const int par = (xoff & 1u) ^ 1u;
            fence_proxy_async();
            bar_sync(1 + w, 128);
            wgmma_fence();
            static_for<4>([&](auto kkc) INL {
              constexpr int kk = decltype(kkc)::value;
              wgmma_n72_ss_tt<kk != 0, desc_lo(3 * 8192 + kk * 2048, 0), desc_lo(4 * 8192 + kk * 2048, 8192 - kk * 2048)>(kvacc, dbase + w * 4096);
            });
            wgmma_commit();
            wgmma_wait<0>();
            float c[8];
#pragma unroll
            for (int i = 0; i < 8; i++)
              c[i] = wq == 0 ? kvacc[i] : (wq == 1 ? kvacc[8 + i] : (wq == 2 ? kvacc[16 + i] : kvacc[24 + i]));
            const int head = (2 * p + t) * 4 + wq;
            float* kvp = &g_kv[par][head][0][0];
            red_add_v2(kvp + g * 16 + 2 * tq, c[0], c[1]);
            red_add_v2(kvp + (g + 8) * 16 + 2 * tq, c[2], c[3]);
            red_add_v2(kvp + g * 16 + 8 + 2 * tq, c[4], c[5]);
            red_add_v2(kvp + (g + 8) * 16 + 8 + 2 * tq, c[6], c[7]);
            if (tq == 0) {
              red_add(&g_z[par][head][g], kvacc[32]);
              red_add(&g_z[par][head][g + 8], kvacc[34]);
            }
            signal(t);
          }
        } else {
          uint32_t aq[4][4];
#pragma unroll
          for (int c = 0; c < 4; c++) {
            const int a = c * 8;
            aq[c][0] = pack_bf16(phi_f(acc[a] * rs0), phi_f(acc[a + 1] * rs0));
            aq[c][1] = pack_bf16(phi_f(acc[a + 2] * rs1), phi_f(acc[a + 3] * rs1));
            aq[c][2] = pack_bf16(phi_f(acc[a + 4] * rs0), phi_f(acc[a + 5] * rs0));
            aq[c][3] = pack_bf16(phi_f(acc[a + 6] * rs1), phi_f(acc[a + 7] * rs1));
          }
          if (hb == 0) mbar_wait(BAR(B_KVREADY), 0);
          float nd[4][12];
          wgmma_fence();
          static_for<4>([&](auto cc) INL {
            constexpr int c = decltype(cc)::value;
            wgmma_n24_rs<desc_lo(5 * 8192 + (hb * 4 + c) * 768, 128)>(nd[c], aq[c][0], aq[c][1], aq[c][2], aq[c][3], dbase + w * 4096);
          });
          wgmma_commit();
          wgmma_wait<0>();
          if (hb == 1) bar_sync(1 + w, 128);
          const uint32_t tg = xoff & 1u;
#pragma unroll
          for (int c = 0; c < 4; c++) {
            const float i0 = __fdividef(1.f, nd[c][8] + 1e-6f), i1 = __fdividef(1.f, nd[c][10] + 1e-6f);
            aq[c][0] = tagged(pack_bf16(nd[c][0] * i0, nd[c][1] * i0), tg);
            aq[c][1] = tagged(pack_bf16(nd[c][2] * i1, nd[c][3] * i1), tg);
            aq[c][2] = tagged(pack_bf16(nd[c][4] * i0, nd[c][5] * i0), tg);
            aq[c][3] = tagged(pack_bf16(nd[c][6] * i1, nd[c][7] * i1), tg);
          }
#pragma unroll
          for (int c = 0; c < 4; c++) {
            stg_u4(xptr(4 + hb, c), aq[c][0], aq[c][1], aq[c][2], aq[c][3]);
            sts_u4(stash + (4 + hb) * 8192 + c * 2048, aq[c][0], aq[c][1], aq[c][2], aq[c][3]);
          }
        }
      });
      PROF(w, 1 + 2 * t);
    }
    PROF(w, 10);

    const int n_own = odd ? 3 : 6;
    auto load_a = [&](int kb) INL {
      if (kb < n_own) {
#pragma unroll
        for (int jj = 0; jj < 4; jj++) {
          const int i = (kb * 4 + jj) * 4;
          lds_u4(stash + kb * 8192 + jj * 2048, A[i], A[i + 1], A[i + 2], A[i + 3]);
        }
      } else {
        const int xs = odd ? kb - 3 : kb;
#pragma unroll
        for (int jj = 0; jj < 4; jj++) {
          const int i = (kb * 4 + jj) * 4;
          ldg_poll_u4(xptr(xs, jj), A[i], A[i + 1], A[i + 2], A[i + 3]);
        }
      }
    };
    auto fix_a = [&](int kb) INL {
      if (kb >= n_own) {
        const int xs = odd ? kb - 3 : kb;
        recv_group<4>(xptr(xs, 0), &A[kb * 16], xoff & 1u);
      }
    };
#pragma unroll
    for (int kb = 0; kb < 7; kb++) load_a(kb);
    PROF(w, 11);

    const uint32_t ooff = (uint32_t)(m * 128 + w * 64 + wq * 16 + (lane >> 3)) * kD + odd * 256 + p * 64 + (lane & 7) * 8;
    float acc2[2][32];
    uint32_t poff = (uint32_t)((m * 2 + odd) * 24 + w) * 8192u + (uint32_t)t128 * 16u;
    asm volatile("" : "+r"(poff));
    auto pptr = [&](int dest, int sl) INL { return (uint4*)((char*)g_pbuf + (poff + (uint32_t)(dest * 3 + sl) * 16384u)); };
    uint32_t P[3][16];
    uint4 xr[4];
    auto send = [&](float (&acc)[32], int bi) INL {
      uint4* dst = pptr((p + 1 + bi) & 3, bi);
#pragma unroll
      for (int q = 0; q < 4; q++)
        stg_u4(dst + q * 128, tagged(pack_bf16(acc[q * 8], acc[q * 8 + 1]), xoff & 1u), tagged(pack_bf16(acc[q * 8 + 2], acc[q * 8 + 3]), xoff & 1u),
               tagged(pack_bf16(acc[q * 8 + 4], acc[q * 8 + 5]), xoff & 1u), tagged(pack_bf16(acc[q * 8 + 6], acc[q * 8 + 7]), xoff & 1u));
      PROF(w, 12 + 2 * bi);
    };
    auto fetch = [&](int sl) INL {
#pragma unroll
      for (int q = 0; q < 4; q++)
        asm volatile("cp.async.cg.shared.global [%0], [%1], 16;" ::"r"(stash + (3 + sl) * 8192 + q * 2048), "l"(pptr(p, sl) + q * 128) : "memory");
    };
    auto collect = [&](int sl) INL {
      if (sl == 0) asm volatile("cp.async.wait_group 1;" ::: "memory");
      if (sl == 2) asm volatile("cp.async.wait_group 0;" ::: "memory");
#pragma unroll
      for (int q = 0; q < 4; q++) lds_u4(stash + (3 + sl) * 8192 + q * 2048, P[sl][q * 4], P[sl][q * 4 + 1], P[sl][q * 4 + 2], P[sl][q * 4 + 3]);
      recv_group<4>(pptr(p, sl), &P[sl][0], xoff & 1u);
    };
    static_for<36>([&](auto ic) INL {
      constexpr int i = decltype(ic)::value, bi = p2_bi(i), kb = p2_kb(i), j = i >> 1, st = j & 7;
      if (i == 9) { load_a(7); load_a(8); }
      if (i == 14) PROF(w, 2);
      if (bi == 0 && kb >= 3) fix_a(kb);
      if (i == 15) PROF(w, 4);
      if (i == 7) PROF(w, 6);
      if (i == 0 || i == 7 || i == 14 || i == 18 || i == 27) pp_wait();
      if ((i & 1) == 0) mbar_wait(BAR(B_FULL + st), (5 + (j >> 3)) & 1);
      wgmma_fence();
      static_for<4>([&](auto kkc) INL {
        constexpr int kk = decltype(kkc)::value, a = (kb * 4 + kk) * 4;
        wgmma_n64_rs<CB, (kb | kk) != 0, desc_lo(stage_off(st) + (i & 1) * 8192 + kk * 2048, 0), kHi128>(acc2[bi & 1], A[a], A[a + 1], A[a + 2], A[a + 3], dbase);
      });
      wgmma_commit();
      if (i == 6 - QPOS || i == 13 - QPOS || i == 17 - QPOS || i == 26 - QPOS || (i == 35 - QPOS && w == 0)) pp_pass();
      if (i > 0) {
        wgmma_wait<1>();
        if ((i & 1) == 0 && j - 1 <= 9) release((j - 1) & 7);
      }
      if constexpr (i == 17) { send(acc2[0], 0); wgmma_wait<0>(); send(acc2[1], 1); }
      if constexpr (i == 26) { wgmma_wait<0>(); send(acc2[0], 2); }
      if constexpr (i == 28) {
#pragma unroll
        for (int q = 0; q < 4; q++) xr[q] = __ldg((const uint4*)(x + ooff + q * 4 * kD));
      }
      if constexpr (i == 27) { fetch(0); fetch(1); asm volatile("cp.async.commit_group;" ::: "memory"); }
      if constexpr (i == FPOS) { fetch(2); asm volatile("cp.async.commit_group;" ::: "memory"); }
    });
    PROF(w, 17);
    collect(0);
    collect(1);
#pragma unroll
    for (int q = 0; q < 16; q++) {
      acc2[0][2 * q] = __uint_as_float(P[0][q] << 16) + __uint_as_float(P[1][q] << 16);
      acc2[0][2 * q + 1] = __uint_as_float(P[0][q] & 0xffff0000u) + __uint_as_float(P[1][q] & 0xffff0000u);
    }
    PROF(w, 13);
    collect(2);
    PROF(w, 15);
    wgmma_wait<0>();
    PROF(w, 18);
    {
      const uint32_t tile = area + wq * 4352;
#pragma unroll
      for (int q = 0; q < 8; q++) {
        float rr[4];
#pragma unroll
        for (int e = 0; e < 4; e++) rr[e] = acc2[1][q * 4 + e] + acc2[0][q * 4 + e];
        rr[0] += __uint_as_float(P[2][2 * q] << 16);
        rr[1] += __uint_as_float(P[2][2 * q] & 0xffff0000u);
        rr[2] += __uint_as_float(P[2][2 * q + 1] << 16);
        rr[3] += __uint_as_float(P[2][2 * q + 1] & 0xffff0000u);
        const uint32_t ad = tile + g * 272 + q * 32 + tq * 8;
        asm volatile("st.shared.v2.f32 [%0], {%1,%2};" ::"r"(ad), "f"(rr[0]), "f"(rr[1]) : "memory");
        asm volatile("st.shared.v2.f32 [%0], {%1,%2};" ::"r"(ad + 8 * 272), "f"(rr[2]), "f"(rr[3]) : "memory");
      }
      __syncwarp();
#pragma unroll
      for (int q = 0; q < 4; q++) {
        const uint32_t ad = tile + ((lane >> 3) + 4 * q) * 272 + (lane & 7) * 32;
        uint32_t v[8];
        lds_u4(ad, v[0], v[1], v[2], v[3]);
        lds_u4(ad + 16, v[4], v[5], v[6], v[7]);
        const uint32_t xv[4] = {xr[q].x, xr[q].y, xr[q].z, xr[q].w};
        uint32_t o[4];
#pragma unroll
        for (int e = 0; e < 4; e++)
          o[e] = pack_bf16(__uint_as_float(v[2 * e]) + __uint_as_float(xv[e] << 16), __uint_as_float(v[2 * e + 1]) + __uint_as_float(xv[e] & 0xffff0000u));
        stg_u4(out + ooff + q * 4 * kD, o[0], o[1], o[2], o[3]);
      }
    }
    PROF(w, 19);
    if (tid == 0) {
      const uint32_t old = atomicAdd(&g_done, 1u);
      if ((old & 127u) == 127u) st_relaxed(&g_epoch, ld_relaxed(&g_epoch) + 1u);
    }
  }
#undef BAR
}

typedef CUresult (*EncodeFn)(CUtensorMap*, CUtensorMapDataType, cuuint32_t, void*, const cuuint64_t*, const cuuint64_t*,
                             const cuuint32_t*, const cuuint32_t*, CUtensorMapInterleave, CUtensorMapSwizzle,
                             CUtensorMapL2promotion, CUtensorMapFloatOOBfill);

void make_map(EncodeFn enc, CUtensorMap* tm, const void* ptr, int rows, int cols, bool narrow) {
  cuuint64_t gd[2] = {(cuuint64_t)cols, (cuuint64_t)rows};
  cuuint64_t gs[1] = {(cuuint64_t)cols * 2};
  cuuint32_t bd[2] = {narrow ? 32u : 64u, narrow ? 128u : 64u};
  cuuint32_t es[2] = {1, 1};
  enc(tm, CU_TENSOR_MAP_DATA_TYPE_BFLOAT16, 2, const_cast<void*>(ptr), gd, gs, bd, es, CU_TENSOR_MAP_INTERLEAVE_NONE,
      narrow ? CU_TENSOR_MAP_SWIZZLE_64B : CU_TENSOR_MAP_SWIZZLE_128B, CU_TENSOR_MAP_L2_PROMOTION_L2_256B, CU_TENSOR_MAP_FLOAT_OOB_FILL_NONE);
}

}

extern "C" void kernel_launch(void* const* d_in, const int* in_sizes, int n_in, void* d_out, int out_size) {
  static EncodeFn enc = nullptr;
  static bool const_base = false;
  if (!enc) {
    void* fn = nullptr;
    cudaDriverEntryPointQueryResult qr;
    cudaGetDriverEntryPoint("cuTensorMapEncodeTiled", &fn, cudaEnableDefault, &qr);
    enc = (EncodeFn)fn;
    cudaFuncSetAttribute(fused_kernel<true>, cudaFuncAttributeMaxDynamicSharedMemorySize, kSmemBytes);
    cudaFuncSetAttribute(fused_kernel<false>, cudaFuncAttributeMaxDynamicSharedMemorySize, kSmemBytes);
    int dev = 0, reserved = 0;
    cudaFuncAttributes fa;
    cudaGetDevice(&dev);
    cudaDeviceGetAttribute(&reserved, cudaDevAttrReservedSharedMemoryPerBlock, dev);
    const_base = cudaFuncGetAttributes(&fa, fused_kernel<true>) == cudaSuccess && fa.sharedSizeBytes == 0 && reserved == (int)kSmemBase;
  }
  CUtensorMap tm_x, tm_wqkv, tm_w1, tm_w3, tm_w2, tm_wo;
  make_map(enc, &tm_x, d_in[0], kS, kD, false);
  make_map(enc, &tm_wqkv, d_in[1], kD, 3 * kD, true);
  make_map(enc, &tm_wo, d_in[2], kD, kD, false);
  make_map(enc, &tm_w1, d_in[4], kD, kF, true);
  make_map(enc, &tm_w3, d_in[5], kD, kF, true);
  make_map(enc, &tm_w2, d_in[6], kF, kD, false);
  if (const_base)
    fused_kernel<true><<<128, 384, kSmemBytes>>>(tm_x, tm_wqkv, tm_w1, tm_w3, tm_w2, tm_wo, (const __nv_bfloat16*)d_in[0], (__nv_bfloat16*)d_out);
  else
    fused_kernel<false><<<128, 384, kSmemBytes>>>(tm_x, tm_wqkv, tm_w1, tm_w3, tm_w2, tm_wo, (const __nv_bfloat16*)d_in[0], (__nv_bfloat16*)d_out);
}
```
